```python
import torch

def _softmax(x, axis=-1):
    return torch.softmax(x, dim=axis)

def _gelu(x):
    return torch.nn.functional.gelu(x, approximate='tanh')

def _silu(x):
    return torch.nn.functional.silu(x)

def _sigmoid(x):
    return torch.sigmoid(x)

def _layernorm(x, axis=-1, eps=1e-05):
    m = x.mean(dim=axis, keepdim=True)
    v = x.var(dim=axis, keepdim=True, unbiased=False)
    return (x - m) / torch.sqrt(v + eps)

def _scatter_add(tgt, idx, src, axis=0):
    return tgt.clone().index_add_(axis, idx, src)

def _segment_sum(src, seg, n):
    out = torch.zeros((n,) + src.shape[1:], dtype=src.dtype)
    return out.index_add_(0, seg, src)

def _pad(x, pw):
    flat = tuple((v for pair in reversed(pw) for v in pair))
    return torch.nn.functional.pad(x, flat)
kernel_name = 'gated_mix__memory_aug_recurrent_mem_tr__dense_activation_relu__prompt'

def setup_inputs():

    _w = lambda a: (lambda t: t.to(torch.bfloat16) if t.is_floating_point() else t)(torch.as_tensor(a))

    def _A_setup():
        B, S, Dm = (1, 2048, 448)
        H, Dh = (16, 256)
        M, seg = (8, 32)
        seg = min(seg, S)
        S = S // seg * seg
        return {'x': _w((lambda *s: torch.randn(*s, dtype=torch.bfloat16) * 0.05)(B, S, Dm)), 'mem0': _w((lambda *s: torch.randn(*s, dtype=torch.bfloat16) * 0.8)(B, M, Dm)), 'Wq': _w((lambda *s: torch.randn(*s, dtype=torch.bfloat16) * 3.2)(Dm, H, Dh) * Dm ** (-0.5)), 'Wk': _w((lambda *s: torch.randn(*s, dtype=torch.bfloat16) * 3.2)(Dm, H, Dh) * Dm ** (-0.5)), 'Wv': _w((lambda *s: torch.randn(*s, dtype=torch.bfloat16) * 0.8)(Dm, H, Dh) * Dm ** (-0.5)), 'Wo': _w((lambda *s: torch.randn(*s, dtype=torch.bfloat16) * 0.8)(H, Dh, Dm) * (H * Dh) ** (-0.5)), 'seg_len': seg}
    _A_in = _A_setup()

    def _B_setup():
        B, S, D, Dff = (1, 2048, 448, 1792)
        return {'x': _w((lambda *s: torch.randn(*s, dtype=torch.bfloat16) * 0.05)(B, S, D)), 'w1': _w((lambda *s: torch.randn(*s, dtype=torch.bfloat16) * 0.05)(D, Dff)), 'w2': _w((lambda *s: torch.randn(*s, dtype=torch.bfloat16) * 0.05)(Dff, D))}
    _B_in = _B_setup()
    return {'A_x': _A_in['x'], 'A_mem0': _A_in['mem0'], 'A_Wq': _A_in['Wq'], 'A_Wk': _A_in['Wk'], 'A_Wv': _A_in['Wv'], 'A_Wo': _A_in['Wo'], 'A_seg_len': _A_in['seg_len'], 'B_x': _B_in['x'], 'B_w1': _B_in['w1'], 'B_w2': _B_in['w2'], 'gate_w': _w((lambda *s: torch.randn(*s, dtype=torch.bfloat16) * 0.05)(448) * 16.0)}

def reference(A_x, A_mem0, A_Wq, A_Wk, A_Wv, A_Wo, A_seg_len, B_x, B_w1, B_w2, gate_w):

    def _A_ref(x, mem0, Wq, Wk, Wv, Wo, seg_len):
        B, S, Dm = x.shape
        H, Dh = (Wq.shape[1], Wq.shape[2])
        M = mem0.shape[1]
        scale = Dh ** (-0.5)
        n_seg = S // seg_len
        L = M + seg_len
        idx = torch.arange(L)
        mask = (idx[:, None] < M) | (idx[:, None] >= idx[None, :])
        mem = mem0
        outs = []
        for s in range(n_seg):
            xs = x[:, s * seg_len:(s + 1) * seg_len, :].clone()
            h = torch.concatenate([mem, xs], axis=1)
            q = torch.einsum('btd,dhe->bhte', h, Wq)
            k = torch.einsum('btd,dhe->bhte', h, Wk)
            v = torch.einsum('btd,dhe->bhte', h, Wv)
            scores = torch.einsum('bhqe,bhke->bhqk', q, k) * scale
            scores = torch.where(mask[None, None], scores, -1000000000.0)
            p = _softmax(scores, axis=-1)
            o = torch.einsum('bhqk,bhke->bhqe', p, v)
            o = torch.einsum('bhte,hed->btd', o, Wo)
            mem = o[:, :M, :].clone()
            outs.append(o[:, M:, :])
        return torch.concatenate(outs, axis=1)

    def _B_ref(x, w1, w2):
        h = torch.einsum('bsd,df->bsf', x, w1)
        zero = torch.zeros_like(h)
        h = torch.maximum(h, zero)
        return torch.einsum('bsf,fd->bsd', h, w2)
    x = A_x
    g = _sigmoid((x * gate_w).sum(-1, keepdims=True))
    a = _A_ref(x, A_mem0, A_Wq, A_Wk, A_Wv, A_Wo, A_seg_len)
    b = _B_ref(x, B_w1, B_w2)
    return g * a + (1 - g) * b
```

```cpp
#include <cuda_runtime.h>
#include <cuda_bf16.h>
#include <cuda.h>
#include <stdint.h>

namespace {

#define DEVI __device__ __forceinline__

constexpr int SEQ = 2048, DM = 448, NH = 16, DH = 256, NSEG = 64, DFF = 1792;
constexpr float SC2 = 1.4426950408889634f / 16.0f;
constexpr float MASKV = -1.6e10f;
constexpr uint32_t SPIN_LIMIT = 1u << 21;

#define D_M 1200
#define D_S 470

__device__ __align__(1024) uint8_t g_mslot[4][7168];
__device__ __align__(1024) float g_smm[4][NH][7][64];
__device__ __align__(1024) float g_smx[4][NH][7][256];
__device__ __align__(1024) float g_sacc[8][NH][1280];
__device__ __align__(1024) uint32_t g_sflag[8][NH][8];
__device__ __align__(1024) float g_stash[SEQ * DM];
__device__ __align__(1024) float g_b[SEQ * DM];
__device__ __align__(1024) __nv_bfloat16 g_h[SEQ * DFF];
__device__ int g_err;
#define TS(i)

DEVI uint32_t smem_u32(const void* p) { return (uint32_t)__cvta_generic_to_shared(p); }
DEVI uint32_t clk() { uint32_t c; asm volatile("mov.u32 %0, %%clock;" : "=r"(c) :: "memory"); return c; }
DEVI void mbar_init(uint32_t bar, uint32_t cnt) { asm volatile("mbarrier.init.shared::cta.b64 [%0], %1;" :: "r"(bar), "r"(cnt) : "memory"); }
DEVI void mbar_expect(uint32_t bar, uint32_t bytes) { asm volatile("mbarrier.arrive.expect_tx.shared::cta.b64 _, [%0], %1;" :: "r"(bar), "r"(bytes) : "memory"); }
DEVI void mbar_arrive(uint32_t bar) { asm volatile("mbarrier.arrive.shared::cta.b64 _, [%0];" :: "r"(bar) : "memory"); }
DEVI bool mbar_try(uint32_t bar, uint32_t par) {
  uint32_t ok;
  asm volatile("{\n.reg .pred p;\nmbarrier.try_wait.parity.shared::cta.b64 p, [%1], %2;\nselp.u32 %0,1,0,p;\n}"
               : "=r"(ok) : "r"(bar), "r"(par) : "memory");
  return ok;
}
DEVI uint32_t lds32v(uint32_t a) { uint32_t v; asm volatile("ld.volatile.shared::cta.u32 %0, [%1];" : "=r"(v) : "r"(a) : "memory"); return v; }
DEVI void sts32v(uint32_t a, uint32_t v) { asm volatile("st.volatile.shared::cta.u32 [%0], %1;" :: "r"(a), "r"(v) : "memory"); }
DEVI bool spin_fail(uint32_t& it, uint32_t dead) {
  if ((++it & 63) == 0) {
    if (lds32v(dead)) return true;
    if (it > SPIN_LIMIT) { sts32v(dead, 1); g_err = 1; return true; }
  }
  return false;
}
DEVI void mbar_wait(uint32_t bar, uint32_t par, uint32_t dead) {
  uint32_t it = 0;
  while (!mbar_try(bar, par)) { if (spin_fail(it, dead)) break; }
}
DEVI void bar_sync(int id, int n) { asm volatile("bar.sync %0, %1;" :: "r"(id), "r"(n) : "memory"); }
DEVI void bar_arrive(int id, int n) { asm volatile("bar.arrive %0, %1;" :: "r"(id), "r"(n) : "memory"); }
DEVI void cluster_arrive() { asm volatile("barrier.cluster.arrive.release.aligned;" ::: "memory"); }
DEVI void cluster_wait() { asm volatile("barrier.cluster.wait.acquire.aligned;" ::: "memory"); }
DEVI uint32_t mapa(uint32_t a, uint32_t r) { uint32_t o; asm("mapa.shared::cluster.u32 %0, %1, %2;" : "=r"(o) : "r"(a), "r"(r)); return o; }
DEVI uint32_t pack2(float lo, float hi) { uint32_t r; asm("cvt.rn.bf16x2.f32 %0, %1, %2;" : "=r"(r) : "f"(hi), "f"(lo)); return r; }
DEVI float ex2(float x) { float y; asm("ex2.approx.ftz.f32 %0, %1;" : "=f"(y) : "f"(x)); return y; }
DEVI float bf_lo(uint32_t v) { return __uint_as_float(v << 16); }
DEVI float bf_hi(uint32_t v) { return __uint_as_float(v & 0xffff0000u); }
DEVI void ldsm4(uint32_t (&r)[4], uint32_t a) {
  asm volatile("ldmatrix.sync.aligned.m8n8.x4.shared.b16 {%0,%1,%2,%3}, [%4];" : "=r"(r[0]), "=r"(r[1]), "=r"(r[2]), "=r"(r[3]) : "r"(a) : "memory");
}
DEVI void stsm4t(uint32_t a, uint32_t r0, uint32_t r1, uint32_t r2, uint32_t r3) {
  asm volatile("stmatrix.sync.aligned.m8n8.x4.trans.shared.b16 [%0], {%1,%2,%3,%4};" :: "r"(a), "r"(r0), "r"(r1), "r"(r2), "r"(r3) : "memory");
}
DEVI void stsm2t(uint32_t a, uint32_t r0, uint32_t r1) {
  asm volatile("stmatrix.sync.aligned.m8n8.x2.trans.shared.b16 [%0], {%1,%2};" :: "r"(a), "r"(r0), "r"(r1) : "memory");
}
DEVI void mma16(float (&c)[4], uint32_t a0, uint32_t a1, uint32_t a2, uint32_t a3, uint32_t b0, uint32_t b1) {
  asm("mma.sync.aligned.m16n8k16.row.col.f32.bf16.bf16.f32 {%0,%1,%2,%3},{%4,%5,%6,%7},{%8,%9},{%0,%1,%2,%3};"
      : "+f"(c[0]), "+f"(c[1]), "+f"(c[2]), "+f"(c[3]) : "r"(a0), "r"(a1), "r"(a2), "r"(a3), "r"(b0), "r"(b1));
}
DEVI void mma8(float (&c)[4], uint32_t a0, uint32_t a1, uint32_t b0) {
  asm("mma.sync.aligned.m16n8k8.row.col.f32.bf16.bf16.f32 {%0,%1,%2,%3},{%4,%5},{%6},{%0,%1,%2,%3};"
      : "+f"(c[0]), "+f"(c[1]), "+f"(c[2]), "+f"(c[3]) : "r"(a0), "r"(a1), "r"(b0));
}
DEVI void wg_fence() { asm volatile("wgmma.fence.sync.aligned;" ::: "memory"); }
DEVI void wg_commit() { asm volatile("wgmma.commit_group.sync.aligned;" ::: "memory"); }
template <int N> DEVI void wg_wait() { asm volatile("wgmma.wait_group.sync.aligned %0;" :: "n"(N) : "memory"); }
template <int N> DEVI void reg_fence(float (&d)[N]) {
#pragma unroll
  for (int i = 0; i < N; i++) asm volatile("" : "+f"(d[i]) :: "memory");
}
DEVI uint64_t desc128(uint32_t addr, uint32_t lbo16) {
  return (uint64_t)((addr >> 4) & 0x3fff) | ((uint64_t)lbo16 << 16) | (64ull << 32) | (1ull << 62);
}
DEVI void tma2d(uint32_t dst, const CUtensorMap* tm, int c0, int c1, uint32_t bar) {
  asm volatile("cp.async.bulk.tensor.2d.shared::cluster.global.mbarrier::complete_tx::bytes [%0], [%1, {%2, %3}], [%4];"
               :: "r"(dst), "l"(tm), "r"(c0), "r"(c1), "r"(bar) : "memory");
}
DEVI void tma2d_mc(uint32_t dst, const CUtensorMap* tm, int c0, int c1, uint32_t bar) {
  asm volatile("cp.async.bulk.tensor.2d.shared::cluster.global.mbarrier::complete_tx::bytes.multicast::cluster [%0], [%1, {%2, %3}], [%4], %5;"
               :: "r"(dst), "l"(tm), "r"(c0), "r"(c1), "r"(bar), "h"((uint16_t)0xffff) : "memory");
}
DEVI void bulk_mc(uint32_t dst, const void* src, uint32_t bytes, uint32_t bar) {
  asm volatile("cp.async.bulk.shared::cluster.global.mbarrier::complete_tx::bytes.multicast::cluster [%0], [%1], %2, [%3], %4;"
               :: "r"(dst), "l"(src), "r"(bytes), "r"(bar), "h"((uint16_t)0xffff) : "memory");
}
DEVI void st_async4(uint32_t a, float x, float y, float z, float w, uint32_t bar) {
  asm volatile("st.async.weak.shared::cluster.mbarrier::complete_tx::bytes.v4.f32 [%0], {%1,%2,%3,%4}, [%5];"
               :: "r"(a), "f"(x), "f"(y), "f"(z), "f"(w), "r"(bar) : "memory");
}
DEVI void ldg2r(uint32_t& x, uint32_t& y, const void* p) { asm volatile("ld.relaxed.gpu.global.v2.u32 {%0,%1}, [%2];" : "=r"(x), "=r"(y) : "l"(p) : "memory"); }
DEVI void stg2r(void* p, uint32_t x, uint32_t y) { asm volatile("st.relaxed.gpu.global.v2.u32 [%0], {%1,%2};" :: "l"(p), "r"(x), "r"(y) : "memory"); }
DEVI void stg16r(void* p, uint16_t v) { asm volatile("st.relaxed.gpu.global.u16 [%0], %1;" :: "l"(p), "h"(v) : "memory"); }
DEVI void red2(float* p, float x, float y) { asm volatile("red.relaxed.gpu.global.add.v2.f32 [%0], {%1,%2};" :: "l"(p), "f"(x), "f"(y) : "memory"); }
DEVI float lds_f(uint32_t a) { float v; asm volatile("ld.shared.f32 %0, [%1];" : "=f"(v) : "r"(a) : "memory"); return v; }
DEVI float2 lds_f2(uint32_t a) { float2 v; asm volatile("ld.shared.v2.f32 {%0,%1}, [%2];" : "=f"(v.x), "=f"(v.y) : "r"(a) : "memory"); return v; }
DEVI float4 lds_f4(uint32_t a) { float4 v; asm volatile("ld.shared.v4.f32 {%0,%1,%2,%3}, [%4];" : "=f"(v.x), "=f"(v.y), "=f"(v.z), "=f"(v.w) : "r"(a) : "memory"); return v; }
DEVI uint2 lds_u2(uint32_t a) { uint2 v; asm volatile("ld.shared.v2.u32 {%0,%1}, [%2];" : "=r"(v.x), "=r"(v.y) : "r"(a) : "memory"); return v; }
DEVI uint4 lds_u4(uint32_t a) { uint4 v; asm volatile("ld.shared.v4.u32 {%0,%1,%2,%3}, [%4];" : "=r"(v.x), "=r"(v.y), "=r"(v.z), "=r"(v.w) : "r"(a) : "memory"); return v; }
DEVI void sts_f2(uint32_t a, float x, float y) { asm volatile("st.shared.v2.f32 [%0], {%1,%2};" :: "r"(a), "f"(x), "f"(y) : "memory"); }
DEVI void sts_u2(uint32_t a, uint32_t x, uint32_t y) { asm volatile("st.shared.v2.u32 [%0], {%1,%2};" :: "r"(a), "r"(x), "r"(y) : "memory"); }
DEVI void sts_u4(uint32_t a, uint32_t x, uint32_t y, uint32_t z, uint32_t w) { asm volatile("st.shared.v4.u32 [%0], {%1,%2,%3,%4};" :: "r"(a), "r"(x), "r"(y), "r"(z), "r"(w) : "memory"); }
DEVI uint32_t tagf(float v, uint32_t tag) { return (__float_as_uint(v) & ~3u) | tag; }
DEVI float qmax(float v) { v = fmaxf(v, __shfl_xor_sync(0xffffffffu, v, 1)); return fmaxf(v, __shfl_xor_sync(0xffffffffu, v, 2)); }
DEVI float qsum(float v) { v += __shfl_xor_sync(0xffffffffu, v, 1); return v + __shfl_xor_sync(0xffffffffu, v, 2); }

__device__ __forceinline__ void wgmma_n224_kk(float (&d)[112], uint64_t da, uint64_t db, int sc) {
  asm volatile("{\n.reg .pred p;\nsetp.ne.b32 p, %114, 0;\n"
    "wgmma.mma_async.sync.aligned.m64n224k16.f32.bf16.bf16 {%0,%1,%2,%3,%4,%5,%6,%7,%8,%9,%10,%11,%12,%13,%14,%15,%16,%17,%18,%19,%20,%21,%22,%23,%24,%25,%26,%27,%28,%29,%30,%31,%32,%33,%34,%35,%36,%37,%38,%39,%40,%41,%42,%43,%44,%45,%46,%47,%48,%49,%50,%51,%52,%53,%54,%55,%56,%57,%58,%59,%60,%61,%62,%63,%64,%65,%66,%67,%68,%69,%70,%71,%72,%73,%74,%75,%76,%77,%78,%79,%80,%81,%82,%83,%84,%85,%86,%87,%88,%89,%90,%91,%92,%93,%94,%95,%96,%97,%98,%99,%100,%101,%102,%103,%104,%105,%106,%107,%108,%109,%110,%111}, %112, %113, p, 1, 1, 0, 0;\n}"
    : "+f"(d[0]),"+f"(d[1]),"+f"(d[2]),"+f"(d[3]),"+f"(d[4]),"+f"(d[5]),"+f"(d[6]),"+f"(d[7]),"+f"(d[8]),"+f"(d[9]),"+f"(d[10]),"+f"(d[11]),"+f"(d[12]),"+f"(d[13]),"+f"(d[14]),"+f"(d[15]),"+f"(d[16]),"+f"(d[17]),"+f"(d[18]),"+f"(d[19]),"+f"(d[20]),"+f"(d[21]),"+f"(d[22]),"+f"(d[23]),"+f"(d[24]),"+f"(d[25]),"+f"(d[26]),"+f"(d[27]),"+f"(d[28]),"+f"(d[29]),"+f"(d[30]),"+f"(d[31]),"+f"(d[32]),"+f"(d[33]),"+f"(d[34]),"+f"(d[35]),"+f"(d[36]),"+f"(d[37]),"+f"(d[38]),"+f"(d[39]),"+f"(d[40]),"+f"(d[41]),"+f"(d[42]),"+f"(d[43]),"+f"(d[44]),"+f"(d[45]),"+f"(d[46]),"+f"(d[47]),"+f"(d[48]),"+f"(d[49]),"+f"(d[50]),"+f"(d[51]),"+f"(d[52]),"+f"(d[53]),"+f"(d[54]),"+f"(d[55]),"+f"(d[56]),"+f"(d[57]),"+f"(d[58]),"+f"(d[59]),"+f"(d[60]),"+f"(d[61]),"+f"(d[62]),"+f"(d[63]),"+f"(d[64]),"+f"(d[65]),"+f"(d[66]),"+f"(d[67]),"+f"(d[68]),"+f"(d[69]),"+f"(d[70]),"+f"(d[71]),"+f"(d[72]),"+f"(d[73]),"+f"(d[74]),"+f"(d[75]),"+f"(d[76]),"+f"(d[77]),"+f"(d[78]),"+f"(d[79]),"+f"(d[80]),"+f"(d[81]),"+f"(d[82]),"+f"(d[83]),"+f"(d[84]),"+f"(d[85]),"+f"(d[86]),"+f"(d[87]),"+f"(d[88]),"+f"(d[89]),"+f"(d[90]),"+f"(d[91]),"+f"(d[92]),"+f"(d[93]),"+f"(d[94]),"+f"(d[95]),"+f"(d[96]),"+f"(d[97]),"+f"(d[98]),"+f"(d[99]),"+f"(d[100]),"+f"(d[101]),"+f"(d[102]),"+f"(d[103]),"+f"(d[104]),"+f"(d[105]),"+f"(d[106]),"+f"(d[107]),"+f"(d[108]),"+f"(d[109]),"+f"(d[110]),"+f"(d[111])
    : "l"(da),"l"(db),"r"(sc));
}
__device__ __forceinline__ void wgmma_n224_mk(float (&d)[112], uint64_t da, uint64_t db, int sc) {
  asm volatile("{\n.reg .pred p;\nsetp.ne.b32 p, %114, 0;\n"
    "wgmma.mma_async.sync.aligned.m64n224k16.f32.bf16.bf16 {%0,%1,%2,%3,%4,%5,%6,%7,%8,%9,%10,%11,%12,%13,%14,%15,%16,%17,%18,%19,%20,%21,%22,%23,%24,%25,%26,%27,%28,%29,%30,%31,%32,%33,%34,%35,%36,%37,%38,%39,%40,%41,%42,%43,%44,%45,%46,%47,%48,%49,%50,%51,%52,%53,%54,%55,%56,%57,%58,%59,%60,%61,%62,%63,%64,%65,%66,%67,%68,%69,%70,%71,%72,%73,%74,%75,%76,%77,%78,%79,%80,%81,%82,%83,%84,%85,%86,%87,%88,%89,%90,%91,%92,%93,%94,%95,%96,%97,%98,%99,%100,%101,%102,%103,%104,%105,%106,%107,%108,%109,%110,%111}, %112, %113, p, 1, 1, 1, 0;\n}"
    : "+f"(d[0]),"+f"(d[1]),"+f"(d[2]),"+f"(d[3]),"+f"(d[4]),"+f"(d[5]),"+f"(d[6]),"+f"(d[7]),"+f"(d[8]),"+f"(d[9]),"+f"(d[10]),"+f"(d[11]),"+f"(d[12]),"+f"(d[13]),"+f"(d[14]),"+f"(d[15]),"+f"(d[16]),"+f"(d[17]),"+f"(d[18]),"+f"(d[19]),"+f"(d[20]),"+f"(d[21]),"+f"(d[22]),"+f"(d[23]),"+f"(d[24]),"+f"(d[25]),"+f"(d[26]),"+f"(d[27]),"+f"(d[28]),"+f"(d[29]),"+f"(d[30]),"+f"(d[31]),"+f"(d[32]),"+f"(d[33]),"+f"(d[34]),"+f"(d[35]),"+f"(d[36]),"+f"(d[37]),"+f"(d[38]),"+f"(d[39]),"+f"(d[40]),"+f"(d[41]),"+f"(d[42]),"+f"(d[43]),"+f"(d[44]),"+f"(d[45]),"+f"(d[46]),"+f"(d[47]),"+f"(d[48]),"+f"(d[49]),"+f"(d[50]),"+f"(d[51]),"+f"(d[52]),"+f"(d[53]),"+f"(d[54]),"+f"(d[55]),"+f"(d[56]),"+f"(d[57]),"+f"(d[58]),"+f"(d[59]),"+f"(d[60]),"+f"(d[61]),"+f"(d[62]),"+f"(d[63]),"+f"(d[64]),"+f"(d[65]),"+f"(d[66]),"+f"(d[67]),"+f"(d[68]),"+f"(d[69]),"+f"(d[70]),"+f"(d[71]),"+f"(d[72]),"+f"(d[73]),"+f"(d[74]),"+f"(d[75]),"+f"(d[76]),"+f"(d[77]),"+f"(d[78]),"+f"(d[79]),"+f"(d[80]),"+f"(d[81]),"+f"(d[82]),"+f"(d[83]),"+f"(d[84]),"+f"(d[85]),"+f"(d[86]),"+f"(d[87]),"+f"(d[88]),"+f"(d[89]),"+f"(d[90]),"+f"(d[91]),"+f"(d[92]),"+f"(d[93]),"+f"(d[94]),"+f"(d[95]),"+f"(d[96]),"+f"(d[97]),"+f"(d[98]),"+f"(d[99]),"+f"(d[100]),"+f"(d[101]),"+f"(d[102]),"+f"(d[103]),"+f"(d[104]),"+f"(d[105]),"+f"(d[106]),"+f"(d[107]),"+f"(d[108]),"+f"(d[109]),"+f"(d[110]),"+f"(d[111])
    : "l"(da),"l"(db),"r"(sc));
}
__device__ __forceinline__ void wgmma_n32_rs(float (&d)[16], const uint32_t (&a)[4], uint64_t db, int sc) {
  asm volatile("{\n.reg .pred p;\nsetp.ne.b32 p, %21, 0;\n"
    "wgmma.mma_async.sync.aligned.m64n32k16.f32.bf16.bf16 {%0,%1,%2,%3,%4,%5,%6,%7,%8,%9,%10,%11,%12,%13,%14,%15}, {%16,%17,%18,%19}, %20, p, 1, 1, 0;\n}"
    : "+f"(d[0]),"+f"(d[1]),"+f"(d[2]),"+f"(d[3]),"+f"(d[4]),"+f"(d[5]),"+f"(d[6]),"+f"(d[7]),"+f"(d[8]),"+f"(d[9]),"+f"(d[10]),"+f"(d[11]),"+f"(d[12]),"+f"(d[13]),"+f"(d[14]),"+f"(d[15])
    : "r"(a[0]),"r"(a[1]),"r"(a[2]),"r"(a[3]),"l"(db),"r"(sc));
}
__device__ __forceinline__ void wgmma_n256_kn(float (&d)[128], uint64_t da, uint64_t db, int sc) {
  asm volatile("{\n.reg .pred p;\nsetp.ne.b32 p, %130, 0;\n"
    "wgmma.mma_async.sync.aligned.m64n256k16.f32.bf16.bf16 {%0,%1,%2,%3,%4,%5,%6,%7,%8,%9,%10,%11,%12,%13,%14,%15,%16,%17,%18,%19,%20,%21,%22,%23,%24,%25,%26,%27,%28,%29,%30,%31,%32,%33,%34,%35,%36,%37,%38,%39,%40,%41,%42,%43,%44,%45,%46,%47,%48,%49,%50,%51,%52,%53,%54,%55,%56,%57,%58,%59,%60,%61,%62,%63,%64,%65,%66,%67,%68,%69,%70,%71,%72,%73,%74,%75,%76,%77,%78,%79,%80,%81,%82,%83,%84,%85,%86,%87,%88,%89,%90,%91,%92,%93,%94,%95,%96,%97,%98,%99,%100,%101,%102,%103,%104,%105,%106,%107,%108,%109,%110,%111,%112,%113,%114,%115,%116,%117,%118,%119,%120,%121,%122,%123,%124,%125,%126,%127}, %128, %129, p, 1, 1, 0, 1;\n}"
    : "+f"(d[0]),"+f"(d[1]),"+f"(d[2]),"+f"(d[3]),"+f"(d[4]),"+f"(d[5]),"+f"(d[6]),"+f"(d[7]),"+f"(d[8]),"+f"(d[9]),"+f"(d[10]),"+f"(d[11]),"+f"(d[12]),"+f"(d[13]),"+f"(d[14]),"+f"(d[15]),"+f"(d[16]),"+f"(d[17]),"+f"(d[18]),"+f"(d[19]),"+f"(d[20]),"+f"(d[21]),"+f"(d[22]),"+f"(d[23]),"+f"(d[24]),"+f"(d[25]),"+f"(d[26]),"+f"(d[27]),"+f"(d[28]),"+f"(d[29]),"+f"(d[30]),"+f"(d[31]),"+f"(d[32]),"+f"(d[33]),"+f"(d[34]),"+f"(d[35]),"+f"(d[36]),"+f"(d[37]),"+f"(d[38]),"+f"(d[39]),"+f"(d[40]),"+f"(d[41]),"+f"(d[42]),"+f"(d[43]),"+f"(d[44]),"+f"(d[45]),"+f"(d[46]),"+f"(d[47]),"+f"(d[48]),"+f"(d[49]),"+f"(d[50]),"+f"(d[51]),"+f"(d[52]),"+f"(d[53]),"+f"(d[54]),"+f"(d[55]),"+f"(d[56]),"+f"(d[57]),"+f"(d[58]),"+f"(d[59]),"+f"(d[60]),"+f"(d[61]),"+f"(d[62]),"+f"(d[63]),"+f"(d[64]),"+f"(d[65]),"+f"(d[66]),"+f"(d[67]),"+f"(d[68]),"+f"(d[69]),"+f"(d[70]),"+f"(d[71]),"+f"(d[72]),"+f"(d[73]),"+f"(d[74]),"+f"(d[75]),"+f"(d[76]),"+f"(d[77]),"+f"(d[78]),"+f"(d[79]),"+f"(d[80]),"+f"(d[81]),"+f"(d[82]),"+f"(d[83]),"+f"(d[84]),"+f"(d[85]),"+f"(d[86]),"+f"(d[87]),"+f"(d[88]),"+f"(d[89]),"+f"(d[90]),"+f"(d[91]),"+f"(d[92]),"+f"(d[93]),"+f"(d[94]),"+f"(d[95]),"+f"(d[96]),"+f"(d[97]),"+f"(d[98]),"+f"(d[99]),"+f"(d[100]),"+f"(d[101]),"+f"(d[102]),"+f"(d[103]),"+f"(d[104]),"+f"(d[105]),"+f"(d[106]),"+f"(d[107]),"+f"(d[108]),"+f"(d[109]),"+f"(d[110]),"+f"(d[111]),"+f"(d[112]),"+f"(d[113]),"+f"(d[114]),"+f"(d[115]),"+f"(d[116]),"+f"(d[117]),"+f"(d[118]),"+f"(d[119]),"+f"(d[120]),"+f"(d[121]),"+f"(d[122]),"+f"(d[123]),"+f"(d[124]),"+f"(d[125]),"+f"(d[126]),"+f"(d[127])
    : "l"(da),"l"(db),"r"(sc));
}
__device__ __forceinline__ void wgmma_n192_kn(float (&d)[96], uint64_t da, uint64_t db, int sc) {
  asm volatile("{\n.reg .pred p;\nsetp.ne.b32 p, %98, 0;\n"
    "wgmma.mma_async.sync.aligned.m64n192k16.f32.bf16.bf16 {%0,%1,%2,%3,%4,%5,%6,%7,%8,%9,%10,%11,%12,%13,%14,%15,%16,%17,%18,%19,%20,%21,%22,%23,%24,%25,%26,%27,%28,%29,%30,%31,%32,%33,%34,%35,%36,%37,%38,%39,%40,%41,%42,%43,%44,%45,%46,%47,%48,%49,%50,%51,%52,%53,%54,%55,%56,%57,%58,%59,%60,%61,%62,%63,%64,%65,%66,%67,%68,%69,%70,%71,%72,%73,%74,%75,%76,%77,%78,%79,%80,%81,%82,%83,%84,%85,%86,%87,%88,%89,%90,%91,%92,%93,%94,%95}, %96, %97, p, 1, 1, 0, 1;\n}"
    : "+f"(d[0]),"+f"(d[1]),"+f"(d[2]),"+f"(d[3]),"+f"(d[4]),"+f"(d[5]),"+f"(d[6]),"+f"(d[7]),"+f"(d[8]),"+f"(d[9]),"+f"(d[10]),"+f"(d[11]),"+f"(d[12]),"+f"(d[13]),"+f"(d[14]),"+f"(d[15]),"+f"(d[16]),"+f"(d[17]),"+f"(d[18]),"+f"(d[19]),"+f"(d[20]),"+f"(d[21]),"+f"(d[22]),"+f"(d[23]),"+f"(d[24]),"+f"(d[25]),"+f"(d[26]),"+f"(d[27]),"+f"(d[28]),"+f"(d[29]),"+f"(d[30]),"+f"(d[31]),"+f"(d[32]),"+f"(d[33]),"+f"(d[34]),"+f"(d[35]),"+f"(d[36]),"+f"(d[37]),"+f"(d[38]),"+f"(d[39]),"+f"(d[40]),"+f"(d[41]),"+f"(d[42]),"+f"(d[43]),"+f"(d[44]),"+f"(d[45]),"+f"(d[46]),"+f"(d[47]),"+f"(d[48]),"+f"(d[49]),"+f"(d[50]),"+f"(d[51]),"+f"(d[52]),"+f"(d[53]),"+f"(d[54]),"+f"(d[55]),"+f"(d[56]),"+f"(d[57]),"+f"(d[58]),"+f"(d[59]),"+f"(d[60]),"+f"(d[61]),"+f"(d[62]),"+f"(d[63]),"+f"(d[64]),"+f"(d[65]),"+f"(d[66]),"+f"(d[67]),"+f"(d[68]),"+f"(d[69]),"+f"(d[70]),"+f"(d[71]),"+f"(d[72]),"+f"(d[73]),"+f"(d[74]),"+f"(d[75]),"+f"(d[76]),"+f"(d[77]),"+f"(d[78]),"+f"(d[79]),"+f"(d[80]),"+f"(d[81]),"+f"(d[82]),"+f"(d[83]),"+f"(d[84]),"+f"(d[85]),"+f"(d[86]),"+f"(d[87]),"+f"(d[88]),"+f"(d[89]),"+f"(d[90]),"+f"(d[91]),"+f"(d[92]),"+f"(d[93]),"+f"(d[94]),"+f"(d[95])
    : "l"(da),"l"(db),"r"(sc));
}

constexpr uint32_t XB = 28672;
constexpr uint32_t O_WQ = 5 * XB;
constexpr uint32_t O_WO = O_WQ + 32768;
constexpr uint32_t O_MIMG = O_WO + 32768;
constexpr uint32_t O_BAR = O_MIMG + 2 * 7168;
constexpr uint32_t O_TS = O_BAR + 256;
constexpr uint32_t T_SMEM = O_TS + 4096 + 1024;
constexpr uint32_t O_Z = 4 * XB;
constexpr uint32_t O_RS = O_Z + 2 * 5120;
constexpr uint32_t O_ORS = O_RS + 2 * 2048;
constexpr uint32_t O_P = O_ORS + 2 * 8192;
constexpr uint32_t O_SX = O_P + 2 * 2560;
enum { B_X = 0, B_M = 4, B_RS = 6, B_O = 8, B_ZX = 10, B_P = 12, B_PF = 14, B_PE = 18, B_WQ = 22, B_WO = 23, B_N = 24 };
constexpr uint32_t O_DEAD = O_BAR + 8 * B_N, O_C3 = O_DEAD + 4;

DEVI bool fix_m(uint32_t img, const uint8_t* gslot, uint32_t dead, int lane) {
  bool ok = true;
#pragma unroll 1
  for (int k0 = 0; k0 < 14; k0 += 7) {
    uint32_t v[7][4], it = 0;
    const uint8_t* p = gslot + (k0 * 32 + lane) * 16;
    while (true) {
      uint32_t mx = 0;
#pragma unroll
      for (int k = 0; k < 7; k++)
        asm volatile("ld.relaxed.gpu.global.v4.u32 {%0,%1,%2,%3}, [%4];" : "=r"(v[k][0]), "=r"(v[k][1]), "=r"(v[k][2]), "=r"(v[k][3]) : "l"(p + k * 512) : "memory");
#pragma unroll
      for (int k = 0; k < 7; k++) mx = __vimax3_u32(mx, __vimax3_u32(v[k][0], v[k][1], v[k][2]), v[k][3]);
      if (mx != 0xffffffffu) break;
      if (spin_fail(it, dead)) { ok = false; break; }
    }
#pragma unroll
    for (int k = 0; k < 7; k++) sts_u4(img + ((k0 + k) * 32 + lane) * 16, v[k][0], v[k][1], v[k][2], v[k][3]);
  }
  return __all_sync(0xffffffffu, ok);
}

DEVI bool gemm_m(const uint32_t (&w)[28][4], uint32_t img_lane, float (&c)[4]) {
  float acc[4][4];
#pragma unroll
  for (int i = 0; i < 4; i++) { acc[i][0] = acc[i][1] = acc[i][2] = acc[i][3] = 0.f; }
  uint32_t mx = 0;
#pragma unroll
  for (int u = 0; u < 14; u++) {
    uint32_t r[4];
    ldsm4(r, img_lane + u * 512);
    mma16(acc[(2 * u) & 3], w[2 * u][0], w[2 * u][1], w[2 * u][2], w[2 * u][3], r[0], r[1]);
    mma16(acc[(2 * u + 1) & 3], w[2 * u + 1][0], w[2 * u + 1][1], w[2 * u + 1][2], w[2 * u + 1][3], r[2], r[3]);
    mx = __vimax3_u32(mx, r[0], r[1]);
    mx = __vimax3_u32(mx, r[2], r[3]);
  }
#pragma unroll
  for (int i = 0; i < 4; i++) c[i] = (acc[0][i] + acc[1][i]) + (acc[2][i] + acc[3][i]);
  return mx == 0xffffffffu;
}

DEVI void gemm_x(const uint32_t (&w)[28][4], uint32_t xbuf, float (&d)[16]) {
  const uint64_t b0 = desc128(xbuf, 1);
  wg_fence();
#pragma unroll
  for (int k = 0; k < 28; k++) wgmma_n32_rs(d, w[k], b0 + (uint64_t)((k >> 2) * 256 + (k & 3) * 2), k != 0);
  wg_commit();
  wg_wait<0>();
  reg_fence(d);
}

template <int WHICH>
DEVI void build_weights(uint32_t (&w)[28][4], uint32_t sb, uint32_t dead, int lane) {
  const uint32_t bar = sb + O_BAR;
  mbar_wait(bar + 8 * (WHICH ? B_WO : B_WQ), 0, dead);
#pragma unroll
  for (int half = 0; half < 2; half++) {
    float d[112];
#pragma unroll 1
    for (int fk = 0; fk < 4; fk++) {
      const int c = 2 * (4 * half + fk) + WHICH, st = c & 3;
      mbar_wait(bar + 8 * (B_PF + st), (c >> 2) & 1, dead);
      __syncwarp();
      const uint64_t db = desc128(sb + (st + 1) * XB, 1);
      wg_fence();
#pragma unroll
      for (int kk = 0; kk < 4; kk++) {
        if (WHICH == 0) wgmma_n224_kk(d, desc128(sb + O_WQ + fk * 8192 + kk * 32, 1), db + kk * 2, (fk | kk) != 0);
        else            wgmma_n224_mk(d, desc128(sb + O_WO + (fk * 4 + kk) * 2048, 1), db + kk * 2, (fk | kk) != 0);
      }
      wg_commit();
      wg_wait<0>();
      if (lane == 0) mbar_arrive(bar + 8 * (B_PE + st));
    }
    reg_fence(d);
#pragma unroll
    for (int kk = 0; kk < 14; kk++) {
      w[14 * half + kk][0] = pack2(d[8 * kk + 0], d[8 * kk + 1]);
      w[14 * half + kk][1] = pack2(d[8 * kk + 2], d[8 * kk + 3]);
      w[14 * half + kk][2] = pack2(d[8 * kk + 4], d[8 * kk + 5]);
      w[14 * half + kk][3] = pack2(d[8 * kk + 6], d[8 * kk + 7]);
    }
  }
}

DEVI float2 sum7(uint32_t (&v)[14], const float* p, int stride, uint32_t tag, uint32_t dead) {
  uint32_t it = 0;
  while (true) {
    uint32_t bad = 0;
#pragma unroll
    for (int k = 0; k < 14; k++) bad |= v[k] ^ tag;
    if ((bad & 3u) == 0) break;
    if (spin_fail(it, dead)) break;
#pragma unroll
    for (int k = 0; k < 7; k++) ldg2r(v[2 * k], v[2 * k + 1], p + k * stride);
  }
  __syncwarp();
  float2 r;
  r.x = ((__uint_as_float(v[0]) + __uint_as_float(v[2])) + (__uint_as_float(v[4]) + __uint_as_float(v[6]))) +
        ((__uint_as_float(v[8]) + __uint_as_float(v[10])) + __uint_as_float(v[12]));
  r.y = ((__uint_as_float(v[1]) + __uint_as_float(v[3])) + (__uint_as_float(v[5]) + __uint_as_float(v[7]))) +
        ((__uint_as_float(v[9]) + __uint_as_float(v[11])) + __uint_as_float(v[13]));
  return r;
}

__global__ void __launch_bounds__(384, 1)
rmt_kernel(const __grid_constant__ CUtensorMap tmWq, const __grid_constant__ CUtensorMap tmWk,
           const __grid_constant__ CUtensorMap tmWv, const __grid_constant__ CUtensorMap tmWo,
           const __grid_constant__ CUtensorMap tmX, const __nv_bfloat16* __restrict__ x,
           const __nv_bfloat16* __restrict__ mem0, const __nv_bfloat16* __restrict__ gate_w) {
  extern __shared__ uint8_t smem_raw[];
  const uint32_t sb = (smem_u32(smem_raw) + 1023) & ~1023u;
  const uint32_t bar = sb + O_BAR, dead = sb + O_DEAD;
  const int tid = threadIdx.x, lane = tid & 31, warp = __shfl_sync(0xffffffffu, tid >> 5, 0);
  uint32_t h, j;
  asm volatile("mov.u32 %0, %%cluster_ctarank;" : "=r"(h));
  asm volatile("mov.u32 %0, %%clusterid.x;" : "=r"(j));

  if (tid == 256) {
    for (int i = 0; i < B_N; i++) mbar_init(bar + 8 * i, (i >= B_ZX && i < B_P) || (i >= B_PE && i < B_WQ) ? 4 : (i >= B_P && i < B_PF) ? 2 : 1);
    sts32v(dead, 0);
    sts32v(sb + O_C3, 0);
    asm volatile("fence.mbarrier_init.release.cluster;" ::: "memory");
    asm volatile("fence.proxy.async.shared::cta;" ::: "memory");
    mbar_expect(bar + 8 * B_WQ, 32768);
    for (int k = 0; k < 4; k++) tma2d(sb + O_WQ + k * 8192, &tmWq, h * DH + k * 64, j * 64, bar + 8 * B_WQ);
    for (int c = 0; c < 4; c++) {
      mbar_expect(bar + 8 * (B_PF + c), XB);
      tma2d(sb + (c + 1) * XB, (c & 1) ? &tmWv : &tmWk, h * DH + (c >> 1) * 64, 0, bar + 8 * (B_PF + c));
      if (c == 0) { mbar_expect(bar + 8 * B_WO, 32768); tma2d(sb + O_WO, &tmWo, j * 64, h * DH, bar + 8 * B_WO); }
    }
    mbar_expect(bar + 8 * B_X, XB);
    for (int i = 0; i < 2; i++) { mbar_expect(bar + 8 * (B_RS + i), 2048); mbar_expect(bar + 8 * (B_O + i), 8192); }
  }
  for (int t = tid; t < 448; t += 384) {
    const uint4 v = *reinterpret_cast<const uint4*>(mem0 + (t & 7) * DM + (t >> 3) * 8);
    sts_u4(sb + O_MIMG + t * 16, v.x, v.y, v.z, v.w);
  }
  asm volatile("griddepcontrol.launch_dependents;");
  __syncthreads();
  cluster_arrive();
  cluster_wait();

  if (warp < 4) {
    asm volatile("setmaxnreg.inc.sync.aligned.u32 208;");
    uint32_t w[28][4];
    build_weights<0>(w, sb, dead, lane);
    cluster_arrive();
    const uint32_t zst = sb + O_Z + ((2 * warp + ((lane >> 3) & 1)) * 40 + 8 * (lane >> 4) + (lane & 7)) * 16;
    const uint32_t zld = sb + O_Z + ((lane >> 3) * 40 + (lane & 7)) * 16;
    const int mt = warp & 1, n0 = (warp >> 1) * 3;
    const int xrow = 16 * mt + (lane & 15);
    const uint32_t xq = sb + j * 4096 + xrow * 128;
    {
      float d[16];
      mbar_wait(bar + 8 * B_X, 0, dead);
      __syncwarp();
      gemm_x(w, sb, d);
      cluster_wait();
      stsm4t(zst + 8 * 16, pack2(d[0], d[1]), pack2(d[2], d[3]), pack2(d[4], d[5]), pack2(d[6], d[7]));
      stsm4t(zst + 24 * 16, pack2(d[8], d[9]), pack2(d[10], d[11]), pack2(d[12], d[13]), pack2(d[14], d[15]));
      __syncwarp();
      if (lane == 0) mbar_arrive(bar + 8 * B_ZX);
    }
#pragma unroll 1
    for (int s = 0; s < NSEG; s++) {
      const uint32_t img = sb + O_MIMG + (s & 1) * 7168, zo = (s & 1) * 5120;
      if (s) mbar_wait(bar + 8 * (B_M + (s & 1)), ((s - 1) >> 1) & 1, dead);
      __syncwarp();
      if (warp == 2) TS(0);
      float c[4];
      while (true) {
        const bool bad = gemm_m(w, img + lane * 16, c);
        if (s == 0 || !__any_sync(0xffffffffu, bad)) break;
        if (!fix_m(img, g_mslot[s & 3], dead, lane)) break;
      }
      stsm2t(zst + zo, pack2(c[0], c[1]), pack2(c[2], c[3]));
      bar_arrive(2, 256);
      if (warp == 2) {
        uint32_t a0[4], a1[4];
        ldsm4(a0, img + j * 1024 + lane * 16);
        ldsm4(a1, img + j * 1024 + 512 + lane * 16);
        bar_sync(1, 128);
        TS(1);
        if (s < NSEG - 1) {
          uint32_t b0[4], b1[4];
          ldsm4(b0, zld + zo);
          ldsm4(b1, zld + zo + 4 * 640);
          float e0[4] = {0.f, 0.f, 0.f, 0.f}, e1[4] = {0.f, 0.f, 0.f, 0.f};
          mma16(e0, a0[0], 0, a0[1], 0, b0[0], b0[1]);
          mma16(e1, a1[0], 0, a1[1], 0, b1[0], b1[1]);
          mma16(e0, a0[2], 0, a0[3], 0, b0[2], b0[3]);
          mma16(e1, a1[2], 0, a1[3], 0, b1[2], b1[3]);
          const uint32_t tag = ((s >> 2) + 1) & 3;
          stg2r(&g_smm[s & 3][h][j][lane * 2], tagf(e0[0] + e1[0], tag), tagf(e0[1] + e1[1], tag));
        }
        TS(2);
      } else {
        uint32_t a[4][4];
        const uint32_t xa = xq + (s & 3) * XB;
#pragma unroll
        for (int kk = 0; kk < 4; kk++) ldsm4(a[kk], xa + (((2 * kk + (lane >> 4)) ^ (xrow & 7)) << 4));
        bar_sync(1, 128);
        float* acc = &g_sacc[s & 7][h][(10 * mt + n0) * 64 + lane * 2];
#pragma unroll
        for (int n = 0; n < 3; n++) {
          if (n < 2 || n0 == 0) {
            uint32_t b0[4], b1[4];
            ldsm4(b0, zld + zo + (n0 + n) * 128);
            ldsm4(b1, zld + zo + (n0 + n) * 128 + 4 * 640);
            float e[4] = {0.f, 0.f, 0.f, 0.f};
            mma16(e, a[0][0], a[0][1], a[0][2], a[0][3], b0[0], b0[1]);
            mma16(e, a[1][0], a[1][1], a[1][2], a[1][3], b0[2], b0[3]);
            mma16(e, a[2][0], a[2][1], a[2][2], a[2][3], b1[0], b1[1]);
            mma16(e, a[3][0], a[3][1], a[3][2], a[3][3], b1[2], b1[3]);
            red2(acc + n * 64, e[0], e[1]);
            red2(acc + n * 64 + 320, e[2], e[3]);
          }
        }
      }
      if (s < NSEG - 1) {
        float d[16];
        mbar_wait(bar + 8 * (B_X + ((s + 1) & 3)), ((s + 1) >> 2) & 1, dead);
        __syncwarp();
        gemm_x(w, sb + ((s + 1) & 3) * XB, d);
        const uint32_t zn = zst + (5120 - zo);
        stsm4t(zn + 8 * 16, pack2(d[0], d[1]), pack2(d[2], d[3]), pack2(d[4], d[5]), pack2(d[6], d[7]));
        stsm4t(zn + 24 * 16, pack2(d[8], d[9]), pack2(d[10], d[11]), pack2(d[12], d[13]), pack2(d[14], d[15]));
        __syncwarp();
        if (lane == 0) mbar_arrive(bar + 8 * (B_ZX + ((s + 1) & 1)));
        if (warp == 2) TS(3);
      }
      if (warp != 2) {
        __syncwarp();
        if (lane == 0) asm volatile("red.release.gpu.global.add.u32 [%0], 1;" :: "l"(&g_sflag[s & 7][h][0]) : "memory");
      }
    }
    __syncwarp();
    cluster_arrive();
    cluster_wait();
  } else if (warp < 8) {
    asm volatile("setmaxnreg.inc.sync.aligned.u32 224;");
    const int wq = warp - 4;
    uint32_t w[28][4];
    build_weights<1>(w, sb, dead, lane);
    cluster_arrive();
    uint32_t yx[8], yp[8], ym[2], ymp[2];
    {
      float d[16];
      mbar_wait(bar + 8 * B_X, 0, dead);
      __syncwarp();
      gemm_x(w, sb, d);
#pragma unroll
      for (int i = 0; i < 8; i++) { yx[i] = pack2(d[2 * i], d[2 * i + 1]); yp[i] = 0; }
      ymp[0] = ymp[1] = 0;
      cluster_wait();
    }
    const uint32_t zld = sb + O_Z + ((lane >> 3) * 40 + 8 + 8 * wq + (lane & 7)) * 16;
    const int ri = lane >> 2, q = lane & 3;
    const uint32_t rs_a = mapa(sb + O_RS + h * 128 + ((ri & 1) * 4 + q) * 16, 4 * wq + (ri >> 1));
    const uint32_t rs_b = mapa(bar + 8 * B_RS, 4 * wq + (ri >> 1));
    const uint32_t o_a = mapa(sb + O_ORS + h * 512 + (ri & 1) * 256 + wq * 64 + q * 16, ri >> 1);
    const uint32_t o_b = mapa(bar + 8 * B_O, ri >> 1);
    const uint32_t o_st = mapa(sb, 4) - mapa(sb, 0);

    auto token_pv = [&](int sp) {
      const uint32_t pb = sb + O_P + (sp & 1) * 2560, oo = (sp & 1) * 8192, ob = (sp & 1) * 8;
      mbar_wait(bar + 8 * (B_P + (sp & 1)), (sp >> 1) & 1, dead);
      __syncwarp();
#pragma unroll
      for (int mt = 0; mt < 2; mt++) {
        const uint4 p0 = lds_u4(pb + mt * 1280 + lane * 16);
        const uint2 pm = lds_u2(pb + mt * 1280 + 1024 + lane * 8);
        float o0[4] = {0.f, 0.f, 0.f, 0.f}, o1[4] = {0.f, 0.f, 0.f, 0.f};
        mma8(o0, pm.x, pm.y, ymp[0]);
        mma8(o1, pm.x, pm.y, ymp[1]);
        mma16(o0, p0.x, p0.y, p0.z, p0.w, yp[0], yp[2]);
        mma16(o1, p0.x, p0.y, p0.z, p0.w, yp[1], yp[3]);
        if (mt) {
          const uint4 p1 = lds_u4(pb + mt * 1280 + 512 + lane * 16);
          mma16(o0, p1.x, p1.y, p1.z, p1.w, yp[4], yp[6]);
          mma16(o1, p1.x, p1.y, p1.z, p1.w, yp[5], yp[7]);
        }
        st_async4(o_a + oo + (2 * mt) * o_st, o0[0], o0[1], o1[0], o1[1], o_b + ob + (2 * mt) * o_st);
        st_async4(o_a + oo + (2 * mt + 1) * o_st, o0[2], o0[3], o1[2], o1[3], o_b + ob + (2 * mt + 1) * o_st);
      }
    };

#pragma unroll 1
    for (int s = 0; s < NSEG; s++) {
      const uint32_t img = sb + O_MIMG + (s & 1) * 7168, tag = ((s >> 2) + 1) & 3;
      const bool rec = s < NSEG - 1;
      uint32_t zb0[4], zb1[4];
      mbar_wait(bar + 8 * (B_ZX + (s & 1)), (s >> 1) & 1, dead);
      __syncwarp();
      ldsm4(zb0, zld + (s & 1) * 5120);
      ldsm4(zb1, zld + (s & 1) * 5120 + 4 * 640);
      if (s) mbar_wait(bar + 8 * (B_M + (s & 1)), ((s - 1) >> 1) & 1, dead);
      __syncwarp();
      if (rec) {
        uint32_t a0[4], a1[4];
        while (true) {
          ldsm4(a0, img + j * 1024 + lane * 16);
          ldsm4(a1, img + j * 1024 + 512 + lane * 16);
          const uint32_t mx = __vimax3_u32(__vimax3_u32(a0[0], a0[1], a0[2]), __vimax3_u32(a0[3], a1[0], a1[1]), max(a1[2], a1[3]));
          if (s == 0 || !__any_sync(0xffffffffu, mx == 0xffffffffu)) break;
          if (!fix_m(img, g_mslot[s & 3], dead, lane)) break;
        }
        float e0[4] = {0.f, 0.f, 0.f, 0.f}, e1[4] = {0.f, 0.f, 0.f, 0.f};
        mma16(e0, a0[0], 0, a0[1], 0, zb0[0], zb0[1]);
        mma16(e1, a1[0], 0, a1[1], 0, zb1[0], zb1[1]);
        mma16(e0, a0[2], 0, a0[3], 0, zb0[2], zb0[3]);
        mma16(e1, a1[2], 0, a1[3], 0, zb1[2], zb1[3]);
        stg2r(&g_smx[s & 3][h][j][wq * 64 + lane * 2], tagf(e0[0] + e1[0], tag), tagf(e0[1] + e1[1], tag));
      }
      bar_sync(2, 256);
      const uint32_t t0 = clk();
      {
        float c[4];
        while (true) {
          const bool bad = gemm_m(w, img + lane * 16, c);
          if (s == 0 || !__any_sync(0xffffffffu, bad)) break;
          if (!fix_m(img, g_mslot[s & 3], dead, lane)) break;
        }
        ym[0] = pack2(c[0], c[1]);
        ym[1] = pack2(c[2], c[3]);
      }
      if (wq == 0) TS(4);
      uint32_t vx[14], vm[14];
      const float* px = &g_smx[s & 3][h][0][wq * 64 + lane * 2];
      const float* pm = &g_smm[s & 3][h][0][lane * 2];
      if (rec) {
#pragma unroll
        for (int k = 0; k < 7; k++) ldg2r(vx[2 * k], vx[2 * k + 1], px + k * 256);
      }
      if (s) token_pv(s - 1);
      if (wq == 0) TS(5);
      if (rec) {
        while (clk() - t0 < D_S) {}
#pragma unroll
        for (int k = 0; k < 7; k++) ldg2r(vm[2 * k], vm[2 * k + 1], pm + k * 64);
        const float2 sx = sum7(vx, px, 256, tag, dead);
        if (wq == 0) TS(6);
        sts_f2(sb + O_SX + wq * 256 + lane * 8, sx.x, sx.y);
        bar_sync(3, 128);
        float2 v[4];
#pragma unroll
        for (int n = 0; n < 4; n++) v[n] = lds_f2(sb + O_SX + n * 256 + lane * 8);
        const float mxx = qmax(fmaxf(fmaxf(fmaxf(v[0].x, v[0].y), fmaxf(v[1].x, v[1].y)), fmaxf(fmaxf(v[2].x, v[2].y), fmaxf(v[3].x, v[3].y))));
        const float nb = -mxx * SC2;
        float lx = 0.f;
        uint32_t pa[4];
#pragma unroll
        for (int n = 0; n < 4; n++) {
          const float p0 = ex2(fmaf(v[n].x, SC2, nb)), p1 = ex2(fmaf(v[n].y, SC2, nb));
          lx += p0 + p1;
          pa[n] = pack2(p0, p1);
        }
        float o0[4] = {0.f, 0.f, 0.f, 0.f}, o1[4] = {0.f, 0.f, 0.f, 0.f};
        mma16(o0, pa[0], 0, pa[1], 0, yx[0], yx[2]);
        mma16(o1, pa[0], 0, pa[1], 0, yx[1], yx[3]);
        mma16(o0, pa[2], 0, pa[3], 0, yx[4], yx[6]);
        mma16(o1, pa[2], 0, pa[3], 0, yx[5], yx[7]);
        if (wq == 0) TS(7);
        const float2 sm = sum7(vm, pm, 64, tag, dead);
        if (wq == 0) TS(8);
        const float mx = fmaxf(mxx, qmax(fmaxf(sm.x, sm.y)));
        const float nm = -mx * SC2;
        const float al = ex2(fmaf(mxx, SC2, nm)), p0 = ex2(fmaf(sm.x, SC2, nm)), p1 = ex2(fmaf(sm.y, SC2, nm));
        const uint32_t pp = pack2(p0, p1);
        o0[0] *= al; o0[1] *= al; o1[0] *= al; o1[1] *= al;
        mma8(o0, pp, 0, ym[0]);
        mma8(o1, pp, 0, ym[1]);
        const float inv = __fdividef(1.f, qsum(fmaf(al, lx, p0 + p1)));
        st_async4(rs_a + (s & 1) * 2048, o0[0] * inv, o0[1] * inv, o1[0] * inv, o1[1] * inv, rs_b + (s & 1) * 8);
        if (wq == 0) TS(9);
      }
#pragma unroll
      for (int i = 0; i < 8; i++) yp[i] = yx[i];
      ymp[0] = ym[0]; ymp[1] = ym[1];
      if (rec) {
        float d[16];
        mbar_wait(bar + 8 * (B_X + ((s + 1) & 3)), ((s + 1) >> 2) & 1, dead);
        __syncwarp();
        gemm_x(w, sb + ((s + 1) & 3) * XB, d);
#pragma unroll
        for (int i = 0; i < 8; i++) yx[i] = pack2(d[2 * i], d[2 * i + 1]);
        if (wq == 0) TS(10);
      }
    }
    token_pv(NSEG - 1);
    __syncwarp();
    cluster_arrive();
    cluster_wait();
  } else {
    asm volatile("setmaxnreg.dec.sync.aligned.u32 72;");
    if (warp == 8) {
      const int u = lane >> 2, comp = lane & 3;
      const uint32_t moff = (8 * j + 2 * (h >> 2) + (comp >> 1)) * 128 + (2 * (h & 3) + (u >> 2)) * 16 + ((u & 3) * 2 + (comp & 1)) * 2;
#pragma unroll
      for (int k = 0; k < 4; k++) stg16r(&g_mslot[k][moff], 0xffff);
      __threadfence();
      if (lane == 0) {
        if (h < 7) tma2d_mc(sb + h * 4096, &tmX, h * 64, 0, bar + 8 * B_X);
#pragma unroll 1
        for (int c = 4; c < 16; c++) {
          const int st = c & 3;
          mbar_wait(bar + 8 * (B_PE + st), ((c >> 2) - 1) & 1, dead);
          mbar_expect(bar + 8 * (B_PF + st), XB);
          tma2d(sb + (st + 1) * XB, (c & 1) ? &tmWv : &tmWk, h * DH + ((c >> 1) & 3) * 64, (c >> 3) * 224, bar + 8 * (B_PF + st));
        }
      }
      __syncwarp();
      cluster_arrive();
      cluster_wait();
      if (lane == 0) {
        for (int k = 1; k < 3; k++) {
          mbar_expect(bar + 8 * (B_X + k), XB);
          if (h < 7) tma2d_mc(sb + k * XB + h * 4096, &tmX, h * 64, k * 32, bar + 8 * (B_X + k));
        }
      }
#pragma unroll 1
      for (int s = 0; s < NSEG - 1; s++) {
        const uint32_t rb = sb + O_RS + (s & 1) * 2048 + lane * 4;
        uint8_t* gm = g_mslot[(s + 1) & 3];
        if (lane == 0) {
          mbar_expect(bar + 8 * (B_M + ((s + 1) & 1)), 7168);
          uint32_t it = 0;
          while ((int)lds32v(sb + O_C3) < s - 1) { if (spin_fail(it, dead)) break; }
        }
        mbar_wait(bar + 8 * (B_RS + (s & 1)), (s >> 1) & 1, dead);
        __syncwarp();
        TS(11);
        float v[16];
#pragma unroll
        for (int k = 0; k < 16; k++) v[k] = lds_f(rb + k * 128);
        const float sum = (((v[0] + v[1]) + (v[2] + v[3])) + ((v[4] + v[5]) + (v[6] + v[7]))) +
                          (((v[8] + v[9]) + (v[10] + v[11])) + ((v[12] + v[13]) + (v[14] + v[15])));
        stg16r(gm + moff, (uint16_t)(pack2(sum, 0.f) & 0xffff));
        const uint32_t t0 = clk();
        TS(12);
        __syncwarp();
        if (lane == 0) {
          mbar_expect(bar + 8 * (B_RS + (s & 1)), 2048);
          while (clk() - t0 < D_M) {}
          bulk_mc(sb + O_MIMG + ((s + 1) & 1) * 7168 + h * 448, gm + h * 448, 448, bar + 8 * (B_M + ((s + 1) & 1)));
          if (s + 3 < NSEG) {
            mbar_expect(bar + 8 * (B_X + ((s + 3) & 3)), XB);
            if (h < 7) tma2d_mc(sb + ((s + 3) & 3) * XB + h * 4096, &tmX, h * 64, (s + 3) * 32, bar + 8 * (B_X + ((s + 3) & 3)));
          }
        }
        stg16r(&g_mslot[(s + 3) & 3][moff], 0xffff);
        __syncwarp();
      }
    } else if (warp < 11) {
      const int mt = warp - 9, q = lane & 3;
      cluster_arrive();
      cluster_wait();
#pragma unroll 1
      for (int s = 0; s < NSEG; s++) {
        const uint32_t* fl = &g_sflag[s & 7][h][0];
        uint32_t it = 0;
        while (true) {
          uint32_t f;
          asm volatile("ld.relaxed.gpu.global.u32 %0, [%1];" : "=r"(f) : "l"(fl) : "memory");
          if (f >= 21) break;
          if (spin_fail(it, dead)) break;
          __nanosleep(40);
        }
        __syncwarp();
        const float* sp = &g_sacc[s & 7][h][mt * 640 + lane * 2];
        uint32_t pk[2][5];
        float v[2][10];
#pragma unroll
        for (int rg = 0; rg < 2; rg++)
#pragma unroll
          for (int n = 0; n < 5; n++) {
            uint32_t a = 0, b = 0;
            if (n < 3 || mt) ldg2r(a, b, sp + (rg * 5 + n) * 64);
            v[rg][2 * n] = __uint_as_float(a);
            v[rg][2 * n + 1] = __uint_as_float(b);
          }
#pragma unroll
        for (int rg = 0; rg < 2; rg++) {
          const int row = 16 * mt + 8 * rg + (lane >> 2);
#pragma unroll
          for (int e = 2; e < 10; e++)
            if (8 * ((e >> 1) - 1) + 2 * q + (e & 1) > row) v[rg][e] = MASKV;
          float mx = v[rg][0];
#pragma unroll
          for (int e = 1; e < 10; e++) mx = fmaxf(mx, v[rg][e]);
          mx = qmax(mx);
          const float nb = -mx * SC2;
          float l = 0.f;
#pragma unroll
          for (int e = 0; e < 10; e++) { v[rg][e] = ex2(fmaf(v[rg][e], SC2, nb)); l += v[rg][e]; }
          const float inv = __fdividef(1.f, qsum(l));
#pragma unroll
          for (int n = 0; n < 5; n++) pk[rg][n] = pack2(v[rg][2 * n] * inv, v[rg][2 * n + 1] * inv);
        }
        const uint32_t pb = sb + O_P + (s & 1) * 2560 + mt * 1280;
        sts_u4(pb + lane * 16, pk[0][1], pk[1][1], pk[0][2], pk[1][2]);
        sts_u4(pb + 512 + lane * 16, pk[0][3], pk[1][3], pk[0][4], pk[1][4]);
        sts_u2(pb + 1024 + lane * 8, pk[0][0], pk[1][0]);
        __syncwarp();
        if (lane == 0) mbar_arrive(bar + 8 * (B_P + (s & 1)));
        if (mt == 1) TS(13);
        float* zp = &g_sacc[(s + 4) & 7][h][lane * 2];
        for (int uu = j + 7 * mt; uu < 20; uu += 14) stg2r(zp + uu * 64, 0, 0);
        if (j == 0 && mt == 0 && lane == 0) asm volatile("st.relaxed.gpu.global.u32 [%0], 0;" :: "l"(&g_sflag[(s + 4) & 7][h][0]) : "memory");
        asm volatile("fence.release.gpu;" ::: "memory");
      }
    } else {
      const int t1 = lane >> 4, l16 = lane & 15;
      uint2 gw[7];
#pragma unroll
      for (int k = 0; k < 7; k++) gw[k] = *reinterpret_cast<const uint2*>(gate_w + (k * 16 + l16) * 4);
      const int col = j * 64 + ((lane >> 2) & 3) * 16 + (lane & 3) * 2;
      cluster_arrive();
      cluster_wait();
#pragma unroll 1
      for (int s = 0; s < NSEG; s++) {
        const int tok = s * 32 + 2 * h + t1;
        float z = 0.f;
#pragma unroll
        for (int k = 0; k < 7; k++) {
          const uint2 xv = *reinterpret_cast<const uint2*>(x + tok * DM + (k * 16 + l16) * 4);
          z = fmaf(bf_lo(xv.x), bf_lo(gw[k].x), z); z = fmaf(bf_hi(xv.x), bf_hi(gw[k].x), z);
          z = fmaf(bf_lo(xv.y), bf_lo(gw[k].y), z); z = fmaf(bf_hi(xv.y), bf_hi(gw[k].y), z);
        }
#pragma unroll
        for (int o = 1; o < 16; o <<= 1) z += __shfl_xor_sync(0xffffffffu, z, o);
        const float g = 1.f / (1.f + __expf(-z));
        mbar_wait(bar + 8 * (B_O + (s & 1)), (s >> 1) & 1, dead);
        __syncwarp();
        const uint32_t ob = sb + O_ORS + (s & 1) * 8192 + lane * 16;
        float4 a = lds_f4(ob), b = lds_f4(ob + 512);
#pragma unroll
        for (int k = 2; k < 16; k += 2) {
          const float4 c = lds_f4(ob + k * 512), d = lds_f4(ob + k * 512 + 512);
          a.x += c.x; a.y += c.y; a.z += c.z; a.w += c.w;
          b.x += d.x; b.y += d.y; b.z += d.z; b.w += d.w;
        }
        a.x += b.x; a.y += b.y; a.z += b.z; a.w += b.w;
        __syncwarp();
        if (lane == 0) { mbar_expect(bar + 8 * (B_O + (s & 1)), 8192); sts32v(sb + O_C3, s + 1); }
        float* sp = &g_stash[tok * DM + col];
        *reinterpret_cast<float2*>(sp) = make_float2(g * a.x, g * a.y);
        *reinterpret_cast<float2*>(sp + 8) = make_float2(g * a.z, g * a.w);
        TS(14);
      }
    }
    __syncwarp();
    cluster_arrive();
    cluster_wait();
  }
}

constexpr uint32_t F_STAGE = 49152, F_BAR = 4 * F_STAGE, F_G = F_BAR + 128, F_SMEM = F_G + 512 + 1024;

template <int N>
DEVI void ffn_tile(float (&d)[N / 2], uint32_t sb, int wg, int nk, int& it, uint32_t dead, int lane) {
#pragma unroll 1
  for (int k = 0; k < nk; k++, it++) {
    const int st = it & 3;
    mbar_wait(sb + F_BAR + 8 * st, (it >> 2) & 1, dead);
    __syncwarp();
    const uint64_t da = desc128(sb + st * F_STAGE + wg * 8192, 1), db = desc128(sb + st * F_STAGE + 16384, 512);
    wg_fence();
#pragma unroll
    for (int kk = 0; kk < 4; kk++) {
      if constexpr (N == 256) wgmma_n256_kn(d, da + kk * 2, db + kk * 128, (k | kk) != 0);
      else                    wgmma_n192_kn(d, da + kk * 2, db + kk * 128, (k | kk) != 0);
    }
    wg_commit();
    if (k) { wg_wait<1>(); if (lane == 0) mbar_arrive(sb + F_BAR + 32 + 8 * ((it - 1) & 3)); }
  }
  wg_wait<0>();
  if (lane == 0) mbar_arrive(sb + F_BAR + 32 + 8 * ((it - 1) & 3));
  reg_fence(d);
}

__global__ void __launch_bounds__(384, 1)
ffn_kernel(const __grid_constant__ CUtensorMap tmX, const __grid_constant__ CUtensorMap tmW1,
           const __grid_constant__ CUtensorMap tmH, const __grid_constant__ CUtensorMap tmW2,
           const __nv_bfloat16* __restrict__ x, const __nv_bfloat16* __restrict__ gate_w, __nv_bfloat16* __restrict__ out) {
  extern __shared__ uint8_t smem_raw[];
  const uint32_t sb = (smem_u32(smem_raw) + 1023) & ~1023u;
  const uint32_t dead = sb + F_BAR + 96, hbar = sb + F_BAR + 64;
  const int tid = threadIdx.x, lane = tid & 31, warp = __shfl_sync(0xffffffffu, tid >> 5, 0), r0 = blockIdx.x * 128;
  if (tid == 0) {
    for (int i = 0; i < 4; i++) { mbar_init(sb + F_BAR + 8 * i, 1); mbar_init(sb + F_BAR + 32 + 8 * i, 8); }
    mbar_init(hbar, 256);
    sts32v(dead, 0);
    asm volatile("fence.mbarrier_init.release.cluster;" ::: "memory");
    asm volatile("fence.proxy.async.shared::cta;" ::: "memory");
  }
  __syncthreads();
  if (warp >= 8) {
    asm volatile("setmaxnreg.dec.sync.aligned.u32 40;");
    if (tid == 256) {
      int it = 0;
#pragma unroll 1
      for (int t = 0; t < 9; t++) {
        const int nk = t < 7 ? 7 : 28, nb = t < 8 ? 4 : 3;
        if (t == 7) mbar_wait(hbar, 0, dead);
#pragma unroll 1
        for (int k = 0; k < nk; k++, it++) {
          const int st = it & 3;
          const uint32_t fb = sb + F_BAR + 8 * st, a = sb + st * F_STAGE;
          if (it >= 4) mbar_wait(fb + 32, ((it >> 2) - 1) & 1, dead);
          mbar_expect(fb, 16384 + nb * 8192);
          tma2d(a, t < 7 ? &tmX : &tmH, k * 64, r0, fb);
          for (int b = 0; b < nb; b++) tma2d(a + 16384 + b * 8192, t < 7 ? &tmW1 : &tmW2, (t < 7 ? t : t - 7) * 256 + b * 64, k * 64, fb);
        }
      }
    } else if (warp > 8) {
      const int l16 = lane & 15;
      for (int r = (warp - 9) * 2 + (lane >> 4); r < 132; r += 6) {
        const int rr = r < 128 ? r : 127;
        float z = 0.f;
#pragma unroll
        for (int k = 0; k < 7; k++) {
          const uint2 xv = *reinterpret_cast<const uint2*>(x + (r0 + rr) * DM + (k * 16 + l16) * 4);
          const uint2 gv = *reinterpret_cast<const uint2*>(gate_w + (k * 16 + l16) * 4);
          z = fmaf(bf_lo(xv.x), bf_lo(gv.x), z); z = fmaf(bf_hi(xv.x), bf_hi(gv.x), z);
          z = fmaf(bf_lo(xv.y), bf_lo(gv.y), z); z = fmaf(bf_hi(xv.y), bf_hi(gv.y), z);
        }
#pragma unroll
        for (int o = 1; o < 16; o <<= 1) z += __shfl_xor_sync(0xffffffffu, z, o);
        if (l16 == 0) sts32v(sb + F_G + rr * 4, __float_as_uint(1.f - 1.f / (1.f + __expf(-z))));
      }
      __syncwarp();
      bar_arrive(1, 352);
    }
  } else {
    asm volatile("setmaxnreg.inc.sync.aligned.u32 232;");
    const int wg = warp >> 2, row = wg * 64 + (warp & 3) * 16 + (lane >> 2), q = lane & 3;
    int it = 0;
#pragma unroll 1
    for (int t = 0; t < 7; t++) {
      float d[128];
      ffn_tile<256>(d, sb, wg, 7, it, dead, lane);
      __nv_bfloat16* hp = g_h + (size_t)(r0 + row) * DFF + t * 256 + 2 * q;
#pragma unroll
      for (int n = 0; n < 32; n++) {
        *reinterpret_cast<uint32_t*>(hp + n * 8) = pack2(fmaxf(d[4 * n], 0.f), fmaxf(d[4 * n + 1], 0.f));
        *reinterpret_cast<uint32_t*>(hp + 8 * DFF + n * 8) = pack2(fmaxf(d[4 * n + 2], 0.f), fmaxf(d[4 * n + 3], 0.f));
      }
    }
    __threadfence();
    asm volatile("fence.proxy.async;" ::: "memory");
    mbar_arrive(hbar);
    bar_sync(1, 352);
    const float g0 = lds_f(sb + F_G + row * 4), g1 = lds_f(sb + F_G + row * 4 + 32);
    float* bp = g_b + (size_t)(r0 + row) * DM + 2 * q;
    {
      float d[128];
      ffn_tile<256>(d, sb, wg, 28, it, dead, lane);
#pragma unroll
      for (int n = 0; n < 32; n++) {
        *reinterpret_cast<float2*>(bp + n * 8) = make_float2(g0 * d[4 * n], g0 * d[4 * n + 1]);
        *reinterpret_cast<float2*>(bp + 8 * DM + n * 8) = make_float2(g1 * d[4 * n + 2], g1 * d[4 * n + 3]);
      }
    }
    {
      float d[96];
      ffn_tile<192>(d, sb, wg, 28, it, dead, lane);
#pragma unroll
      for (int n = 0; n < 24; n++) {
        *reinterpret_cast<float2*>(bp + 256 + n * 8) = make_float2(g0 * d[4 * n], g0 * d[4 * n + 1]);
        *reinterpret_cast<float2*>(bp + 256 + 8 * DM + n * 8) = make_float2(g1 * d[4 * n + 2], g1 * d[4 * n + 3]);
      }
    }
    bar_sync(2, 256);
    asm volatile("griddepcontrol.wait;" ::: "memory");
    const float4* sa = reinterpret_cast<const float4*>(g_stash + (size_t)r0 * DM);
    const float4* sbp = reinterpret_cast<const float4*>(g_b + (size_t)r0 * DM);
    uint2* op = reinterpret_cast<uint2*>(out + (size_t)r0 * DM);
#pragma unroll 8
    for (int i = tid; i < 128 * DM / 4; i += 256) {
      const float4 a = __ldcg(sa + i), b = __ldcg(sbp + i);
      op[i] = make_uint2(pack2(a.x + b.x, a.y + b.y), pack2(a.z + b.z, a.w + b.w));
    }
  }
}

typedef CUresult (*EncodeFn)(CUtensorMap*, CUtensorMapDataType, cuuint32_t, void*, const cuuint64_t*, const cuuint64_t*,
                             const cuuint32_t*, const cuuint32_t*, CUtensorMapInterleave, CUtensorMapSwizzle,
                             CUtensorMapL2promotion, CUtensorMapFloatOOBfill);

void make_map(EncodeFn fn, CUtensorMap* m, const void* p, uint64_t rows, uint64_t cols, uint32_t box_rows) {
  const cuuint64_t dims[2] = {cols, rows}, strides[1] = {cols * 2};
  const cuuint32_t box[2] = {64, box_rows}, es[2] = {1, 1};
  fn(m, CU_TENSOR_MAP_DATA_TYPE_BFLOAT16, 2, const_cast<void*>(p), dims, strides, box, es, CU_TENSOR_MAP_INTERLEAVE_NONE,
     CU_TENSOR_MAP_SWIZZLE_128B, CU_TENSOR_MAP_L2_PROMOTION_L2_256B, CU_TENSOR_MAP_FLOAT_OOB_FILL_NONE);
}

}

extern "C" void kernel_launch(void* const* d_in, const int* in_sizes, int n_in, void* d_out, int out_size) {
  (void)in_sizes; (void)n_in; (void)out_size;
  const __nv_bfloat16* x = (const __nv_bfloat16*)d_in[0];
  const __nv_bfloat16* mem0 = (const __nv_bfloat16*)d_in[1];
  const __nv_bfloat16* gate_w = (const __nv_bfloat16*)d_in[10];
  static EncodeFn fn = nullptr;
  static void* hptr = nullptr;
  if (!fn) {
    cudaDriverEntryPointQueryResult qr;
    cudaGetDriverEntryPoint("cuTensorMapEncodeTiled", (void**)&fn, cudaEnableDefault, &qr);
    cudaGetSymbolAddress(&hptr, g_h);
    cudaFuncSetAttribute(rmt_kernel, cudaFuncAttributeMaxDynamicSharedMemorySize, T_SMEM);
    cudaFuncSetAttribute(rmt_kernel, cudaFuncAttributeNonPortableClusterSizeAllowed, 1);
    cudaFuncSetAttribute(ffn_kernel, cudaFuncAttributeMaxDynamicSharedMemorySize, F_SMEM);
  }
  CUtensorMap mWq, mWk, mWv, mWo, mX, mXf, mW1, mH, mW2;
  make_map(fn, &mWq, d_in[2], DM, NH * DH, 64);
  make_map(fn, &mWk, d_in[3], DM, NH * DH, 224);
  make_map(fn, &mWv, d_in[4], DM, NH * DH, 224);
  make_map(fn, &mWo, d_in[5], NH * DH, DM, 256);
  make_map(fn, &mX, x, SEQ, DM, 32);
  make_map(fn, &mXf, x, SEQ, DM, 128);
  make_map(fn, &mW1, d_in[8], DM, DFF, 64);
  make_map(fn, &mH, hptr, SEQ, DFF, 128);
  make_map(fn, &mW2, d_in[9], DFF, DM, 64);

  cudaLaunchConfig_t cfg = {};
  cudaLaunchAttribute at[1];
  cfg.gridDim = dim3(112); cfg.blockDim = dim3(384); cfg.dynamicSmemBytes = T_SMEM; cfg.stream = cudaStreamPerThread;
  at[0].id = cudaLaunchAttributeClusterDimension;
  at[0].val.clusterDim.x = 16; at[0].val.clusterDim.y = 1; at[0].val.clusterDim.z = 1;
  cfg.attrs = at; cfg.numAttrs = 1;
  cudaLaunchKernelEx(&cfg, rmt_kernel, mWq, mWk, mWv, mWo, mX, x, mem0, gate_w);

  cfg.gridDim = dim3(16); cfg.dynamicSmemBytes = F_SMEM;
  at[0].id = cudaLaunchAttributeProgrammaticStreamSerialization;
  at[0].val.programmaticStreamSerializationAllowed = 1;
  cudaLaunchKernelEx(&cfg, ffn_kernel, mXf, mW1, mH, mW2, x, gate_w, (__nv_bfloat16*)d_out);
}
```

```cpp
#include <cuda_runtime.h>
#include <cuda_bf16.h>
#include <cuda.h>
#include <stdint.h>

namespace {

#define DEVI __device__ __forceinline__

constexpr int SEQ = 2048, DM = 448, NH = 16, DH = 256, NSEG = 64, DFF = 1792;
constexpr float SC2 = 1.4426950408889634f / 16.0f;
constexpr float MASKV = -1.6e10f;
constexpr uint32_t SPIN_LIMIT = 1u << 19;

#define D_M 700
#define D_X 330
#define D_S 470

__device__ __align__(1024) uint8_t g_mslot[4][7168];
__device__ __align__(1024) float g_smm[4][NH][7][64];
__device__ __align__(1024) float g_smx[4][NH][7][256];
__device__ __align__(1024) float g_sacc[8][NH][1280];
__device__ __align__(1024) uint32_t g_sflag[8][NH][8];
__device__ __align__(1024) float g_stash[SEQ * DM];
__device__ __align__(1024) float g_b[SEQ * DM];
__device__ __align__(1024) __nv_bfloat16 g_h[SEQ * DFF];
__device__ int g_err;
#define TS(i)

DEVI uint32_t smem_u32(const void* p) { return (uint32_t)__cvta_generic_to_shared(p); }
DEVI uint32_t clk() { uint32_t c; asm volatile("mov.u32 %0, %%clock;" : "=r"(c) :: "memory"); return c; }
DEVI void mbar_init(uint32_t bar, uint32_t cnt) { asm volatile("mbarrier.init.shared::cta.b64 [%0], %1;" :: "r"(bar), "r"(cnt) : "memory"); }
DEVI void mbar_expect(uint32_t bar, uint32_t bytes) { asm volatile("mbarrier.arrive.expect_tx.shared::cta.b64 _, [%0], %1;" :: "r"(bar), "r"(bytes) : "memory"); }
DEVI void mbar_arrive(uint32_t bar) { asm volatile("mbarrier.arrive.shared::cta.b64 _, [%0];" :: "r"(bar) : "memory"); }
DEVI uint32_t lds32v(uint32_t a) { uint32_t v; asm volatile("ld.volatile.shared::cta.u32 %0, [%1];" : "=r"(v) : "r"(a) : "memory"); return v; }
DEVI void sts32v(uint32_t a, uint32_t v) { asm volatile("st.volatile.shared::cta.u32 [%0], %1;" :: "r"(a), "r"(v) : "memory"); }
DEVI void mbar_wait(uint32_t bar, uint32_t par, uint32_t& lim) {
  uint32_t left;
  asm volatile("{\n.reg .pred p, q;\nmov.u32 %0, %3;\nWAIT_LOOP:\n"
               "mbarrier.try_wait.parity.shared::cta.b64 p, [%1], %2;\n"
               "sub.u32 %0, %0, 1;\nsetp.ne.and.u32 q, %0, 0, !p;\n@q bra WAIT_LOOP;\n}"
               : "=&r"(left) : "r"(bar), "r"(par), "r"(lim) : "memory");
  lim = left ? lim : 1u;
}
template <class T> DEVI void pin(T& v) { asm volatile("" : "+r"(v)); }
template <class T> DEVI void pinp(T*& v) { asm volatile("" : "+l"(v)); }
DEVI void bar_sync(int id, int n) { asm volatile("bar.sync %0, %1;" :: "r"(id), "r"(n) : "memory"); }
DEVI void bar_arrive(int id, int n) { asm volatile("bar.arrive %0, %1;" :: "r"(id), "r"(n) : "memory"); }
DEVI void cluster_arrive() { asm volatile("barrier.cluster.arrive.release.aligned;" ::: "memory"); }
DEVI void cluster_wait() { asm volatile("barrier.cluster.wait.acquire.aligned;" ::: "memory"); }
DEVI uint32_t mapa(uint32_t a, uint32_t r) { uint32_t o; asm("mapa.shared::cluster.u32 %0, %1, %2;" : "=r"(o) : "r"(a), "r"(r)); return o; }
DEVI uint32_t pack2(float lo, float hi) { uint32_t r; asm("cvt.rn.bf16x2.f32 %0, %1, %2;" : "=r"(r) : "f"(hi), "f"(lo)); return r; }
DEVI float ex2(float x) { float y; asm("ex2.approx.ftz.f32 %0, %1;" : "=f"(y) : "f"(x)); return y; }
DEVI float bf_lo(uint32_t v) { return __uint_as_float(v << 16); }
DEVI float bf_hi(uint32_t v) { return __uint_as_float(v & 0xffff0000u); }
DEVI void ldsm4(uint32_t (&r)[4], uint32_t a) {
  asm volatile("ldmatrix.sync.aligned.m8n8.x4.shared.b16 {%0,%1,%2,%3}, [%4];" : "=r"(r[0]), "=r"(r[1]), "=r"(r[2]), "=r"(r[3]) : "r"(a) : "memory");
}
DEVI void stsm4t(uint32_t a, uint32_t r0, uint32_t r1, uint32_t r2, uint32_t r3) {
  asm volatile("stmatrix.sync.aligned.m8n8.x4.trans.shared.b16 [%0], {%1,%2,%3,%4};" :: "r"(a), "r"(r0), "r"(r1), "r"(r2), "r"(r3) : "memory");
}
DEVI void stsm2t(uint32_t a, uint32_t r0, uint32_t r1) {
  asm volatile("stmatrix.sync.aligned.m8n8.x2.trans.shared.b16 [%0], {%1,%2};" :: "r"(a), "r"(r0), "r"(r1) : "memory");
}
DEVI void mma16(float (&c)[4], uint32_t a0, uint32_t a1, uint32_t a2, uint32_t a3, uint32_t b0, uint32_t b1) {
  asm("mma.sync.aligned.m16n8k16.row.col.f32.bf16.bf16.f32 {%0,%1,%2,%3},{%4,%5,%6,%7},{%8,%9},{%0,%1,%2,%3};"
      : "+f"(c[0]), "+f"(c[1]), "+f"(c[2]), "+f"(c[3]) : "r"(a0), "r"(a1), "r"(a2), "r"(a3), "r"(b0), "r"(b1));
}
DEVI void mma8(float (&c)[4], uint32_t a0, uint32_t a1, uint32_t b0) {
  asm("mma.sync.aligned.m16n8k8.row.col.f32.bf16.bf16.f32 {%0,%1,%2,%3},{%4,%5},{%6},{%0,%1,%2,%3};"
      : "+f"(c[0]), "+f"(c[1]), "+f"(c[2]), "+f"(c[3]) : "r"(a0), "r"(a1), "r"(b0));
}
DEVI void wg_fence() { asm volatile("wgmma.fence.sync.aligned;" ::: "memory"); }
DEVI void wg_commit() { asm volatile("wgmma.commit_group.sync.aligned;" ::: "memory"); }
template <int N> DEVI void wg_wait() { asm volatile("wgmma.wait_group.sync.aligned %0;" :: "n"(N) : "memory"); }
template <int N> DEVI void reg_fence(float (&d)[N]) {
#pragma unroll
  for (int i = 0; i < N; i++) asm volatile("" : "+f"(d[i]) :: "memory");
}
DEVI uint64_t desc128(uint32_t addr, uint32_t lbo16) {
  return (uint64_t)((addr >> 4) & 0x3fff) | ((uint64_t)lbo16 << 16) | (64ull << 32) | (1ull << 62);
}
DEVI void tma2d(uint32_t dst, const CUtensorMap* tm, int c0, int c1, uint32_t bar) {
  asm volatile("cp.async.bulk.tensor.2d.shared::cluster.global.mbarrier::complete_tx::bytes [%0], [%1, {%2, %3}], [%4];"
               :: "r"(dst), "l"(tm), "r"(c0), "r"(c1), "r"(bar) : "memory");
}
DEVI void tma2d_mc(uint32_t dst, const CUtensorMap* tm, int c0, int c1, uint32_t bar) {
  asm volatile("cp.async.bulk.tensor.2d.shared::cluster.global.mbarrier::complete_tx::bytes.multicast::cluster [%0], [%1, {%2, %3}], [%4], %5;"
               :: "r"(dst), "l"(tm), "r"(c0), "r"(c1), "r"(bar), "h"((uint16_t)0xffff) : "memory");
}
DEVI void bulk_mc(uint32_t dst, const void* src, uint32_t bytes, uint32_t bar) {
  asm volatile("cp.async.bulk.shared::cluster.global.mbarrier::complete_tx::bytes.multicast::cluster [%0], [%1], %2, [%3], %4;"
               :: "r"(dst), "l"(src), "r"(bytes), "r"(bar), "h"((uint16_t)0xffff) : "memory");
}
DEVI void st_async4(uint32_t a, float x, float y, float z, float w, uint32_t bar) {
  asm volatile("st.async.weak.shared::cluster.mbarrier::complete_tx::bytes.v4.f32 [%0], {%1,%2,%3,%4}, [%5];"
               :: "r"(a), "f"(x), "f"(y), "f"(z), "f"(w), "r"(bar) : "memory");
}
DEVI void ldg2r(uint32_t& x, uint32_t& y, const void* p) { asm volatile("ld.relaxed.gpu.global.v2.u32 {%0,%1}, [%2];" : "=r"(x), "=r"(y) : "l"(p) : "memory"); }
DEVI void stg2r(void* p, uint32_t x, uint32_t y) { asm volatile("st.relaxed.gpu.global.v2.u32 [%0], {%1,%2};" :: "l"(p), "r"(x), "r"(y) : "memory"); }
DEVI void stg16r(void* p, uint16_t v) { asm volatile("st.relaxed.gpu.global.u16 [%0], %1;" :: "l"(p), "h"(v) : "memory"); }
DEVI void red2(float* p, float x, float y) { asm volatile("red.relaxed.gpu.global.add.v2.f32 [%0], {%1,%2};" :: "l"(p), "f"(x), "f"(y) : "memory"); }
DEVI float lds_f(uint32_t a) { float v; asm volatile("ld.shared.f32 %0, [%1];" : "=f"(v) : "r"(a) : "memory"); return v; }
DEVI float2 lds_f2(uint32_t a) { float2 v; asm volatile("ld.shared.v2.f32 {%0,%1}, [%2];" : "=f"(v.x), "=f"(v.y) : "r"(a) : "memory"); return v; }
DEVI float4 lds_f4(uint32_t a) { float4 v; asm volatile("ld.shared.v4.f32 {%0,%1,%2,%3}, [%4];" : "=f"(v.x), "=f"(v.y), "=f"(v.z), "=f"(v.w) : "r"(a) : "memory"); return v; }
DEVI uint2 lds_u2(uint32_t a) { uint2 v; asm volatile("ld.shared.v2.u32 {%0,%1}, [%2];" : "=r"(v.x), "=r"(v.y) : "r"(a) : "memory"); return v; }
DEVI uint4 lds_u4(uint32_t a) { uint4 v; asm volatile("ld.shared.v4.u32 {%0,%1,%2,%3}, [%4];" : "=r"(v.x), "=r"(v.y), "=r"(v.z), "=r"(v.w) : "r"(a) : "memory"); return v; }
DEVI void sts_f2(uint32_t a, float x, float y) { asm volatile("st.shared.v2.f32 [%0], {%1,%2};" :: "r"(a), "f"(x), "f"(y) : "memory"); }
DEVI void sts_u2(uint32_t a, uint32_t x, uint32_t y) { asm volatile("st.shared.v2.u32 [%0], {%1,%2};" :: "r"(a), "r"(x), "r"(y) : "memory"); }
DEVI void sts_u4(uint32_t a, uint32_t x, uint32_t y, uint32_t z, uint32_t w) { asm volatile("st.shared.v4.u32 [%0], {%1,%2,%3,%4};" :: "r"(a), "r"(x), "r"(y), "r"(z), "r"(w) : "memory"); }
DEVI uint32_t tagf(float v, uint32_t tag) { return (__float_as_uint(v) & ~3u) | tag; }
DEVI float qmax(float v) { v = fmaxf(v, __shfl_xor_sync(0xffffffffu, v, 1)); return fmaxf(v, __shfl_xor_sync(0xffffffffu, v, 2)); }
DEVI float qsum(float v) { v += __shfl_xor_sync(0xffffffffu, v, 1); return v + __shfl_xor_sync(0xffffffffu, v, 2); }

__device__ __forceinline__ void wgmma_n224_kk(float (&d)[112], uint64_t da, uint64_t db, int sc) {
  asm volatile("{\n.reg .pred p;\nsetp.ne.b32 p, %114, 0;\n"
    "wgmma.mma_async.sync.aligned.m64n224k16.f32.bf16.bf16 {%0,%1,%2,%3,%4,%5,%6,%7,%8,%9,%10,%11,%12,%13,%14,%15,%16,%17,%18,%19,%20,%21,%22,%23,%24,%25,%26,%27,%28,%29,%30,%31,%32,%33,%34,%35,%36,%37,%38,%39,%40,%41,%42,%43,%44,%45,%46,%47,%48,%49,%50,%51,%52,%53,%54,%55,%56,%57,%58,%59,%60,%61,%62,%63,%64,%65,%66,%67,%68,%69,%70,%71,%72,%73,%74,%75,%76,%77,%78,%79,%80,%81,%82,%83,%84,%85,%86,%87,%88,%89,%90,%91,%92,%93,%94,%95,%96,%97,%98,%99,%100,%101,%102,%103,%104,%105,%106,%107,%108,%109,%110,%111}, %112, %113, p, 1, 1, 0, 0;\n}"
    : "+f"(d[0]),"+f"(d[1]),"+f"(d[2]),"+f"(d[3]),"+f"(d[4]),"+f"(d[5]),"+f"(d[6]),"+f"(d[7]),"+f"(d[8]),"+f"(d[9]),"+f"(d[10]),"+f"(d[11]),"+f"(d[12]),"+f"(d[13]),"+f"(d[14]),"+f"(d[15]),"+f"(d[16]),"+f"(d[17]),"+f"(d[18]),"+f"(d[19]),"+f"(d[20]),"+f"(d[21]),"+f"(d[22]),"+f"(d[23]),"+f"(d[24]),"+f"(d[25]),"+f"(d[26]),"+f"(d[27]),"+f"(d[28]),"+f"(d[29]),"+f"(d[30]),"+f"(d[31]),"+f"(d[32]),"+f"(d[33]),"+f"(d[34]),"+f"(d[35]),"+f"(d[36]),"+f"(d[37]),"+f"(d[38]),"+f"(d[39]),"+f"(d[40]),"+f"(d[41]),"+f"(d[42]),"+f"(d[43]),"+f"(d[44]),"+f"(d[45]),"+f"(d[46]),"+f"(d[47]),"+f"(d[48]),"+f"(d[49]),"+f"(d[50]),"+f"(d[51]),"+f"(d[52]),"+f"(d[53]),"+f"(d[54]),"+f"(d[55]),"+f"(d[56]),"+f"(d[57]),"+f"(d[58]),"+f"(d[59]),"+f"(d[60]),"+f"(d[61]),"+f"(d[62]),"+f"(d[63]),"+f"(d[64]),"+f"(d[65]),"+f"(d[66]),"+f"(d[67]),"+f"(d[68]),"+f"(d[69]),"+f"(d[70]),"+f"(d[71]),"+f"(d[72]),"+f"(d[73]),"+f"(d[74]),"+f"(d[75]),"+f"(d[76]),"+f"(d[77]),"+f"(d[78]),"+f"(d[79]),"+f"(d[80]),"+f"(d[81]),"+f"(d[82]),"+f"(d[83]),"+f"(d[84]),"+f"(d[85]),"+f"(d[86]),"+f"(d[87]),"+f"(d[88]),"+f"(d[89]),"+f"(d[90]),"+f"(d[91]),"+f"(d[92]),"+f"(d[93]),"+f"(d[94]),"+f"(d[95]),"+f"(d[96]),"+f"(d[97]),"+f"(d[98]),"+f"(d[99]),"+f"(d[100]),"+f"(d[101]),"+f"(d[102]),"+f"(d[103]),"+f"(d[104]),"+f"(d[105]),"+f"(d[106]),"+f"(d[107]),"+f"(d[108]),"+f"(d[109]),"+f"(d[110]),"+f"(d[111])
    : "l"(da),"l"(db),"r"(sc));
}
__device__ __forceinline__ void wgmma_n224_mk(float (&d)[112], uint64_t da, uint64_t db, int sc) {
  asm volatile("{\n.reg .pred p;\nsetp.ne.b32 p, %114, 0;\n"
    "wgmma.mma_async.sync.aligned.m64n224k16.f32.bf16.bf16 {%0,%1,%2,%3,%4,%5,%6,%7,%8,%9,%10,%11,%12,%13,%14,%15,%16,%17,%18,%19,%20,%21,%22,%23,%24,%25,%26,%27,%28,%29,%30,%31,%32,%33,%34,%35,%36,%37,%38,%39,%40,%41,%42,%43,%44,%45,%46,%47,%48,%49,%50,%51,%52,%53,%54,%55,%56,%57,%58,%59,%60,%61,%62,%63,%64,%65,%66,%67,%68,%69,%70,%71,%72,%73,%74,%75,%76,%77,%78,%79,%80,%81,%82,%83,%84,%85,%86,%87,%88,%89,%90,%91,%92,%93,%94,%95,%96,%97,%98,%99,%100,%101,%102,%103,%104,%105,%106,%107,%108,%109,%110,%111}, %112, %113, p, 1, 1, 1, 0;\n}"
    : "+f"(d[0]),"+f"(d[1]),"+f"(d[2]),"+f"(d[3]),"+f"(d[4]),"+f"(d[5]),"+f"(d[6]),"+f"(d[7]),"+f"(d[8]),"+f"(d[9]),"+f"(d[10]),"+f"(d[11]),"+f"(d[12]),"+f"(d[13]),"+f"(d[14]),"+f"(d[15]),"+f"(d[16]),"+f"(d[17]),"+f"(d[18]),"+f"(d[19]),"+f"(d[20]),"+f"(d[21]),"+f"(d[22]),"+f"(d[23]),"+f"(d[24]),"+f"(d[25]),"+f"(d[26]),"+f"(d[27]),"+f"(d[28]),"+f"(d[29]),"+f"(d[30]),"+f"(d[31]),"+f"(d[32]),"+f"(d[33]),"+f"(d[34]),"+f"(d[35]),"+f"(d[36]),"+f"(d[37]),"+f"(d[38]),"+f"(d[39]),"+f"(d[40]),"+f"(d[41]),"+f"(d[42]),"+f"(d[43]),"+f"(d[44]),"+f"(d[45]),"+f"(d[46]),"+f"(d[47]),"+f"(d[48]),"+f"(d[49]),"+f"(d[50]),"+f"(d[51]),"+f"(d[52]),"+f"(d[53]),"+f"(d[54]),"+f"(d[55]),"+f"(d[56]),"+f"(d[57]),"+f"(d[58]),"+f"(d[59]),"+f"(d[60]),"+f"(d[61]),"+f"(d[62]),"+f"(d[63]),"+f"(d[64]),"+f"(d[65]),"+f"(d[66]),"+f"(d[67]),"+f"(d[68]),"+f"(d[69]),"+f"(d[70]),"+f"(d[71]),"+f"(d[72]),"+f"(d[73]),"+f"(d[74]),"+f"(d[75]),"+f"(d[76]),"+f"(d[77]),"+f"(d[78]),"+f"(d[79]),"+f"(d[80]),"+f"(d[81]),"+f"(d[82]),"+f"(d[83]),"+f"(d[84]),"+f"(d[85]),"+f"(d[86]),"+f"(d[87]),"+f"(d[88]),"+f"(d[89]),"+f"(d[90]),"+f"(d[91]),"+f"(d[92]),"+f"(d[93]),"+f"(d[94]),"+f"(d[95]),"+f"(d[96]),"+f"(d[97]),"+f"(d[98]),"+f"(d[99]),"+f"(d[100]),"+f"(d[101]),"+f"(d[102]),"+f"(d[103]),"+f"(d[104]),"+f"(d[105]),"+f"(d[106]),"+f"(d[107]),"+f"(d[108]),"+f"(d[109]),"+f"(d[110]),"+f"(d[111])
    : "l"(da),"l"(db),"r"(sc));
}
__device__ __forceinline__ void wgmma_n32_rs(float (&d)[16], const uint32_t (&a)[4], uint64_t db, int sc) {
  asm volatile("{\n.reg .pred p;\nsetp.ne.b32 p, %21, 0;\n"
    "wgmma.mma_async.sync.aligned.m64n32k16.f32.bf16.bf16 {%0,%1,%2,%3,%4,%5,%6,%7,%8,%9,%10,%11,%12,%13,%14,%15}, {%16,%17,%18,%19}, %20, p, 1, 1, 0;\n}"
    : "+f"(d[0]),"+f"(d[1]),"+f"(d[2]),"+f"(d[3]),"+f"(d[4]),"+f"(d[5]),"+f"(d[6]),"+f"(d[7]),"+f"(d[8]),"+f"(d[9]),"+f"(d[10]),"+f"(d[11]),"+f"(d[12]),"+f"(d[13]),"+f"(d[14]),"+f"(d[15])
    : "r"(a[0]),"r"(a[1]),"r"(a[2]),"r"(a[3]),"l"(db),"r"(sc));
}
__device__ __forceinline__ void wgmma_n256_kn(float (&d)[128], uint64_t da, uint64_t db, int sc) {
  asm volatile("{\n.reg .pred p;\nsetp.ne.b32 p, %130, 0;\n"
    "wgmma.mma_async.sync.aligned.m64n256k16.f32.bf16.bf16 {%0,%1,%2,%3,%4,%5,%6,%7,%8,%9,%10,%11,%12,%13,%14,%15,%16,%17,%18,%19,%20,%21,%22,%23,%24,%25,%26,%27,%28,%29,%30,%31,%32,%33,%34,%35,%36,%37,%38,%39,%40,%41,%42,%43,%44,%45,%46,%47,%48,%49,%50,%51,%52,%53,%54,%55,%56,%57,%58,%59,%60,%61,%62,%63,%64,%65,%66,%67,%68,%69,%70,%71,%72,%73,%74,%75,%76,%77,%78,%79,%80,%81,%82,%83,%84,%85,%86,%87,%88,%89,%90,%91,%92,%93,%94,%95,%96,%97,%98,%99,%100,%101,%102,%103,%104,%105,%106,%107,%108,%109,%110,%111,%112,%113,%114,%115,%116,%117,%118,%119,%120,%121,%122,%123,%124,%125,%126,%127}, %128, %129, p, 1, 1, 0, 1;\n}"
    : "+f"(d[0]),"+f"(d[1]),"+f"(d[2]),"+f"(d[3]),"+f"(d[4]),"+f"(d[5]),"+f"(d[6]),"+f"(d[7]),"+f"(d[8]),"+f"(d[9]),"+f"(d[10]),"+f"(d[11]),"+f"(d[12]),"+f"(d[13]),"+f"(d[14]),"+f"(d[15]),"+f"(d[16]),"+f"(d[17]),"+f"(d[18]),"+f"(d[19]),"+f"(d[20]),"+f"(d[21]),"+f"(d[22]),"+f"(d[23]),"+f"(d[24]),"+f"(d[25]),"+f"(d[26]),"+f"(d[27]),"+f"(d[28]),"+f"(d[29]),"+f"(d[30]),"+f"(d[31]),"+f"(d[32]),"+f"(d[33]),"+f"(d[34]),"+f"(d[35]),"+f"(d[36]),"+f"(d[37]),"+f"(d[38]),"+f"(d[39]),"+f"(d[40]),"+f"(d[41]),"+f"(d[42]),"+f"(d[43]),"+f"(d[44]),"+f"(d[45]),"+f"(d[46]),"+f"(d[47]),"+f"(d[48]),"+f"(d[49]),"+f"(d[50]),"+f"(d[51]),"+f"(d[52]),"+f"(d[53]),"+f"(d[54]),"+f"(d[55]),"+f"(d[56]),"+f"(d[57]),"+f"(d[58]),"+f"(d[59]),"+f"(d[60]),"+f"(d[61]),"+f"(d[62]),"+f"(d[63]),"+f"(d[64]),"+f"(d[65]),"+f"(d[66]),"+f"(d[67]),"+f"(d[68]),"+f"(d[69]),"+f"(d[70]),"+f"(d[71]),"+f"(d[72]),"+f"(d[73]),"+f"(d[74]),"+f"(d[75]),"+f"(d[76]),"+f"(d[77]),"+f"(d[78]),"+f"(d[79]),"+f"(d[80]),"+f"(d[81]),"+f"(d[82]),"+f"(d[83]),"+f"(d[84]),"+f"(d[85]),"+f"(d[86]),"+f"(d[87]),"+f"(d[88]),"+f"(d[89]),"+f"(d[90]),"+f"(d[91]),"+f"(d[92]),"+f"(d[93]),"+f"(d[94]),"+f"(d[95]),"+f"(d[96]),"+f"(d[97]),"+f"(d[98]),"+f"(d[99]),"+f"(d[100]),"+f"(d[101]),"+f"(d[102]),"+f"(d[103]),"+f"(d[104]),"+f"(d[105]),"+f"(d[106]),"+f"(d[107]),"+f"(d[108]),"+f"(d[109]),"+f"(d[110]),"+f"(d[111]),"+f"(d[112]),"+f"(d[113]),"+f"(d[114]),"+f"(d[115]),"+f"(d[116]),"+f"(d[117]),"+f"(d[118]),"+f"(d[119]),"+f"(d[120]),"+f"(d[121]),"+f"(d[122]),"+f"(d[123]),"+f"(d[124]),"+f"(d[125]),"+f"(d[126]),"+f"(d[127])
    : "l"(da),"l"(db),"r"(sc));
}
__device__ __forceinline__ void wgmma_n192_kn(float (&d)[96], uint64_t da, uint64_t db, int sc) {
  asm volatile("{\n.reg .pred p;\nsetp.ne.b32 p, %98, 0;\n"
    "wgmma.mma_async.sync.aligned.m64n192k16.f32.bf16.bf16 {%0,%1,%2,%3,%4,%5,%6,%7,%8,%9,%10,%11,%12,%13,%14,%15,%16,%17,%18,%19,%20,%21,%22,%23,%24,%25,%26,%27,%28,%29,%30,%31,%32,%33,%34,%35,%36,%37,%38,%39,%40,%41,%42,%43,%44,%45,%46,%47,%48,%49,%50,%51,%52,%53,%54,%55,%56,%57,%58,%59,%60,%61,%62,%63,%64,%65,%66,%67,%68,%69,%70,%71,%72,%73,%74,%75,%76,%77,%78,%79,%80,%81,%82,%83,%84,%85,%86,%87,%88,%89,%90,%91,%92,%93,%94,%95}, %96, %97, p, 1, 1, 0, 1;\n}"
    : "+f"(d[0]),"+f"(d[1]),"+f"(d[2]),"+f"(d[3]),"+f"(d[4]),"+f"(d[5]),"+f"(d[6]),"+f"(d[7]),"+f"(d[8]),"+f"(d[9]),"+f"(d[10]),"+f"(d[11]),"+f"(d[12]),"+f"(d[13]),"+f"(d[14]),"+f"(d[15]),"+f"(d[16]),"+f"(d[17]),"+f"(d[18]),"+f"(d[19]),"+f"(d[20]),"+f"(d[21]),"+f"(d[22]),"+f"(d[23]),"+f"(d[24]),"+f"(d[25]),"+f"(d[26]),"+f"(d[27]),"+f"(d[28]),"+f"(d[29]),"+f"(d[30]),"+f"(d[31]),"+f"(d[32]),"+f"(d[33]),"+f"(d[34]),"+f"(d[35]),"+f"(d[36]),"+f"(d[37]),"+f"(d[38]),"+f"(d[39]),"+f"(d[40]),"+f"(d[41]),"+f"(d[42]),"+f"(d[43]),"+f"(d[44]),"+f"(d[45]),"+f"(d[46]),"+f"(d[47]),"+f"(d[48]),"+f"(d[49]),"+f"(d[50]),"+f"(d[51]),"+f"(d[52]),"+f"(d[53]),"+f"(d[54]),"+f"(d[55]),"+f"(d[56]),"+f"(d[57]),"+f"(d[58]),"+f"(d[59]),"+f"(d[60]),"+f"(d[61]),"+f"(d[62]),"+f"(d[63]),"+f"(d[64]),"+f"(d[65]),"+f"(d[66]),"+f"(d[67]),"+f"(d[68]),"+f"(d[69]),"+f"(d[70]),"+f"(d[71]),"+f"(d[72]),"+f"(d[73]),"+f"(d[74]),"+f"(d[75]),"+f"(d[76]),"+f"(d[77]),"+f"(d[78]),"+f"(d[79]),"+f"(d[80]),"+f"(d[81]),"+f"(d[82]),"+f"(d[83]),"+f"(d[84]),"+f"(d[85]),"+f"(d[86]),"+f"(d[87]),"+f"(d[88]),"+f"(d[89]),"+f"(d[90]),"+f"(d[91]),"+f"(d[92]),"+f"(d[93]),"+f"(d[94]),"+f"(d[95])
    : "l"(da),"l"(db),"r"(sc));
}

constexpr uint32_t XB = 28672;
constexpr uint32_t O_WQ = 5 * XB;
constexpr uint32_t O_WO = O_WQ + 32768;
constexpr uint32_t O_MIMG = O_WO + 32768;
constexpr uint32_t O_BAR = O_MIMG + 2 * 7168;
constexpr uint32_t O_TS = O_BAR + 256;
constexpr uint32_t T_SMEM = O_TS + 4096 + 1024;
constexpr uint32_t O_Z = 4 * XB;
constexpr uint32_t O_RS = O_Z + 2 * 5120;
constexpr uint32_t O_ORS = O_RS + 2 * 2048;
constexpr uint32_t O_P = O_ORS + 2 * 8192;
constexpr uint32_t O_SX = O_P + 2 * 2560;
enum { B_X = 0, B_M = 4, B_RS = 6, B_O = 8, B_ZX = 10, B_P = 12, B_PF = 14, B_PE = 18, B_WQ = 22, B_WO = 23, B_T = 24, B_N = 26 };
constexpr uint32_t O_C3 = O_BAR + 8 * B_N, O_REDO = O_C3 + 4;
enum { N_ZM = 1, N_YM = 2, N_MOK = 3, N_SX = 4, N_ZX = 5, N_REDO = 6 };

DEVI void gemm_m(const uint32_t (&w)[28][4], uint32_t img_lane, float (&c)[4]) {
  float acc[4][4];
#pragma unroll
  for (int i = 0; i < 4; i++) { acc[i][0] = acc[i][1] = acc[i][2] = acc[i][3] = 0.f; }
#pragma unroll
  for (int u = 0; u < 14; u++) {
    uint32_t r[4];
    ldsm4(r, img_lane + u * 512);
    mma16(acc[(2 * u) & 3], w[2 * u][0], w[2 * u][1], w[2 * u][2], w[2 * u][3], r[0], r[1]);
    mma16(acc[(2 * u + 1) & 3], w[2 * u + 1][0], w[2 * u + 1][1], w[2 * u + 1][2], w[2 * u + 1][3], r[2], r[3]);
  }
#pragma unroll
  for (int i = 0; i < 4; i++) c[i] = (acc[0][i] + acc[1][i]) + (acc[2][i] + acc[3][i]);
}

DEVI void gemm_x(const uint32_t (&w)[28][4], uint32_t xbuf, float (&d)[16]) {
  const uint64_t b0 = desc128(xbuf, 1);
  wg_fence();
#pragma unroll
  for (int k = 0; k < 28; k++) wgmma_n32_rs(d, w[k], b0 + (uint64_t)((k >> 2) * 256 + (k & 3) * 2), k != 0);
  wg_commit();
  wg_wait<0>();
  reg_fence(d);
}

template <int WHICH>
DEVI void build_weights(uint32_t (&w)[28][4], uint32_t sb, uint32_t& dead, int lane) {
  const uint32_t bar = sb + O_BAR;
  mbar_wait(bar + 8 * (WHICH ? B_WO : B_WQ), 0, dead);
#pragma unroll
  for (int half = 0; half < 2; half++) {
    float d[112];
#pragma unroll 1
    for (int fk = 0; fk < 4; fk++) {
      const int c = 2 * (4 * half + fk) + WHICH, st = c & 3;
      mbar_wait(bar + 8 * (B_PF + st), (c >> 2) & 1, dead);
      __syncwarp();
      const uint64_t db = desc128(sb + (st + 1) * XB, 1);
      wg_fence();
#pragma unroll
      for (int kk = 0; kk < 4; kk++) {
        if (WHICH == 0) wgmma_n224_kk(d, desc128(sb + O_WQ + fk * 8192 + kk * 32, 1), db + kk * 2, (fk | kk) != 0);
        else            wgmma_n224_mk(d, desc128(sb + O_WO + (fk * 4 + kk) * 2048, 1), db + kk * 2, (fk | kk) != 0);
      }
      wg_commit();
      wg_wait<0>();
      if (lane == 0) mbar_arrive(bar + 8 * (B_PE + st));
    }
    reg_fence(d);
#pragma unroll
    for (int kk = 0; kk < 14; kk++) {
      w[14 * half + kk][0] = pack2(d[8 * kk + 0], d[8 * kk + 1]);
      w[14 * half + kk][1] = pack2(d[8 * kk + 2], d[8 * kk + 3]);
      w[14 * half + kk][2] = pack2(d[8 * kk + 4], d[8 * kk + 5]);
      w[14 * half + kk][3] = pack2(d[8 * kk + 6], d[8 * kk + 7]);
    }
  }
}

DEVI void load7(uint32_t (&v)[14], const float* p, int stride) {
#pragma unroll
  for (int k = 0; k < 7; k++) ldg2r(v[2 * k], v[2 * k + 1], p + k * stride);
}
DEVI bool stale7(const uint32_t (&v)[14], uint32_t tag) {
  const uint32_t o = ((v[0] | v[1] | v[2]) | (v[3] | v[4] | v[5]) | (v[6] | v[7] | v[8])) | ((v[9] | v[10] | v[11]) | (v[12] | v[13]));
  const uint32_t a = ((v[0] & v[1] & v[2]) & (v[3] & v[4] & v[5]) & (v[6] & v[7] & v[8])) & ((v[9] & v[10] & v[11]) & (v[12] & v[13]));
  return (((o ^ tag) | (a ^ tag)) & 3u) != 0;
}
DEVI float2 sum7(uint32_t (&v)[14], const float* p, int stride, uint32_t tag, uint32_t& lim) {
  if (__builtin_expect(stale7(v, tag), 0)) {
    uint32_t left = lim;
    do { load7(v, p, stride); } while (stale7(v, tag) && --left);
    lim = left ? lim : 1u;
  }
  __syncwarp();
  float2 r;
  r.x = ((__uint_as_float(v[0]) + __uint_as_float(v[2])) + (__uint_as_float(v[4]) + __uint_as_float(v[6]))) +
        ((__uint_as_float(v[8]) + __uint_as_float(v[10])) + __uint_as_float(v[12]));
  r.y = ((__uint_as_float(v[1]) + __uint_as_float(v[3])) + (__uint_as_float(v[5]) + __uint_as_float(v[7]))) +
        ((__uint_as_float(v[9]) + __uint_as_float(v[11])) + __uint_as_float(v[13]));
  return r;
}

__global__ void __launch_bounds__(384, 1)
rmt_kernel(const __grid_constant__ CUtensorMap tmWq, const __grid_constant__ CUtensorMap tmWk,
           const __grid_constant__ CUtensorMap tmWv, const __grid_constant__ CUtensorMap tmWo,
           const __grid_constant__ CUtensorMap tmX, const __nv_bfloat16* __restrict__ x,
           const __nv_bfloat16* __restrict__ mem0, const __nv_bfloat16* __restrict__ gate_w) {
  extern __shared__ uint8_t smem_raw[];
  const uint32_t sb = (smem_u32(smem_raw) + 1023) & ~1023u;
  const uint32_t bar = sb + O_BAR;
  uint32_t lim = SPIN_LIMIT;
  int tid;
  uint32_t h, j;
  asm volatile("mov.u32 %0, %%tid.x;" : "=r"(tid));
  asm volatile("mov.u32 %0, %%cluster_ctarank;" : "=r"(h));
  asm volatile("mov.u32 %0, %%clusterid.x;" : "=r"(j));
  const int lane = tid & 31, warp = __shfl_sync(0xffffffffu, tid >> 5, 0);

  if (tid == 256) {
    for (int i = 0; i < B_N; i++)
      mbar_init(bar + 8 * i, i >= B_T ? 3 : (i >= B_ZX && i < B_P) || (i >= B_PE && i < B_WQ) ? 4 : (i >= B_P && i < B_PF) ? 2 : 1);
    sts32v(sb + O_C3, 0);
    asm volatile("fence.mbarrier_init.release.cluster;" ::: "memory");
    asm volatile("fence.proxy.async.shared::cta;" ::: "memory");
    mbar_expect(bar + 8 * B_WQ, 32768);
    for (int k = 0; k < 4; k++) tma2d(sb + O_WQ + k * 8192, &tmWq, h * DH + k * 64, j * 64, bar + 8 * B_WQ);
    for (int c = 0; c < 4; c++) {
      mbar_expect(bar + 8 * (B_PF + c), XB);
      tma2d(sb + (c + 1) * XB, (c & 1) ? &tmWv : &tmWk, h * DH + (c >> 1) * 64, 0, bar + 8 * (B_PF + c));
      if (c == 0) { mbar_expect(bar + 8 * B_WO, 32768); tma2d(sb + O_WO, &tmWo, j * 64, h * DH, bar + 8 * B_WO); }
    }
    mbar_expect(bar + 8 * B_X, XB);
    for (int i = 0; i < 2; i++) { mbar_expect(bar + 8 * (B_RS + i), 2048); mbar_expect(bar + 8 * (B_O + i), 8192); }
  }
  for (int t = tid; t < 448; t += 384) {
    const uint4 v = *reinterpret_cast<const uint4*>(mem0 + (t & 7) * DM + (t >> 3) * 8);
    sts_u4(sb + O_MIMG + t * 16, v.x, v.y, v.z, v.w);
  }
  asm volatile("griddepcontrol.launch_dependents;");
  __syncthreads();
  cluster_arrive();
  cluster_wait();

  if (warp < 4) {
    asm volatile("setmaxnreg.inc.sync.aligned.u32 208;");
    uint32_t w[28][4];
    build_weights<0>(w, sb, lim, lane);
    cluster_arrive();
    uint32_t zst = sb + O_Z + ((2 * warp + ((lane >> 3) & 1)) * 40 + 8 * (lane >> 4) + (lane & 7)) * 16;
    const int mt = warp & 1, n0 = (warp >> 1) * 3;
    uint32_t zld = sb + O_Z + ((lane >> 3) * 40 + (lane & 7)) * 16 + (warp == 2 ? 0 : n0 * 128);
    const int xrow = 16 * mt + (lane & 15);
    uint32_t xq = sb + j * 4096 + xrow * 128 + (((lane >> 4) ^ (xrow & 7)) << 4);
    uint32_t mimg = sb + O_MIMG + lane * 16, sxa = sb + O_SX + warp * 256 + lane * 8;
    float* p_smm = &g_smm[0][h][j][lane * 2];
    const float* p_smx = &g_smx[0][h][0][warp * 64 + lane * 2];
    float* p_acc = &g_sacc[0][h][(10 * mt + n0) * 64 + lane * 2];
    pin(zst); pin(zld); pin(xq); pin(mimg); pin(sxa); pinp(p_smm); pinp(p_smx); pinp(p_acc);
    {
      float d[16];
      mbar_wait(bar + 8 * B_X, 0, lim);
      __syncwarp();
      gemm_x(w, sb, d);
      cluster_wait();
      stsm4t(zst + 8 * 16, pack2(d[0], d[1]), pack2(d[2], d[3]), pack2(d[4], d[5]), pack2(d[6], d[7]));
      stsm4t(zst + 24 * 16, pack2(d[8], d[9]), pack2(d[10], d[11]), pack2(d[12], d[13]), pack2(d[14], d[15]));
      __syncwarp();
      if (lane == 0) mbar_arrive(bar + 8 * B_ZX);
    }
#pragma unroll 1
    for (int s = 0; s < NSEG; s++) {
      const bool rec = s < NSEG - 1;
      uint32_t img = mimg + (s & 1) * 7168, zs = zst + (s & 1) * 5120, zl = zld + (s & 1) * 5120;
      uint32_t tag = ((s >> 2) + 1) & 3, redo_a = sb + O_REDO + (s & 1) * 4;
      float* smm = p_smm + (s & 3) * (NH * 7 * 64);
      pin(img); pin(zs); pin(zl); pin(tag); pin(redo_a); pinp(smm);
      uint32_t a[4][4];
      if (warp != 2) {
        const uint32_t xa = xq + (s & 3) * XB;
#pragma unroll
        for (int kk = 0; kk < 4; kk++) ldsm4(a[kk], xa ^ (kk << 5));
      }
      if (s) mbar_wait(bar + 8 * (B_M + (s & 1)), ((s - 1) >> 1) & 1, lim);
      __syncwarp();
      if (warp == 2) TS(0);
      float c[4];
      gemm_m(w, img, c);
      stsm2t(zs, pack2(c[0], c[1]), pack2(c[2], c[3]));
      bar_arrive(N_YM, 256);
      if (warp == 2) { ldsm4(a[0], img + j * 1024); ldsm4(a[1], img + j * 1024 + 512); }
      bar_sync(N_ZM, 160);
      const uint32_t t0 = clk();
      uint32_t b0[4], b1[4];
      ldsm4(b0, zl);
      ldsm4(b1, zl + 4 * 640);
      if (__builtin_expect(lds32v(redo_a) != 0, 0)) {
        bar_sync(N_REDO, 128);
        gemm_m(w, img, c);
        stsm2t(zs, pack2(c[0], c[1]), pack2(c[2], c[3]));
        if (warp == 2) { ldsm4(a[0], img + j * 1024); ldsm4(a[1], img + j * 1024 + 512); }
        bar_sync(N_REDO, 128);
        ldsm4(b0, zl);
        ldsm4(b1, zl + 4 * 640);
      }
      if (warp == 2) {
        TS(1);
        float e0[4] = {0.f, 0.f, 0.f, 0.f}, e1[4] = {0.f, 0.f, 0.f, 0.f};
        mma16(e0, a[0][0], 0, a[0][1], 0, b0[0], b0[1]);
        mma16(e1, a[1][0], 0, a[1][1], 0, b1[0], b1[1]);
        mma16(e0, a[0][2], 0, a[0][3], 0, b0[2], b0[3]);
        mma16(e1, a[1][2], 0, a[1][3], 0, b1[2], b1[3]);
        if (rec) stg2r(smm, tagf(e0[0] + e1[0], tag), tagf(e0[1] + e1[1], tag));
        TS(2);
      } else {
        float* acc = p_acc + (s & 7) * (NH * 1280);
#pragma unroll
        for (int n = 0; n < 3; n++) {
          if (n < 2 || n0 == 0) {
            if (n) { ldsm4(b0, zl + n * 128); ldsm4(b1, zl + n * 128 + 4 * 640); }
            float e[4] = {0.f, 0.f, 0.f, 0.f};
            mma16(e, a[0][0], a[0][1], a[0][2], a[0][3], b0[0], b0[1]);
            mma16(e, a[1][0], a[1][1], a[1][2], a[1][3], b0[2], b0[3]);
            mma16(e, a[2][0], a[2][1], a[2][2], a[2][3], b1[0], b1[1]);
            mma16(e, a[3][0], a[3][1], a[3][2], a[3][3], b1[2], b1[3]);
            red2(acc + n * 64, e[0], e[1]);
            red2(acc + n * 64 + 320, e[2], e[3]);
          }
        }
      }
      if (rec) {
        const float* px = p_smx + (s & 3) * (NH * 7 * 256);
        uint32_t vx[14];
        while (clk() - t0 < D_X) {}
        load7(vx, px, 256);
        const float2 sx = sum7(vx, px, 256, tag, lim);
        sts_f2(sxa, sx.x, sx.y);
        bar_arrive(N_SX, 256);
        if (warp == 2) TS(6);
      }
      if (warp != 2) {
        __syncwarp();
        if (lane == 0) {
          asm volatile("red.release.gpu.global.add.u32 [%0], 1;" :: "l"(&g_sflag[s & 7][h][0]) : "memory");
          mbar_arrive(bar + 8 * (B_T + (s & 1)));
        }
        __syncwarp();
      }
      if (rec) {
        float d[16];
        mbar_wait(bar + 8 * (B_X + ((s + 1) & 3)), ((s + 1) >> 2) & 1, lim);
        bar_sync(N_ZX, 256);
        gemm_x(w, sb + ((s + 1) & 3) * XB, d);
        const uint32_t zn = zst + ((s + 1) & 1) * 5120;
        stsm4t(zn + 8 * 16, pack2(d[0], d[1]), pack2(d[2], d[3]), pack2(d[4], d[5]), pack2(d[6], d[7]));
        stsm4t(zn + 24 * 16, pack2(d[8], d[9]), pack2(d[10], d[11]), pack2(d[12], d[13]), pack2(d[14], d[15]));
        __syncwarp();
        if (lane == 0) mbar_arrive(bar + 8 * (B_ZX + ((s + 1) & 1)));
        if (warp == 2) TS(3);
      }
    }
    if (lim == 1) g_err = 1;
    __syncwarp();
    cluster_arrive();
    cluster_wait();
  } else if (warp < 8) {
    asm volatile("setmaxnreg.inc.sync.aligned.u32 224;");
    const int wq = warp - 4;
    uint32_t w[28][4];
    build_weights<1>(w, sb, lim, lane);
    cluster_arrive();
    uint32_t yx[8], yp[8], ym[2], ymp[2];
    {
      float d[16];
      mbar_wait(bar + 8 * B_X, 0, lim);
      __syncwarp();
      gemm_x(w, sb, d);
#pragma unroll
      for (int i = 0; i < 8; i++) { yx[i] = pack2(d[2 * i], d[2 * i + 1]); yp[i] = 0; }
      ymp[0] = ymp[1] = 0;
      cluster_wait();
    }
    const int ri = lane >> 2, q = lane & 3;
    uint32_t zld = sb + O_Z + ((lane >> 3) * 40 + 8 + 8 * wq + (lane & 7)) * 16;
    uint32_t rs_a = mapa(sb + O_RS + h * 128 + ((ri & 1) * 4 + q) * 16, 4 * wq + (ri >> 1));
    uint32_t rs_b = mapa(bar + 8 * B_RS, 4 * wq + (ri >> 1));
    uint32_t o_a = mapa(sb + O_ORS + h * 512 + (ri & 1) * 256 + wq * 64 + q * 16, ri >> 1);
    uint32_t o_b = mapa(bar + 8 * B_O, ri >> 1);
    const uint32_t o_st = mapa(sb, 4) - mapa(sb, 0);
    uint32_t mimg = sb + O_MIMG + lane * 16, l8 = sb + lane * 8;
    float* p_smx = &g_smx[0][h][j][wq * 64 + lane * 2];
    const float* p_smm = &g_smm[0][h][0][lane * 2];
    pin(zld); pin(rs_a); pin(rs_b); pin(o_a); pin(o_b); pin(mimg); pin(l8); pinp(p_smx); pinp(p_smm);

    auto token_pv = [&](int sp) {
      const uint32_t p16 = mimg + (O_P - O_MIMG) + (sp & 1) * 2560, p8 = l8 + O_P + 1024 + (sp & 1) * 2560;
      const uint32_t oa = o_a + (sp & 1) * 8192, ob = o_b + (sp & 1) * 8;
      mbar_wait(bar + 8 * (B_P + (sp & 1)), (sp >> 1) & 1, lim);
      __syncwarp();
      const uint2 m0 = lds_u2(p8), m1 = lds_u2(p8 + 1280);
      const uint4 p0 = lds_u4(p16), p1 = lds_u4(p16 + 1280), p2 = lds_u4(p16 + 1280 + 512);
      float o0[4] = {0.f, 0.f, 0.f, 0.f}, o1[4] = {0.f, 0.f, 0.f, 0.f}, o2[4] = {0.f, 0.f, 0.f, 0.f}, o3[4] = {0.f, 0.f, 0.f, 0.f};
      mma8(o0, m0.x, m0.y, ymp[0]);
      mma8(o1, m0.x, m0.y, ymp[1]);
      mma8(o2, m1.x, m1.y, ymp[0]);
      mma8(o3, m1.x, m1.y, ymp[1]);
      mma16(o0, p0.x, p0.y, p0.z, p0.w, yp[0], yp[2]);
      mma16(o1, p0.x, p0.y, p0.z, p0.w, yp[1], yp[3]);
      mma16(o2, p1.x, p1.y, p1.z, p1.w, yp[0], yp[2]);
      mma16(o3, p1.x, p1.y, p1.z, p1.w, yp[1], yp[3]);
      mma16(o2, p2.x, p2.y, p2.z, p2.w, yp[4], yp[6]);
      mma16(o3, p2.x, p2.y, p2.z, p2.w, yp[5], yp[7]);
      st_async4(oa, o0[0], o0[1], o1[0], o1[1], ob);
      st_async4(oa + o_st, o0[2], o0[3], o1[2], o1[3], ob + o_st);
      st_async4(oa + 2 * o_st, o2[0], o2[1], o3[0], o3[1], ob + 2 * o_st);
      st_async4(oa + 3 * o_st, o2[2], o2[3], o3[2], o3[3], ob + 3 * o_st);
    };

#pragma unroll 1
    for (int s = 0; s < NSEG; s++) {
      const bool rec = s < NSEG - 1;
      uint32_t img = mimg + (s & 1) * 7168, tag = ((s >> 2) + 1) & 3;
      uint32_t ra = rs_a + (s & 1) * 2048, rb = rs_b + (s & 1) * 8;
      float* smx = p_smx + (s & 3) * (NH * 7 * 256);
      const float* pm = p_smm + (s & 3) * (NH * 7 * 64);
      pin(img); pin(tag); pin(ra); pin(rb); pinp(smx); pinp(pm);
      uint32_t zb0[4], zb1[4];
      mbar_wait(bar + 8 * (B_ZX + (s & 1)), (s >> 1) & 1, lim);
      __syncwarp();
      ldsm4(zb0, zld + (s & 1) * 5120);
      ldsm4(zb1, zld + (s & 1) * 5120 + 4 * 640);
      bar_sync(N_MOK, 160);
      {
        uint32_t a0[4], a1[4];
        ldsm4(a0, img + j * 1024);
        ldsm4(a1, img + j * 1024 + 512);
        float e0[4] = {0.f, 0.f, 0.f, 0.f}, e1[4] = {0.f, 0.f, 0.f, 0.f};
        mma16(e0, a0[0], 0, a0[1], 0, zb0[0], zb0[1]);
        mma16(e1, a1[0], 0, a1[1], 0, zb1[0], zb1[1]);
        mma16(e0, a0[2], 0, a0[3], 0, zb0[2], zb0[3]);
        mma16(e1, a1[2], 0, a1[3], 0, zb1[2], zb1[3]);
        if (rec) stg2r(smx, tagf(e0[0] + e1[0], tag), tagf(e0[1] + e1[1], tag));
      }
      if (wq == 0) TS(15);
      bar_sync(N_YM, 256);
      const uint32_t t0 = clk();
      {
        float c[4];
        gemm_m(w, img, c);
        ym[0] = pack2(c[0], c[1]);
        ym[1] = pack2(c[2], c[3]);
      }
      if (wq == 0) TS(4);
      if (s) token_pv(s - 1);
      if (wq == 0) TS(5);
      if (rec) {
        uint32_t vm[14];
        while (clk() - t0 < D_S) {}
        load7(vm, pm, 64);
        bar_sync(N_SX, 256);
        float2 v[4];
#pragma unroll
        for (int n = 0; n < 4; n++) v[n] = lds_f2(l8 + O_SX + n * 256);
        const float mxx = qmax(fmaxf(fmaxf(fmaxf(v[0].x, v[0].y), fmaxf(v[1].x, v[1].y)), fmaxf(fmaxf(v[2].x, v[2].y), fmaxf(v[3].x, v[3].y))));
        const float nb = -mxx * SC2;
        float lx = 0.f;
        uint32_t pa[4];
#pragma unroll
        for (int n = 0; n < 4; n++) {
          const float p0 = ex2(fmaf(v[n].x, SC2, nb)), p1 = ex2(fmaf(v[n].y, SC2, nb));
          lx += p0 + p1;
          pa[n] = pack2(p0, p1);
        }
        float o0[4] = {0.f, 0.f, 0.f, 0.f}, o1[4] = {0.f, 0.f, 0.f, 0.f};
        mma16(o0, pa[0], 0, pa[1], 0, yx[0], yx[2]);
        mma16(o1, pa[0], 0, pa[1], 0, yx[1], yx[3]);
        mma16(o0, pa[2], 0, pa[3], 0, yx[4], yx[6]);
        mma16(o1, pa[2], 0, pa[3], 0, yx[5], yx[7]);
        if (wq == 0) TS(7);
        const float2 sm = sum7(vm, pm, 64, tag, lim);
        if (wq == 0) TS(8);
        const float mx = fmaxf(mxx, qmax(fmaxf(sm.x, sm.y)));
        const float nm = -mx * SC2;
        const float al = ex2(fmaf(mxx, SC2, nm)), p0 = ex2(fmaf(sm.x, SC2, nm)), p1 = ex2(fmaf(sm.y, SC2, nm));
        const uint32_t pp = pack2(p0, p1);
        o0[0] *= al; o0[1] *= al; o1[0] *= al; o1[1] *= al;
        mma8(o0, pp, 0, ym[0]);
        mma8(o1, pp, 0, ym[1]);
        const float inv = __fdividef(1.f, qsum(fmaf(al, lx, p0 + p1)));
        st_async4(ra, o0[0] * inv, o0[1] * inv, o1[0] * inv, o1[1] * inv, rb);
        bar_arrive(N_ZX, 256);
        if (wq == 0) TS(9);
      }
#pragma unroll
      for (int i = 0; i < 8; i++) yp[i] = yx[i];
      ymp[0] = ym[0]; ymp[1] = ym[1];
      if (rec) {
        float d[16];
        mbar_wait(bar + 8 * (B_X + ((s + 1) & 3)), ((s + 1) >> 2) & 1, lim);
        __syncwarp();
        gemm_x(w, sb + ((s + 1) & 3) * XB, d);
#pragma unroll
        for (int i = 0; i < 8; i++) yx[i] = pack2(d[2 * i], d[2 * i + 1]);
        if (wq == 0) TS(10);
      }
    }
    token_pv(NSEG - 1);
    if (lim == 1) g_err = 1;
    __syncwarp();
    cluster_arrive();
    cluster_wait();
  } else {
    asm volatile("setmaxnreg.dec.sync.aligned.u32 72;");
    if (warp == 8) {
      const int u = lane >> 2, comp = lane & 3;
      uint8_t* gm0 = &g_mslot[0][(8 * j + 2 * (h >> 2) + (comp >> 1)) * 128 + (2 * (h & 3) + (u >> 2)) * 16 + ((u & 3) * 2 + (comp & 1)) * 2];
#pragma unroll
      for (int k = 0; k < 4; k++) stg16r(gm0 + k * 7168, 0xffff);
      asm volatile("fence.release.gpu;" ::: "memory");
      if (lane == 0) {
        if (h < 7) tma2d_mc(sb + h * 4096, &tmX, h * 64, 0, bar + 8 * B_X);
#pragma unroll 1
        for (int c = 4; c < 16; c++) {
          const int st = c & 3;
          mbar_wait(bar + 8 * (B_PE + st), ((c >> 2) - 1) & 1, lim);
          mbar_expect(bar + 8 * (B_PF + st), XB);
          tma2d(sb + (st + 1) * XB, (c & 1) ? &tmWv : &tmWk, h * DH + ((c >> 1) & 3) * 64, (c >> 3) * 224, bar + 8 * (B_PF + st));
        }
      }
      __syncwarp();
      cluster_arrive();
      cluster_wait();
      if (lane == 0) {
        for (int k = 1; k < 3; k++) {
          mbar_expect(bar + 8 * (B_X + k), XB);
          if (h < 7) tma2d_mc(sb + k * XB + h * 4096, &tmX, h * 64, k * 32, bar + 8 * (B_X + k));
        }
      }
      uint32_t chk = sb + O_MIMG + lane * 32 + (lane >> 2) * 4, rs0 = sb + O_RS + lane * 4;
      const uint8_t* gsrc = &g_mslot[0][h * 448];
      pin(chk); pin(rs0); pinp(gm0); pinp(gsrc);
#pragma unroll 1
      for (int s = 0; s < NSEG; s++) {
        uint32_t ck = chk + (s & 1) * 7168, redo_a = sb + O_REDO + (s & 1) * 4;
        pin(ck); pin(redo_a);
        uint32_t redo = 0;
        if (s) {
          mbar_wait(bar + 8 * (B_M + (s & 1)), ((s - 1) >> 1) & 1, lim);
          uint32_t v[7];
#pragma unroll
          for (int k = 0; k < 7; k++) v[k] = lds32v(ck + k * 1024);
          const uint32_t mx = __vimax3_u32(__vimax3_u32(v[0], v[1], v[2]), __vimax3_u32(v[3], v[4], v[5]), v[6]);
          if (__builtin_expect(__any_sync(0xffffffffu, mx == 0xffffffffu), 0)) {
            redo = 1;
#pragma unroll 1
            for (int k0 = 0; k0 < 14; k0 += 7) {
              uint32_t t[7][4], left = lim, m2;
              const uint8_t* p = &g_mslot[s & 3][(k0 * 32 + lane) * 16];
              do {
                m2 = 0;
#pragma unroll
                for (int k = 0; k < 7; k++)
                  asm volatile("ld.relaxed.gpu.global.v4.u32 {%0,%1,%2,%3}, [%4];" : "=r"(t[k][0]), "=r"(t[k][1]), "=r"(t[k][2]), "=r"(t[k][3]) : "l"(p + k * 512) : "memory");
#pragma unroll
                for (int k = 0; k < 7; k++) m2 = __vimax3_u32(m2, __vimax3_u32(t[k][0], t[k][1], t[k][2]), t[k][3]);
              } while (m2 == 0xffffffffu && --left);
              lim = left ? lim : 1u;
#pragma unroll
              for (int k = 0; k < 7; k++) sts_u4(sb + O_MIMG + (s & 1) * 7168 + ((k0 + k) * 32 + lane) * 16, t[k][0], t[k][1], t[k][2], t[k][3]);
            }
            __syncwarp();
          }
        }
        if (lane == 0) sts32v(redo_a, redo);
        bar_arrive(N_MOK, 160);
        bar_arrive(N_ZM, 160);
        if (s == NSEG - 1) break;
        uint32_t rb = rs0 + (s & 1) * 2048;
        uint8_t* gm = gm0 + ((s + 1) & 3) * 7168;
        const uint8_t* gs = gsrc + ((s + 1) & 3) * 7168;
        uint32_t mdst = sb + O_MIMG + ((s + 1) & 1) * 7168 + h * 448, mbar = bar + 8 * (B_M + ((s + 1) & 1));
        pin(rb); pinp(gm); pinp(gs); pin(mdst); pin(mbar);
        if (lane == 0) {
          mbar_expect(mbar, 7168);
          uint32_t left = lim;
          while ((int)lds32v(sb + O_C3) < s - 1 && --left) {}
          lim = left ? lim : 1u;
        }
        __syncwarp();
        mbar_wait(bar + 8 * (B_RS + (s & 1)), (s >> 1) & 1, lim);
        TS(11);
        float v[16];
#pragma unroll
        for (int k = 0; k < 16; k++) v[k] = lds_f(rb + k * 128);
        const float sum = (((v[0] + v[1]) + (v[2] + v[3])) + ((v[4] + v[5]) + (v[6] + v[7]))) +
                          (((v[8] + v[9]) + (v[10] + v[11])) + ((v[12] + v[13]) + (v[14] + v[15])));
        stg16r(gm, (uint16_t)(pack2(sum, 0.f) & 0xffff));
        const uint32_t t0 = clk();
        TS(12);
        __syncwarp();
        if (lane == 0) {
          mbar_expect(bar + 8 * (B_RS + (s & 1)), 2048);
          while (clk() - t0 < D_M) {}
          bulk_mc(mdst, gs, 448, mbar);
          if (s + 3 < NSEG) {
            mbar_expect(bar + 8 * (B_X + ((s + 3) & 3)), XB);
            if (h < 7) tma2d_mc(sb + ((s + 3) & 3) * XB + h * 4096, &tmX, h * 64, (s + 3) * 32, bar + 8 * (B_X + ((s + 3) & 3)));
          }
        }
        stg16r(gm0 + ((s + 3) & 3) * 7168, 0xffff);
        __syncwarp();
      }
    } else if (warp < 11) {
      const int mt = warp - 9, q = lane & 3;
      cluster_arrive();
      cluster_wait();
#pragma unroll 1
      for (int s = 0; s < NSEG; s++) {
        const uint32_t* fl = &g_sflag[s & 7][h][0];
        mbar_wait(bar + 8 * (B_T + (s & 1)), (s >> 1) & 1, lim);
        uint32_t left = lim, f;
        do { asm volatile("ld.relaxed.gpu.global.u32 %0, [%1];" : "=r"(f) : "l"(fl) : "memory"); } while (f < 21 && --left);
        lim = left ? lim : 1u;
        __syncwarp();
        const float* sp = &g_sacc[s & 7][h][mt * 640 + lane * 2];
        uint32_t pk[2][5];
        float v[2][10];
#pragma unroll
        for (int rg = 0; rg < 2; rg++)
#pragma unroll
          for (int n = 0; n < 5; n++) {
            uint32_t a = 0, b = 0;
            if (n < 3 || mt) ldg2r(a, b, sp + (rg * 5 + n) * 64);
            v[rg][2 * n] = __uint_as_float(a);
            v[rg][2 * n + 1] = __uint_as_float(b);
          }
#pragma unroll
        for (int rg = 0; rg < 2; rg++) {
          const int row = 16 * mt + 8 * rg + (lane >> 2);
#pragma unroll
          for (int e = 2; e < 10; e++)
            if (8 * ((e >> 1) - 1) + 2 * q + (e & 1) > row) v[rg][e] = MASKV;
          float mx = v[rg][0];
#pragma unroll
          for (int e = 1; e < 10; e++) mx = fmaxf(mx, v[rg][e]);
          mx = qmax(mx);
          const float nb = -mx * SC2;
          float l = 0.f;
#pragma unroll
          for (int e = 0; e < 10; e++) { v[rg][e] = ex2(fmaf(v[rg][e], SC2, nb)); l += v[rg][e]; }
          const float inv = __fdividef(1.f, qsum(l));
#pragma unroll
          for (int n = 0; n < 5; n++) pk[rg][n] = pack2(v[rg][2 * n] * inv, v[rg][2 * n + 1] * inv);
        }
        const uint32_t pb = sb + O_P + (s & 1) * 2560 + mt * 1280;
        sts_u4(pb + lane * 16, pk[0][1], pk[1][1], pk[0][2], pk[1][2]);
        sts_u4(pb + 512 + lane * 16, pk[0][3], pk[1][3], pk[0][4], pk[1][4]);
        sts_u2(pb + 1024 + lane * 8, pk[0][0], pk[1][0]);
        __syncwarp();
        if (lane == 0) mbar_arrive(bar + 8 * (B_P + (s & 1)));
        if (mt == 1) TS(13);
        float* zp = &g_sacc[(s + 4) & 7][h][lane * 2];
        for (int uu = j + 7 * mt; uu < 20; uu += 14) stg2r(zp + uu * 64, 0, 0);
        if (j == 0 && mt == 0 && lane == 0) asm volatile("st.relaxed.gpu.global.u32 [%0], 0;" :: "l"(&g_sflag[(s + 4) & 7][h][0]) : "memory");
        asm volatile("fence.release.gpu;" ::: "memory");
      }
    } else {
      const int t1 = lane >> 4, l16 = lane & 15;
      uint2 gw[7];
#pragma unroll
      for (int k = 0; k < 7; k++) gw[k] = *reinterpret_cast<const uint2*>(gate_w + (k * 16 + l16) * 4);
      const int col = j * 64 + ((lane >> 2) & 3) * 16 + (lane & 3) * 2;
      cluster_arrive();
      cluster_wait();
#pragma unroll 1
      for (int s = 0; s < NSEG; s++) {
        const int tok = s * 32 + 2 * h + t1;
        float z = 0.f;
#pragma unroll
        for (int k = 0; k < 7; k++) {
          const uint2 xv = *reinterpret_cast<const uint2*>(x + tok * DM + (k * 16 + l16) * 4);
          z = fmaf(bf_lo(xv.x), bf_lo(gw[k].x), z); z = fmaf(bf_hi(xv.x), bf_hi(gw[k].x), z);
          z = fmaf(bf_lo(xv.y), bf_lo(gw[k].y), z); z = fmaf(bf_hi(xv.y), bf_hi(gw[k].y), z);
        }
#pragma unroll
        for (int o = 1; o < 16; o <<= 1) z += __shfl_xor_sync(0xffffffffu, z, o);
        const float g = 1.f / (1.f + __expf(-z));
        mbar_wait(bar + 8 * (B_O + (s & 1)), (s >> 1) & 1, lim);
        __syncwarp();
        const uint32_t ob = sb + O_ORS + (s & 1) * 8192 + lane * 16;
        float4 a = lds_f4(ob), b = lds_f4(ob + 512);
#pragma unroll
        for (int k = 2; k < 16; k += 2) {
          const float4 c = lds_f4(ob + k * 512), d = lds_f4(ob + k * 512 + 512);
          a.x += c.x; a.y += c.y; a.z += c.z; a.w += c.w;
          b.x += d.x; b.y += d.y; b.z += d.z; b.w += d.w;
        }
        a.x += b.x; a.y += b.y; a.z += b.z; a.w += b.w;
        __syncwarp();
        if (lane == 0) { mbar_expect(bar + 8 * (B_O + (s & 1)), 8192); sts32v(sb + O_C3, s + 1); }
        float* sp = &g_stash[tok * DM + col];
        *reinterpret_cast<float2*>(sp) = make_float2(g * a.x, g * a.y);
        *reinterpret_cast<float2*>(sp + 8) = make_float2(g * a.z, g * a.w);
        TS(14);
      }
    }
    if (lim == 1) g_err = 1;
    __syncwarp();
    cluster_arrive();
    cluster_wait();
  }
}

constexpr uint32_t F_STAGE = 49152, F_BAR = 4 * F_STAGE, F_G = F_BAR + 128, F_SMEM = F_G + 512 + 1024;

template <int N>
DEVI void ffn_tile(float (&d)[N / 2], uint32_t sb, int wg, int nk, int& it, uint32_t& dead, int lane) {
#pragma unroll 1
  for (int k = 0; k < nk; k++, it++) {
    const int st = it & 3;
    mbar_wait(sb + F_BAR + 8 * st, (it >> 2) & 1, dead);
    __syncwarp();
    const uint64_t da = desc128(sb + st * F_STAGE + wg * 8192, 1), db = desc128(sb + st * F_STAGE + 16384, 512);
    wg_fence();
#pragma unroll
    for (int kk = 0; kk < 4; kk++) {
      if constexpr (N == 256) wgmma_n256_kn(d, da + kk * 2, db + kk * 128, (k | kk) != 0);
      else                    wgmma_n192_kn(d, da + kk * 2, db + kk * 128, (k | kk) != 0);
    }
    wg_commit();
    if (k) { wg_wait<1>(); if (lane == 0) mbar_arrive(sb + F_BAR + 32 + 8 * ((it - 1) & 3)); }
  }
  wg_wait<0>();
  if (lane == 0) mbar_arrive(sb + F_BAR + 32 + 8 * ((it - 1) & 3));
  reg_fence(d);
}

__global__ void __launch_bounds__(384, 1)
ffn_kernel(const __grid_constant__ CUtensorMap tmX, const __grid_constant__ CUtensorMap tmW1,
           const __grid_constant__ CUtensorMap tmH, const __grid_constant__ CUtensorMap tmW2,
           const __nv_bfloat16* __restrict__ x, const __nv_bfloat16* __restrict__ gate_w, __nv_bfloat16* __restrict__ out) {
  extern __shared__ uint8_t smem_raw[];
  const uint32_t sb = (smem_u32(smem_raw) + 1023) & ~1023u;
  const uint32_t hbar = sb + F_BAR + 64;
  uint32_t dead = SPIN_LIMIT;
  const int tid = threadIdx.x, lane = tid & 31, warp = __shfl_sync(0xffffffffu, tid >> 5, 0), r0 = blockIdx.x * 128;
  if (tid == 0) {
    for (int i = 0; i < 4; i++) { mbar_init(sb + F_BAR + 8 * i, 1); mbar_init(sb + F_BAR + 32 + 8 * i, 8); }
    mbar_init(hbar, 256);
    asm volatile("fence.mbarrier_init.release.cluster;" ::: "memory");
    asm volatile("fence.proxy.async.shared::cta;" ::: "memory");
  }
  __syncthreads();
  if (warp >= 8) {
    asm volatile("setmaxnreg.dec.sync.aligned.u32 40;");
    if (tid == 256) {
      int it = 0;
#pragma unroll 1
      for (int t = 0; t < 9; t++) {
        const int nk = t < 7 ? 7 : 28, nb = t < 8 ? 4 : 3;
        if (t == 7) mbar_wait(hbar, 0, dead);
#pragma unroll 1
        for (int k = 0; k < nk; k++, it++) {
          const int st = it & 3;
          const uint32_t fb = sb + F_BAR + 8 * st, a = sb + st * F_STAGE;
          if (it >= 4) mbar_wait(fb + 32, ((it >> 2) - 1) & 1, dead);
          mbar_expect(fb, 16384 + nb * 8192);
          tma2d(a, t < 7 ? &tmX : &tmH, k * 64, r0, fb);
          for (int b = 0; b < nb; b++) tma2d(a + 16384 + b * 8192, t < 7 ? &tmW1 : &tmW2, (t < 7 ? t : t - 7) * 256 + b * 64, k * 64, fb);
        }
      }
    } else if (warp > 8) {
      const int l16 = lane & 15;
      for (int r = (warp - 9) * 2 + (lane >> 4); r < 132; r += 6) {
        const int rr = r < 128 ? r : 127;
        float z = 0.f;
#pragma unroll
        for (int k = 0; k < 7; k++) {
          const uint2 xv = *reinterpret_cast<const uint2*>(x + (r0 + rr) * DM + (k * 16 + l16) * 4);
          const uint2 gv = *reinterpret_cast<const uint2*>(gate_w + (k * 16 + l16) * 4);
          z = fmaf(bf_lo(xv.x), bf_lo(gv.x), z); z = fmaf(bf_hi(xv.x), bf_hi(gv.x), z);
          z = fmaf(bf_lo(xv.y), bf_lo(gv.y), z); z = fmaf(bf_hi(xv.y), bf_hi(gv.y), z);
        }
#pragma unroll
        for (int o = 1; o < 16; o <<= 1) z += __shfl_xor_sync(0xffffffffu, z, o);
        if (l16 == 0) sts32v(sb + F_G + rr * 4, __float_as_uint(1.f - 1.f / (1.f + __expf(-z))));
      }
      __syncwarp();
      bar_arrive(1, 352);
    }
  } else {
    asm volatile("setmaxnreg.inc.sync.aligned.u32 232;");
    const int wg = warp >> 2, row = wg * 64 + (warp & 3) * 16 + (lane >> 2), q = lane & 3;
    int it = 0;
#pragma unroll 1
    for (int t = 0; t < 7; t++) {
      float d[128];
      ffn_tile<256>(d, sb, wg, 7, it, dead, lane);
      __nv_bfloat16* hp = g_h + (size_t)(r0 + row) * DFF + t * 256 + 2 * q;
#pragma unroll
      for (int n = 0; n < 32; n++) {
        *reinterpret_cast<uint32_t*>(hp + n * 8) = pack2(fmaxf(d[4 * n], 0.f), fmaxf(d[4 * n + 1], 0.f));
        *reinterpret_cast<uint32_t*>(hp + 8 * DFF + n * 8) = pack2(fmaxf(d[4 * n + 2], 0.f), fmaxf(d[4 * n + 3], 0.f));
      }
    }
    __threadfence();
    asm volatile("fence.proxy.async;" ::: "memory");
    mbar_arrive(hbar);
    bar_sync(1, 352);
    const float g0 = lds_f(sb + F_G + row * 4), g1 = lds_f(sb + F_G + row * 4 + 32);
    float* bp = g_b + (size_t)(r0 + row) * DM + 2 * q;
    {
      float d[128];
      ffn_tile<256>(d, sb, wg, 28, it, dead, lane);
#pragma unroll
      for (int n = 0; n < 32; n++) {
        *reinterpret_cast<float2*>(bp + n * 8) = make_float2(g0 * d[4 * n], g0 * d[4 * n + 1]);
        *reinterpret_cast<float2*>(bp + 8 * DM + n * 8) = make_float2(g1 * d[4 * n + 2], g1 * d[4 * n + 3]);
      }
    }
    {
      float d[96];
      ffn_tile<192>(d, sb, wg, 28, it, dead, lane);
#pragma unroll
      for (int n = 0; n < 24; n++) {
        *reinterpret_cast<float2*>(bp + 256 + n * 8) = make_float2(g0 * d[4 * n], g0 * d[4 * n + 1]);
        *reinterpret_cast<float2*>(bp + 256 + 8 * DM + n * 8) = make_float2(g1 * d[4 * n + 2], g1 * d[4 * n + 3]);
      }
    }
    bar_sync(2, 256);
    asm volatile("griddepcontrol.wait;" ::: "memory");
    const float4* sa = reinterpret_cast<const float4*>(g_stash + (size_t)r0 * DM);
    const float4* sbp = reinterpret_cast<const float4*>(g_b + (size_t)r0 * DM);
    uint2* op = reinterpret_cast<uint2*>(out + (size_t)r0 * DM);
#pragma unroll 8
    for (int i = tid; i < 128 * DM / 4; i += 256) {
      const float4 a = __ldcg(sa + i), b = __ldcg(sbp + i);
      op[i] = make_uint2(pack2(a.x + b.x, a.y + b.y), pack2(a.z + b.z, a.w + b.w));
    }
  }
}

typedef CUresult (*EncodeFn)(CUtensorMap*, CUtensorMapDataType, cuuint32_t, void*, const cuuint64_t*, const cuuint64_t*,
                             const cuuint32_t*, const cuuint32_t*, CUtensorMapInterleave, CUtensorMapSwizzle,
                             CUtensorMapL2promotion, CUtensorMapFloatOOBfill);

void make_map(EncodeFn fn, CUtensorMap* m, const void* p, uint64_t rows, uint64_t cols, uint32_t box_rows) {
  const cuuint64_t dims[2] = {cols, rows}, strides[1] = {cols * 2};
  const cuuint32_t box[2] = {64, box_rows}, es[2] = {1, 1};
  fn(m, CU_TENSOR_MAP_DATA_TYPE_BFLOAT16, 2, const_cast<void*>(p), dims, strides, box, es, CU_TENSOR_MAP_INTERLEAVE_NONE,
     CU_TENSOR_MAP_SWIZZLE_128B, CU_TENSOR_MAP_L2_PROMOTION_L2_256B, CU_TENSOR_MAP_FLOAT_OOB_FILL_NONE);
}

}

extern "C" void kernel_launch(void* const* d_in, const int* in_sizes, int n_in, void* d_out, int out_size) {
  (void)in_sizes; (void)n_in; (void)out_size;
  const __nv_bfloat16* x = (const __nv_bfloat16*)d_in[0];
  const __nv_bfloat16* mem0 = (const __nv_bfloat16*)d_in[1];
  const __nv_bfloat16* gate_w = (const __nv_bfloat16*)d_in[10];
  static EncodeFn fn = nullptr;
  static void* hptr = nullptr;
  if (!fn) {
    cudaDriverEntryPointQueryResult qr;
    cudaGetDriverEntryPoint("cuTensorMapEncodeTiled", (void**)&fn, cudaEnableDefault, &qr);
    cudaGetSymbolAddress(&hptr, g_h);
    cudaFuncSetAttribute(rmt_kernel, cudaFuncAttributeMaxDynamicSharedMemorySize, T_SMEM);
    cudaFuncSetAttribute(rmt_kernel, cudaFuncAttributeNonPortableClusterSizeAllowed, 1);
    cudaFuncSetAttribute(ffn_kernel, cudaFuncAttributeMaxDynamicSharedMemorySize, F_SMEM);
  }
  CUtensorMap mWq, mWk, mWv, mWo, mX, mXf, mW1, mH, mW2;
  make_map(fn, &mWq, d_in[2], DM, NH * DH, 64);
  make_map(fn, &mWk, d_in[3], DM, NH * DH, 224);
  make_map(fn, &mWv, d_in[4], DM, NH * DH, 224);
  make_map(fn, &mWo, d_in[5], NH * DH, DM, 256);
  make_map(fn, &mX, x, SEQ, DM, 32);
  make_map(fn, &mXf, x, SEQ, DM, 128);
  make_map(fn, &mW1, d_in[8], DM, DFF, 64);
  make_map(fn, &mH, hptr, SEQ, DFF, 128);
  make_map(fn, &mW2, d_in[9], DFF, DM, 64);

  cudaLaunchConfig_t cfg = {};
  cudaLaunchAttribute at[1];
  cfg.gridDim = dim3(112); cfg.blockDim = dim3(384); cfg.dynamicSmemBytes = T_SMEM; cfg.stream = cudaStreamPerThread;
  at[0].id = cudaLaunchAttributeClusterDimension;
  at[0].val.clusterDim.x = 16; at[0].val.clusterDim.y = 1; at[0].val.clusterDim.z = 1;
  cfg.attrs = at; cfg.numAttrs = 1;
  cudaLaunchKernelEx(&cfg, rmt_kernel, mWq, mWk, mWv, mWo, mX, x, mem0, gate_w);

  cfg.gridDim = dim3(16); cfg.dynamicSmemBytes = F_SMEM;
  at[0].id = cudaLaunchAttributeProgrammaticStreamSerialization;
  at[0].val.programmaticStreamSerializationAllowed = 1;
  cudaLaunchKernelEx(&cfg, ffn_kernel, mXf, mW1, mH, mW2, x, gate_w, (__nv_bfloat16*)d_out);
}
```

```cpp
#include <cuda_runtime.h>
#include <cuda_bf16.h>
#include <cuda.h>
#include <stdint.h>

namespace {

#define DEVI __device__ __forceinline__

constexpr int SEQ = 2048, DM = 448, NH = 16, DH = 256, NSEG = 64, DFF = 1792;
constexpr float SC2 = 1.4426950408889634f / 16.0f;
constexpr float MASKV = -1.6e10f;
constexpr int SPIN_LIMIT = 1 << 22;

#define D_M 550
#define D_X 350
#define D_T 700
#define D_SS 130
#define D_S 480

__device__ __align__(1024) uint8_t g_xch_raw[18 * 65536];
DEVI uint8_t* xch(int blk) { return reinterpret_cast<uint8_t*>((reinterpret_cast<uintptr_t>(g_xch_raw) + 65535) & ~(uintptr_t)65535) + blk * 65536; }
constexpr uint32_t XC_R0 = 4096, XC_REG = 16384, XC_TWIN = 8192;
__device__ __align__(1024) float g_sacc[8][NH][1408];
__device__ __align__(1024) float g_stash[SEQ * DM];
__device__ __align__(1024) float g_b[SEQ * DM];
__device__ __align__(1024) __nv_bfloat16 g_h[SEQ * DFF];
__device__ __align__(1024) uint32_t g_mark[NSEG][112];
__device__ uint32_t g_ticket[2];
__device__ int g_err;
#define TS(i)
#define PTS(i)

DEVI uint32_t smem_u32(const void* p) { return (uint32_t)__cvta_generic_to_shared(p); }
DEVI uint32_t clk() { uint32_t c; asm volatile("mov.u32 %0, %%clock;" : "=r"(c) :: "memory"); return c; }
DEVI void mbar_init(uint32_t bar, uint32_t cnt) { asm volatile("mbarrier.init.shared::cta.b64 [%0], %1;" :: "r"(bar), "r"(cnt) : "memory"); }
DEVI void mbar_expect(uint32_t bar, uint32_t bytes) { asm volatile("mbarrier.arrive.expect_tx.shared::cta.b64 _, [%0], %1;" :: "r"(bar), "r"(bytes) : "memory"); }
DEVI void mbar_arrive(uint32_t bar) { asm volatile("mbarrier.arrive.shared::cta.b64 _, [%0];" :: "r"(bar) : "memory"); }
DEVI uint32_t lds32v(uint32_t a) { uint32_t v; asm volatile("ld.volatile.shared::cta.u32 %0, [%1];" : "=r"(v) : "r"(a) : "memory"); return v; }
DEVI void sts32v(uint32_t a, uint32_t v) { asm volatile("st.volatile.shared::cta.u32 [%0], %1;" :: "r"(a), "r"(v) : "memory"); }
DEVI void mbar_wait(uint32_t bar, uint32_t par, int& lim) {
  asm volatile("{\n.reg .pred p, q;\nWAIT_LOOP:\n"
               "mbarrier.try_wait.parity.shared::cta.b64 p, [%1], %2;\n"
               "sub.s32 %0, %0, 1;\nsetp.gt.and.s32 q, %0, 0, !p;\n@q bra.uni WAIT_LOOP;\n}"
               : "+r"(lim) : "r"(bar), "r"(par) : "memory");
}
DEVI void mbar_wait1(uint32_t bar, uint32_t par, int& lim) {
  asm volatile("{\n.reg .pred p, q;\nWAIT_LOOP:\n"
               "mbarrier.try_wait.parity.shared::cta.b64 p, [%1], %2;\n"
               "sub.s32 %0, %0, 1;\nsetp.gt.and.s32 q, %0, 0, !p;\n@q bra WAIT_LOOP;\n}"
               : "+r"(lim) : "r"(bar), "r"(par) : "memory");
}
DEVI bool elect() { uint32_t p; asm volatile("{\n.reg .pred p;\nelect.sync _|p, 0xffffffff;\nselp.u32 %0, 1, 0, p;\n}" : "=r"(p)); return p; }
DEVI bool bar_or(int id, int n, bool v) {
  uint32_t r;
  asm volatile("{\n.reg .pred p, q;\nsetp.ne.u32 q, %3, 0;\nbar.red.or.pred p, %1, %2, q;\nselp.u32 %0, 1, 0, p;\n}"
               : "=r"(r) : "r"(id), "r"(n), "r"((uint32_t)v) : "memory");
  return r;
}
DEVI void delay_until(uint32_t t0, uint32_t d) {
  asm volatile("{\n.reg .pred p;\n.reg .u32 t;\nDELAY_LOOP:\nmov.u32 t, %%clock;\nsub.u32 t, t, %0;\nsetp.lt.u32 p, t, %1;\n@p bra.uni DELAY_LOOP;\n}"
               :: "r"(t0), "r"(d) : "memory");
}
DEVI float rcp(float x) { float y; asm("rcp.approx.ftz.f32 %0, %1;" : "=f"(y) : "f"(x)); return y; }
template <class T> DEVI void pin(T& v) { asm volatile("" : "+r"(v)); }
template <class T> DEVI void pinp(T*& v) { asm volatile("" : "+l"(v)); }
DEVI void bar_sync(int id, int n) { asm volatile("bar.sync %0, %1;" :: "r"(id), "r"(n) : "memory"); }
DEVI void bar_arrive(int id, int n) { asm volatile("bar.arrive %0, %1;" :: "r"(id), "r"(n) : "memory"); }
DEVI void cluster_arrive_relaxed() { asm volatile("barrier.cluster.arrive.relaxed.aligned;" ::: "memory"); }
DEVI void cluster_arrive() { asm volatile("barrier.cluster.arrive.release.aligned;" ::: "memory"); }
DEVI void cluster_wait() { asm volatile("barrier.cluster.wait.acquire.aligned;" ::: "memory"); }
DEVI uint32_t mapa(uint32_t a, uint32_t r) { uint32_t o; asm("mapa.shared::cluster.u32 %0, %1, %2;" : "=r"(o) : "r"(a), "r"(r)); return o; }
DEVI uint32_t pack2(float lo, float hi) { uint32_t r; asm("cvt.rn.bf16x2.f32 %0, %1, %2;" : "=r"(r) : "f"(hi), "f"(lo)); return r; }
DEVI float ex2(float x) { float y; asm("ex2.approx.ftz.f32 %0, %1;" : "=f"(y) : "f"(x)); return y; }
DEVI float bf_lo(uint32_t v) { return __uint_as_float(v << 16); }
DEVI float bf_hi(uint32_t v) { return __uint_as_float(v & 0xffff0000u); }
DEVI void ldsm4(uint32_t (&r)[4], uint32_t a) {
  asm volatile("ldmatrix.sync.aligned.m8n8.x4.shared.b16 {%0,%1,%2,%3}, [%4];" : "=r"(r[0]), "=r"(r[1]), "=r"(r[2]), "=r"(r[3]) : "r"(a) : "memory");
}
DEVI void stsm4t(uint32_t a, uint32_t r0, uint32_t r1, uint32_t r2, uint32_t r3) {
  asm volatile("stmatrix.sync.aligned.m8n8.x4.trans.shared.b16 [%0], {%1,%2,%3,%4};" :: "r"(a), "r"(r0), "r"(r1), "r"(r2), "r"(r3) : "memory");
}
DEVI void stsm2t(uint32_t a, uint32_t r0, uint32_t r1) {
  asm volatile("stmatrix.sync.aligned.m8n8.x2.trans.shared.b16 [%0], {%1,%2};" :: "r"(a), "r"(r0), "r"(r1) : "memory");
}
DEVI void mma16(float (&c)[4], uint32_t a0, uint32_t a1, uint32_t a2, uint32_t a3, uint32_t b0, uint32_t b1) {
  asm("mma.sync.aligned.m16n8k16.row.col.f32.bf16.bf16.f32 {%0,%1,%2,%3},{%4,%5,%6,%7},{%8,%9},{%0,%1,%2,%3};"
      : "+f"(c[0]), "+f"(c[1]), "+f"(c[2]), "+f"(c[3]) : "r"(a0), "r"(a1), "r"(a2), "r"(a3), "r"(b0), "r"(b1));
}
DEVI void mma8(float (&c)[4], uint32_t a0, uint32_t a1, uint32_t b0) {
  asm("mma.sync.aligned.m16n8k8.row.col.f32.bf16.bf16.f32 {%0,%1,%2,%3},{%4,%5},{%6},{%0,%1,%2,%3};"
      : "+f"(c[0]), "+f"(c[1]), "+f"(c[2]), "+f"(c[3]) : "r"(a0), "r"(a1), "r"(b0));
}
DEVI void mma16v(float (&c)[4], uint32_t a0, uint32_t a1, uint32_t a2, uint32_t a3, uint32_t b0, uint32_t b1) {
  asm volatile("mma.sync.aligned.m16n8k16.row.col.f32.bf16.bf16.f32 {%0,%1,%2,%3},{%4,%5,%6,%7},{%8,%9},{%0,%1,%2,%3};"
      : "+f"(c[0]), "+f"(c[1]), "+f"(c[2]), "+f"(c[3]) : "r"(a0), "r"(a1), "r"(a2), "r"(a3), "r"(b0), "r"(b1));
}
DEVI void mma8v(float (&c)[4], uint32_t a0, uint32_t a1, uint32_t b0) {
  asm volatile("mma.sync.aligned.m16n8k8.row.col.f32.bf16.bf16.f32 {%0,%1,%2,%3},{%4,%5},{%6},{%0,%1,%2,%3};"
      : "+f"(c[0]), "+f"(c[1]), "+f"(c[2]), "+f"(c[3]) : "r"(a0), "r"(a1), "r"(b0));
}
DEVI float2 mma_rows8(const uint32_t (&a0)[4], const uint32_t (&a1)[4], const uint32_t (&b0)[4], const uint32_t (&b1)[4]) {
  float e0[4] = {0.f, 0.f, 0.f, 0.f}, e1[4] = {0.f, 0.f, 0.f, 0.f}, e2[4] = {0.f, 0.f, 0.f, 0.f}, e3[4] = {0.f, 0.f, 0.f, 0.f};
  mma16v(e0, a0[0], a0[1], a0[2], a0[3], b0[0], b0[1]);
  mma16v(e1, a0[0], a0[1], a0[2], a0[3], b0[2], b0[3]);
  mma16v(e2, a1[0], a1[1], a1[2], a1[3], b1[0], b1[1]);
  mma16v(e3, a1[0], a1[1], a1[2], a1[3], b1[2], b1[3]);
  return make_float2((e0[0] + e1[2]) + (e2[0] + e3[2]), (e0[1] + e1[3]) + (e2[1] + e3[3]));
}
DEVI void wg_fence() { asm volatile("wgmma.fence.sync.aligned;" ::: "memory"); }
DEVI void wg_commit() { asm volatile("wgmma.commit_group.sync.aligned;" ::: "memory"); }
template <int N> DEVI void wg_wait() { asm volatile("wgmma.wait_group.sync.aligned %0;" :: "n"(N) : "memory"); }
template <int N> DEVI void reg_fence(float (&d)[N]) {
#pragma unroll
  for (int i = 0; i < N; i++) asm volatile("" : "+f"(d[i]) :: "memory");
}
DEVI uint64_t desc128(uint32_t addr, uint32_t lbo16) {
  return (uint64_t)((addr >> 4) & 0x3fff) | ((uint64_t)lbo16 << 16) | (64ull << 32) | (1ull << 62);
}
DEVI void tma2d(uint32_t dst, const CUtensorMap* tm, int c0, int c1, uint32_t bar) {
  asm volatile("cp.async.bulk.tensor.2d.shared::cluster.global.mbarrier::complete_tx::bytes [%0], [%1, {%2, %3}], [%4];"
               :: "r"(dst), "l"(tm), "r"(c0), "r"(c1), "r"(bar) : "memory");
}
DEVI void tma2d_mc(uint32_t dst, const CUtensorMap* tm, int c0, int c1, uint32_t bar) {
  asm volatile("cp.async.bulk.tensor.2d.shared::cluster.global.mbarrier::complete_tx::bytes.multicast::cluster [%0], [%1, {%2, %3}], [%4], %5;"
               :: "r"(dst), "l"(tm), "r"(c0), "r"(c1), "r"(bar), "h"((uint16_t)0xffff) : "memory");
}
DEVI void bulk_mc(uint32_t dst, const void* src, uint32_t bytes, uint32_t bar) {
  asm volatile("cp.async.bulk.shared::cluster.global.mbarrier::complete_tx::bytes.multicast::cluster [%0], [%1], %2, [%3], %4;"
               :: "r"(dst), "l"(src), "r"(bytes), "r"(bar), "h"((uint16_t)0xffff) : "memory");
}
DEVI void st_async4(uint32_t a, float x, float y, float z, float w, uint32_t bar) {
  asm volatile("st.async.weak.shared::cluster.mbarrier::complete_tx::bytes.v4.f32 [%0], {%1,%2,%3,%4}, [%5];"
               :: "r"(a), "f"(x), "f"(y), "f"(z), "f"(w), "r"(bar) : "memory");
}
DEVI void st_async4u(uint32_t a, uint32_t x, uint32_t y, uint32_t z, uint32_t w, uint32_t bar) {
  asm volatile("st.async.weak.shared::cluster.mbarrier::complete_tx::bytes.v4.b32 [%0], {%1,%2,%3,%4}, [%5];"
               :: "r"(a), "r"(x), "r"(y), "r"(z), "r"(w), "r"(bar) : "memory");
}
DEVI uint32_t ldg1r(const void* p) { uint32_t v; asm volatile("ld.relaxed.gpu.global.u32 %0, [%1];" : "=r"(v) : "l"(p) : "memory"); return v; }
DEVI uint32_t exch_release(uint32_t* p, uint32_t v) { uint32_t o; asm volatile("atom.release.gpu.global.exch.b32 %0, [%1], %2;" : "=r"(o) : "l"(p), "r"(v) : "memory"); return o; }
DEVI uint32_t near_copy(uint8_t* blk) {
  uint32_t best[2] = {~0u, ~0u}, v = 0;
#pragma unroll 1
  for (int i = 0; i < 24; i++) {
    const uint8_t* p = blk + XC_R0 + 7936 + (i & 1) * XC_TWIN + (v & 4);
    const uint32_t t0 = clk();
    asm volatile("atom.relaxed.gpu.global.and.b32 %0, [%1], 0;" : "=r"(v) : "l"(p) : "memory");
    uint32_t t1;
    asm volatile("{\n.reg .pred p;\nPROBE_WAIT:\nsetp.eq.u32 p, %1, 0x5a5a5a5a;\n@p nanosleep.u32 32;\nmov.u32 %0, %%clock;\n}" : "=r"(t1) : "r"(v) : "memory");
    const uint32_t d = t1 - t0;
    if (i & 1) best[1] = min(best[1], d); else best[0] = min(best[0], d);
  }
  return best[1] < best[0] ? XC_TWIN : 0;
}
DEVI void tma2d_prefetch(const CUtensorMap* tm, int c0, int c1) {
  asm volatile("cp.async.bulk.prefetch.tensor.2d.L2.global [%0, {%1, %2}];" :: "l"(tm), "r"(c0), "r"(c1) : "memory");
}
DEVI void ldg2r(uint32_t& x, uint32_t& y, const void* p) { asm volatile("ld.relaxed.gpu.global.v2.u32 {%0,%1}, [%2];" : "=r"(x), "=r"(y) : "l"(p) : "memory"); }
DEVI void stg2r(void* p, uint32_t x, uint32_t y) { asm volatile("st.relaxed.gpu.global.v2.u32 [%0], {%1,%2};" :: "l"(p), "r"(x), "r"(y) : "memory"); }
DEVI void stg16r(void* p, uint16_t v) { asm volatile("st.relaxed.gpu.global.u16 [%0], %1;" :: "l"(p), "h"(v) : "memory"); }
DEVI void red2(float* p, float x, float y) { asm volatile("red.relaxed.gpu.global.add.v2.f32 [%0], {%1,%2};" :: "l"(p), "f"(x), "f"(y) : "memory"); }
DEVI float lds_f(uint32_t a) { float v; asm volatile("ld.shared.f32 %0, [%1];" : "=f"(v) : "r"(a) : "memory"); return v; }
DEVI float2 lds_f2(uint32_t a) { float2 v; asm volatile("ld.shared.v2.f32 {%0,%1}, [%2];" : "=f"(v.x), "=f"(v.y) : "r"(a) : "memory"); return v; }
DEVI float2 lds_f2v(uint32_t a) { float2 v; asm volatile("ld.volatile.shared.v2.f32 {%0,%1}, [%2];" : "=f"(v.x), "=f"(v.y) : "r"(a) : "memory"); return v; }
DEVI float4 lds_f4(uint32_t a) { float4 v; asm volatile("ld.shared.v4.f32 {%0,%1,%2,%3}, [%4];" : "=f"(v.x), "=f"(v.y), "=f"(v.z), "=f"(v.w) : "r"(a) : "memory"); return v; }
DEVI uint2 lds_u2(uint32_t a) { uint2 v; asm volatile("ld.shared.v2.u32 {%0,%1}, [%2];" : "=r"(v.x), "=r"(v.y) : "r"(a) : "memory"); return v; }
DEVI uint4 lds_u4(uint32_t a) { uint4 v; asm volatile("ld.shared.v4.u32 {%0,%1,%2,%3}, [%4];" : "=r"(v.x), "=r"(v.y), "=r"(v.z), "=r"(v.w) : "r"(a) : "memory"); return v; }
DEVI void sts_f2(uint32_t a, float x, float y) { asm volatile("st.shared.v2.f32 [%0], {%1,%2};" :: "r"(a), "f"(x), "f"(y) : "memory"); }
DEVI void sts_u2(uint32_t a, uint32_t x, uint32_t y) { asm volatile("st.shared.v2.u32 [%0], {%1,%2};" :: "r"(a), "r"(x), "r"(y) : "memory"); }
DEVI void sts_u4(uint32_t a, uint32_t x, uint32_t y, uint32_t z, uint32_t w) { asm volatile("st.shared.v4.u32 [%0], {%1,%2,%3,%4};" :: "r"(a), "r"(x), "r"(y), "r"(z), "r"(w) : "memory"); }
DEVI uint32_t tagf(float v, uint32_t tag) { return (__float_as_uint(v) & ~3u) | tag; }
DEVI float qmax(float v) { v = fmaxf(v, __shfl_xor_sync(0xffffffffu, v, 1)); return fmaxf(v, __shfl_xor_sync(0xffffffffu, v, 2)); }
DEVI float qsum(float v) { v += __shfl_xor_sync(0xffffffffu, v, 1); return v + __shfl_xor_sync(0xffffffffu, v, 2); }

__device__ __forceinline__ void wgmma_n224_kk(float (&d)[112], uint64_t da, uint64_t db, int sc) {
  asm volatile("{\n.reg .pred p;\nsetp.ne.b32 p, %114, 0;\n"
    "wgmma.mma_async.sync.aligned.m64n224k16.f32.bf16.bf16 {%0,%1,%2,%3,%4,%5,%6,%7,%8,%9,%10,%11,%12,%13,%14,%15,%16,%17,%18,%19,%20,%21,%22,%23,%24,%25,%26,%27,%28,%29,%30,%31,%32,%33,%34,%35,%36,%37,%38,%39,%40,%41,%42,%43,%44,%45,%46,%47,%48,%49,%50,%51,%52,%53,%54,%55,%56,%57,%58,%59,%60,%61,%62,%63,%64,%65,%66,%67,%68,%69,%70,%71,%72,%73,%74,%75,%76,%77,%78,%79,%80,%81,%82,%83,%84,%85,%86,%87,%88,%89,%90,%91,%92,%93,%94,%95,%96,%97,%98,%99,%100,%101,%102,%103,%104,%105,%106,%107,%108,%109,%110,%111}, %112, %113, p, 1, 1, 0, 0;\n}"
    : "+f"(d[0]),"+f"(d[1]),"+f"(d[2]),"+f"(d[3]),"+f"(d[4]),"+f"(d[5]),"+f"(d[6]),"+f"(d[7]),"+f"(d[8]),"+f"(d[9]),"+f"(d[10]),"+f"(d[11]),"+f"(d[12]),"+f"(d[13]),"+f"(d[14]),"+f"(d[15]),"+f"(d[16]),"+f"(d[17]),"+f"(d[18]),"+f"(d[19]),"+f"(d[20]),"+f"(d[21]),"+f"(d[22]),"+f"(d[23]),"+f"(d[24]),"+f"(d[25]),"+f"(d[26]),"+f"(d[27]),"+f"(d[28]),"+f"(d[29]),"+f"(d[30]),"+f"(d[31]),"+f"(d[32]),"+f"(d[33]),"+f"(d[34]),"+f"(d[35]),"+f"(d[36]),"+f"(d[37]),"+f"(d[38]),"+f"(d[39]),"+f"(d[40]),"+f"(d[41]),"+f"(d[42]),"+f"(d[43]),"+f"(d[44]),"+f"(d[45]),"+f"(d[46]),"+f"(d[47]),"+f"(d[48]),"+f"(d[49]),"+f"(d[50]),"+f"(d[51]),"+f"(d[52]),"+f"(d[53]),"+f"(d[54]),"+f"(d[55]),"+f"(d[56]),"+f"(d[57]),"+f"(d[58]),"+f"(d[59]),"+f"(d[60]),"+f"(d[61]),"+f"(d[62]),"+f"(d[63]),"+f"(d[64]),"+f"(d[65]),"+f"(d[66]),"+f"(d[67]),"+f"(d[68]),"+f"(d[69]),"+f"(d[70]),"+f"(d[71]),"+f"(d[72]),"+f"(d[73]),"+f"(d[74]),"+f"(d[75]),"+f"(d[76]),"+f"(d[77]),"+f"(d[78]),"+f"(d[79]),"+f"(d[80]),"+f"(d[81]),"+f"(d[82]),"+f"(d[83]),"+f"(d[84]),"+f"(d[85]),"+f"(d[86]),"+f"(d[87]),"+f"(d[88]),"+f"(d[89]),"+f"(d[90]),"+f"(d[91]),"+f"(d[92]),"+f"(d[93]),"+f"(d[94]),"+f"(d[95]),"+f"(d[96]),"+f"(d[97]),"+f"(d[98]),"+f"(d[99]),"+f"(d[100]),"+f"(d[101]),"+f"(d[102]),"+f"(d[103]),"+f"(d[104]),"+f"(d[105]),"+f"(d[106]),"+f"(d[107]),"+f"(d[108]),"+f"(d[109]),"+f"(d[110]),"+f"(d[111])
    : "l"(da),"l"(db),"r"(sc));
}
__device__ __forceinline__ void wgmma_n224_mk(float (&d)[112], uint64_t da, uint64_t db, int sc) {
  asm volatile("{\n.reg .pred p;\nsetp.ne.b32 p, %114, 0;\n"
    "wgmma.mma_async.sync.aligned.m64n224k16.f32.bf16.bf16 {%0,%1,%2,%3,%4,%5,%6,%7,%8,%9,%10,%11,%12,%13,%14,%15,%16,%17,%18,%19,%20,%21,%22,%23,%24,%25,%26,%27,%28,%29,%30,%31,%32,%33,%34,%35,%36,%37,%38,%39,%40,%41,%42,%43,%44,%45,%46,%47,%48,%49,%50,%51,%52,%53,%54,%55,%56,%57,%58,%59,%60,%61,%62,%63,%64,%65,%66,%67,%68,%69,%70,%71,%72,%73,%74,%75,%76,%77,%78,%79,%80,%81,%82,%83,%84,%85,%86,%87,%88,%89,%90,%91,%92,%93,%94,%95,%96,%97,%98,%99,%100,%101,%102,%103,%104,%105,%106,%107,%108,%109,%110,%111}, %112, %113, p, 1, 1, 1, 0;\n}"
    : "+f"(d[0]),"+f"(d[1]),"+f"(d[2]),"+f"(d[3]),"+f"(d[4]),"+f"(d[5]),"+f"(d[6]),"+f"(d[7]),"+f"(d[8]),"+f"(d[9]),"+f"(d[10]),"+f"(d[11]),"+f"(d[12]),"+f"(d[13]),"+f"(d[14]),"+f"(d[15]),"+f"(d[16]),"+f"(d[17]),"+f"(d[18]),"+f"(d[19]),"+f"(d[20]),"+f"(d[21]),"+f"(d[22]),"+f"(d[23]),"+f"(d[24]),"+f"(d[25]),"+f"(d[26]),"+f"(d[27]),"+f"(d[28]),"+f"(d[29]),"+f"(d[30]),"+f"(d[31]),"+f"(d[32]),"+f"(d[33]),"+f"(d[34]),"+f"(d[35]),"+f"(d[36]),"+f"(d[37]),"+f"(d[38]),"+f"(d[39]),"+f"(d[40]),"+f"(d[41]),"+f"(d[42]),"+f"(d[43]),"+f"(d[44]),"+f"(d[45]),"+f"(d[46]),"+f"(d[47]),"+f"(d[48]),"+f"(d[49]),"+f"(d[50]),"+f"(d[51]),"+f"(d[52]),"+f"(d[53]),"+f"(d[54]),"+f"(d[55]),"+f"(d[56]),"+f"(d[57]),"+f"(d[58]),"+f"(d[59]),"+f"(d[60]),"+f"(d[61]),"+f"(d[62]),"+f"(d[63]),"+f"(d[64]),"+f"(d[65]),"+f"(d[66]),"+f"(d[67]),"+f"(d[68]),"+f"(d[69]),"+f"(d[70]),"+f"(d[71]),"+f"(d[72]),"+f"(d[73]),"+f"(d[74]),"+f"(d[75]),"+f"(d[76]),"+f"(d[77]),"+f"(d[78]),"+f"(d[79]),"+f"(d[80]),"+f"(d[81]),"+f"(d[82]),"+f"(d[83]),"+f"(d[84]),"+f"(d[85]),"+f"(d[86]),"+f"(d[87]),"+f"(d[88]),"+f"(d[89]),"+f"(d[90]),"+f"(d[91]),"+f"(d[92]),"+f"(d[93]),"+f"(d[94]),"+f"(d[95]),"+f"(d[96]),"+f"(d[97]),"+f"(d[98]),"+f"(d[99]),"+f"(d[100]),"+f"(d[101]),"+f"(d[102]),"+f"(d[103]),"+f"(d[104]),"+f"(d[105]),"+f"(d[106]),"+f"(d[107]),"+f"(d[108]),"+f"(d[109]),"+f"(d[110]),"+f"(d[111])
    : "l"(da),"l"(db),"r"(sc));
}
__device__ __forceinline__ void wgmma_n32_rs(float (&d)[16], const uint32_t (&a)[4], uint64_t db, int sc) {
  asm volatile("{\n.reg .pred p;\nsetp.ne.b32 p, %21, 0;\n"
    "wgmma.mma_async.sync.aligned.m64n32k16.f32.bf16.bf16 {%0,%1,%2,%3,%4,%5,%6,%7,%8,%9,%10,%11,%12,%13,%14,%15}, {%16,%17,%18,%19}, %20, p, 1, 1, 0;\n}"
    : "+f"(d[0]),"+f"(d[1]),"+f"(d[2]),"+f"(d[3]),"+f"(d[4]),"+f"(d[5]),"+f"(d[6]),"+f"(d[7]),"+f"(d[8]),"+f"(d[9]),"+f"(d[10]),"+f"(d[11]),"+f"(d[12]),"+f"(d[13]),"+f"(d[14]),"+f"(d[15])
    : "r"(a[0]),"r"(a[1]),"r"(a[2]),"r"(a[3]),"l"(db),"r"(sc));
}
__device__ __forceinline__ void wgmma_n256_kn(float (&d)[128], uint64_t da, uint64_t db, int sc) {
  asm volatile("{\n.reg .pred p;\nsetp.ne.b32 p, %130, 0;\n"
    "wgmma.mma_async.sync.aligned.m64n256k16.f32.bf16.bf16 {%0,%1,%2,%3,%4,%5,%6,%7,%8,%9,%10,%11,%12,%13,%14,%15,%16,%17,%18,%19,%20,%21,%22,%23,%24,%25,%26,%27,%28,%29,%30,%31,%32,%33,%34,%35,%36,%37,%38,%39,%40,%41,%42,%43,%44,%45,%46,%47,%48,%49,%50,%51,%52,%53,%54,%55,%56,%57,%58,%59,%60,%61,%62,%63,%64,%65,%66,%67,%68,%69,%70,%71,%72,%73,%74,%75,%76,%77,%78,%79,%80,%81,%82,%83,%84,%85,%86,%87,%88,%89,%90,%91,%92,%93,%94,%95,%96,%97,%98,%99,%100,%101,%102,%103,%104,%105,%106,%107,%108,%109,%110,%111,%112,%113,%114,%115,%116,%117,%118,%119,%120,%121,%122,%123,%124,%125,%126,%127}, %128, %129, p, 1, 1, 0, 1;\n}"
    : "+f"(d[0]),"+f"(d[1]),"+f"(d[2]),"+f"(d[3]),"+f"(d[4]),"+f"(d[5]),"+f"(d[6]),"+f"(d[7]),"+f"(d[8]),"+f"(d[9]),"+f"(d[10]),"+f"(d[11]),"+f"(d[12]),"+f"(d[13]),"+f"(d[14]),"+f"(d[15]),"+f"(d[16]),"+f"(d[17]),"+f"(d[18]),"+f"(d[19]),"+f"(d[20]),"+f"(d[21]),"+f"(d[22]),"+f"(d[23]),"+f"(d[24]),"+f"(d[25]),"+f"(d[26]),"+f"(d[27]),"+f"(d[28]),"+f"(d[29]),"+f"(d[30]),"+f"(d[31]),"+f"(d[32]),"+f"(d[33]),"+f"(d[34]),"+f"(d[35]),"+f"(d[36]),"+f"(d[37]),"+f"(d[38]),"+f"(d[39]),"+f"(d[40]),"+f"(d[41]),"+f"(d[42]),"+f"(d[43]),"+f"(d[44]),"+f"(d[45]),"+f"(d[46]),"+f"(d[47]),"+f"(d[48]),"+f"(d[49]),"+f"(d[50]),"+f"(d[51]),"+f"(d[52]),"+f"(d[53]),"+f"(d[54]),"+f"(d[55]),"+f"(d[56]),"+f"(d[57]),"+f"(d[58]),"+f"(d[59]),"+f"(d[60]),"+f"(d[61]),"+f"(d[62]),"+f"(d[63]),"+f"(d[64]),"+f"(d[65]),"+f"(d[66]),"+f"(d[67]),"+f"(d[68]),"+f"(d[69]),"+f"(d[70]),"+f"(d[71]),"+f"(d[72]),"+f"(d[73]),"+f"(d[74]),"+f"(d[75]),"+f"(d[76]),"+f"(d[77]),"+f"(d[78]),"+f"(d[79]),"+f"(d[80]),"+f"(d[81]),"+f"(d[82]),"+f"(d[83]),"+f"(d[84]),"+f"(d[85]),"+f"(d[86]),"+f"(d[87]),"+f"(d[88]),"+f"(d[89]),"+f"(d[90]),"+f"(d[91]),"+f"(d[92]),"+f"(d[93]),"+f"(d[94]),"+f"(d[95]),"+f"(d[96]),"+f"(d[97]),"+f"(d[98]),"+f"(d[99]),"+f"(d[100]),"+f"(d[101]),"+f"(d[102]),"+f"(d[103]),"+f"(d[104]),"+f"(d[105]),"+f"(d[106]),"+f"(d[107]),"+f"(d[108]),"+f"(d[109]),"+f"(d[110]),"+f"(d[111]),"+f"(d[112]),"+f"(d[113]),"+f"(d[114]),"+f"(d[115]),"+f"(d[116]),"+f"(d[117]),"+f"(d[118]),"+f"(d[119]),"+f"(d[120]),"+f"(d[121]),"+f"(d[122]),"+f"(d[123]),"+f"(d[124]),"+f"(d[125]),"+f"(d[126]),"+f"(d[127])
    : "l"(da),"l"(db),"r"(sc));
}
__device__ __forceinline__ void wgmma_n192_kn(float (&d)[96], uint64_t da, uint64_t db, int sc) {
  asm volatile("{\n.reg .pred p;\nsetp.ne.b32 p, %98, 0;\n"
    "wgmma.mma_async.sync.aligned.m64n192k16.f32.bf16.bf16 {%0,%1,%2,%3,%4,%5,%6,%7,%8,%9,%10,%11,%12,%13,%14,%15,%16,%17,%18,%19,%20,%21,%22,%23,%24,%25,%26,%27,%28,%29,%30,%31,%32,%33,%34,%35,%36,%37,%38,%39,%40,%41,%42,%43,%44,%45,%46,%47,%48,%49,%50,%51,%52,%53,%54,%55,%56,%57,%58,%59,%60,%61,%62,%63,%64,%65,%66,%67,%68,%69,%70,%71,%72,%73,%74,%75,%76,%77,%78,%79,%80,%81,%82,%83,%84,%85,%86,%87,%88,%89,%90,%91,%92,%93,%94,%95}, %96, %97, p, 1, 1, 0, 1;\n}"
    : "+f"(d[0]),"+f"(d[1]),"+f"(d[2]),"+f"(d[3]),"+f"(d[4]),"+f"(d[5]),"+f"(d[6]),"+f"(d[7]),"+f"(d[8]),"+f"(d[9]),"+f"(d[10]),"+f"(d[11]),"+f"(d[12]),"+f"(d[13]),"+f"(d[14]),"+f"(d[15]),"+f"(d[16]),"+f"(d[17]),"+f"(d[18]),"+f"(d[19]),"+f"(d[20]),"+f"(d[21]),"+f"(d[22]),"+f"(d[23]),"+f"(d[24]),"+f"(d[25]),"+f"(d[26]),"+f"(d[27]),"+f"(d[28]),"+f"(d[29]),"+f"(d[30]),"+f"(d[31]),"+f"(d[32]),"+f"(d[33]),"+f"(d[34]),"+f"(d[35]),"+f"(d[36]),"+f"(d[37]),"+f"(d[38]),"+f"(d[39]),"+f"(d[40]),"+f"(d[41]),"+f"(d[42]),"+f"(d[43]),"+f"(d[44]),"+f"(d[45]),"+f"(d[46]),"+f"(d[47]),"+f"(d[48]),"+f"(d[49]),"+f"(d[50]),"+f"(d[51]),"+f"(d[52]),"+f"(d[53]),"+f"(d[54]),"+f"(d[55]),"+f"(d[56]),"+f"(d[57]),"+f"(d[58]),"+f"(d[59]),"+f"(d[60]),"+f"(d[61]),"+f"(d[62]),"+f"(d[63]),"+f"(d[64]),"+f"(d[65]),"+f"(d[66]),"+f"(d[67]),"+f"(d[68]),"+f"(d[69]),"+f"(d[70]),"+f"(d[71]),"+f"(d[72]),"+f"(d[73]),"+f"(d[74]),"+f"(d[75]),"+f"(d[76]),"+f"(d[77]),"+f"(d[78]),"+f"(d[79]),"+f"(d[80]),"+f"(d[81]),"+f"(d[82]),"+f"(d[83]),"+f"(d[84]),"+f"(d[85]),"+f"(d[86]),"+f"(d[87]),"+f"(d[88]),"+f"(d[89]),"+f"(d[90]),"+f"(d[91]),"+f"(d[92]),"+f"(d[93]),"+f"(d[94]),"+f"(d[95])
    : "l"(da),"l"(db),"r"(sc));
}

constexpr uint32_t XB = 28672;
constexpr uint32_t O_WQ = 5 * XB;
constexpr uint32_t O_WO = O_WQ + 32768;
constexpr uint32_t O_MIMG = O_WO + 32768;
constexpr uint32_t O_BAR = O_MIMG + 2 * 7168;
constexpr uint32_t O_TS = O_BAR + 256;
constexpr uint32_t T_SMEM = O_TS + 4096 + 128 + 1024;
constexpr uint32_t O_Z = 4 * XB;
constexpr uint32_t O_RS = O_Z + 2 * 5120;
constexpr uint32_t O_ORS = O_RS + 2 * 2048;
constexpr uint32_t O_P = O_ORS + 3 * 4096;
constexpr uint32_t O_SX = O_P + 2 * 2560;
constexpr uint32_t O_MJ = O_SX + 1536;
constexpr uint32_t O_ST = O_MJ + 2048;
constexpr uint32_t O_PC = O_ST + 2 * 5632;
enum { B_X = 0, B_M = 4, B_RS = 6, B_O = 8, B_ZX = 10, B_P = 12, B_PF = 14, B_PE = 18, B_WQ = 22, B_WO = 23, B_T = 24, B_MJ = 26, B_OL = 28, B_N = 29 };
constexpr uint32_t O_C3 = O_BAR + 8 * B_N, O_NEAR = O_C3 + 4;
enum { N_ZM = 1, N_YM = 2, N_W1 = 3, N_INIT = 4, N_ZX = 5, N_REDO = 6 };

DEVI void gemm_m(const uint32_t (&w)[28][4], uint32_t img_lane, float (&c)[4]) {
  float acc[4][4];
#pragma unroll
  for (int i = 0; i < 4; i++) { acc[i][0] = acc[i][1] = acc[i][2] = acc[i][3] = 0.f; }
  uint32_t r[14][4];
#pragma unroll
  for (int u = 0; u < 14; u++) ldsm4(r[u], img_lane + u * 512);
#pragma unroll
  for (int u = 0; u < 14; u++) {
    mma16v(acc[(2 * u) & 3], w[2 * u][0], w[2 * u][1], w[2 * u][2], w[2 * u][3], r[u][0], r[u][1]);
    mma16v(acc[(2 * u + 1) & 3], w[2 * u + 1][0], w[2 * u + 1][1], w[2 * u + 1][2], w[2 * u + 1][3], r[u][2], r[u][3]);
  }
#pragma unroll
  for (int i = 0; i < 4; i++) c[i] = (acc[0][i] + acc[1][i]) + (acc[2][i] + acc[3][i]);
}

DEVI void gemm_x(const uint32_t (&w)[28][4], uint32_t xbuf, float (&d)[16]) {
  const uint64_t b0 = desc128(xbuf, 1);
  wg_fence();
#pragma unroll
  for (int k = 0; k < 28; k++) wgmma_n32_rs(d, w[k], b0 + (uint64_t)((k >> 2) * 256 + (k & 3) * 2), k != 0);
  wg_commit();
  wg_wait<0>();
  reg_fence(d);
}

template <int WHICH>
DEVI void build_weights(uint32_t (&w)[28][4], uint32_t sb, int& dead, int lane) {
  const uint32_t bar = sb + O_BAR;
  mbar_wait(bar + 8 * (WHICH ? B_WO : B_WQ), 0, dead);
  if ((threadIdx.x & 127) == 0) PTS(4 + WHICH);
#pragma unroll
  for (int half = 0; half < 2; half++) {
    float d[112];
#pragma unroll 1
    for (int fk = 0; fk < 4; fk++) {
      const int c = 2 * (4 * half + fk) + WHICH, st = c & 3;
      mbar_wait(bar + 8 * (B_PF + st), (c >> 2) & 1, dead);
      if ((threadIdx.x & 127) == 0) PTS(8 + c);
      const uint64_t db = desc128(sb + (st + 1) * XB, 1);
      wg_fence();
#pragma unroll
      for (int kk = 0; kk < 4; kk++) {
        if (WHICH == 0) wgmma_n224_kk(d, desc128(sb + O_WQ + fk * 8192 + kk * 32, 1), db + kk * 2, (fk | kk) != 0);
        else            wgmma_n224_mk(d, desc128(sb + O_WO + (fk * 4 + kk) * 2048, 1), db + kk * 2, (fk | kk) != 0);
      }
      wg_commit();
      wg_wait<0>();
      if (lane == 0) mbar_arrive(bar + 8 * (B_PE + st));
    }
    reg_fence(d);
#pragma unroll
    for (int kk = 0; kk < 14; kk++) {
      w[14 * half + kk][0] = pack2(d[8 * kk + 0], d[8 * kk + 1]);
      w[14 * half + kk][1] = pack2(d[8 * kk + 2], d[8 * kk + 3]);
      w[14 * half + kk][2] = pack2(d[8 * kk + 4], d[8 * kk + 5]);
      w[14 * half + kk][3] = pack2(d[8 * kk + 6], d[8 * kk + 7]);
    }
  }
}

DEVI void load7(uint32_t (&v)[14], const float* p, int stride) {
#pragma unroll
  for (int k = 0; k < 7; k++) ldg2r(v[2 * k], v[2 * k + 1], p + k * stride);
}
DEVI bool stale7(const uint32_t (&v)[14], uint32_t tag) {
  const uint32_t o = ((v[0] | v[1] | v[2]) | (v[3] | v[4] | v[5]) | (v[6] | v[7] | v[8])) | ((v[9] | v[10] | v[11]) | (v[12] | v[13]));
  const uint32_t a = ((v[0] & v[1] & v[2]) & (v[3] & v[4] & v[5]) & (v[6] & v[7] & v[8])) & ((v[9] & v[10] & v[11]) & (v[12] & v[13]));
  return (((o ^ tag) | (a ^ tag)) & 3u) != 0;
}
DEVI float2 add7(const uint32_t (&v)[14]);
DEVI float2 sum7(uint32_t (&v)[14], const float* p, int stride, uint32_t tag, int& lim) {
  if (__builtin_expect(__any_sync(0xffffffffu, stale7(v, tag)), 0)) {
    do { load7(v, p, stride); } while (__any_sync(0xffffffffu, stale7(v, tag)) && --lim > 0);
  }
  return add7(v);
}
DEVI float2 add7(const uint32_t (&v)[14]) {
  float2 r;
  r.x = ((__uint_as_float(v[0]) + __uint_as_float(v[2])) + (__uint_as_float(v[4]) + __uint_as_float(v[6]))) +
        ((__uint_as_float(v[8]) + __uint_as_float(v[10])) + __uint_as_float(v[12]));
  r.y = ((__uint_as_float(v[1]) + __uint_as_float(v[3])) + (__uint_as_float(v[5]) + __uint_as_float(v[7]))) +
        ((__uint_as_float(v[9]) + __uint_as_float(v[11])) + __uint_as_float(v[13]));
  return r;
}

__global__ void __launch_bounds__(384, 1)
rmt_kernel(const __grid_constant__ CUtensorMap tmWq, const __grid_constant__ CUtensorMap tmWk,
           const __grid_constant__ CUtensorMap tmWv, const __grid_constant__ CUtensorMap tmWo,
           const __grid_constant__ CUtensorMap tmX, const __nv_bfloat16* __restrict__ x,
           const __nv_bfloat16* __restrict__ mem0, const __nv_bfloat16* __restrict__ gate_w, __nv_bfloat16* __restrict__ out) {
  extern __shared__ uint8_t smem_raw[];
  const uint32_t sb = (smem_u32(smem_raw) + 1023) & ~1023u;
  const uint32_t bar = sb + O_BAR;
  int lim = SPIN_LIMIT;
  int tid;
  uint32_t h, j;
  asm volatile("mov.u32 %0, %%tid.x;" : "=r"(tid));
  asm volatile("mov.u32 %0, %%cluster_ctarank;" : "=r"(h));
  asm volatile("mov.u32 %0, %%clusterid.x;" : "=r"(j));
  const int lane = tid & 31, warp = __shfl_sync(0xffffffffu, tid >> 5, 0);
  if (warp == 0) PTS(0);

  if (warp == 8) {
    if (elect()) {
#pragma unroll
      for (int i = 0; i < 4; i++) mbar_init(bar + 8 * (B_PF + i), 1);
      mbar_init(bar + 8 * B_WQ, 1);
      mbar_init(bar + 8 * B_WO, 1);
      asm volatile("fence.mbarrier_init.release.cluster;" ::: "memory");
      PTS(1);
      mbar_expect(bar + 8 * B_PF, XB);
      tma2d(sb + XB, &tmWk, h * DH, 0, bar + 8 * B_PF);
      PTS(27);
      mbar_expect(bar + 8 * B_WQ, 32768);
#pragma unroll
      for (int k = 0; k < 4; k++) tma2d(sb + O_WQ + k * 8192, &tmWq, h * DH + k * 64, j * 64, bar + 8 * B_WQ);
      PTS(28);
      mbar_expect(bar + 8 * B_WO, 32768);
      tma2d(sb + O_WO, &tmWo, j * 64, h * DH, bar + 8 * B_WO);
      PTS(29);
#pragma unroll
      for (int c = 1; c < 4; c++) {
        mbar_expect(bar + 8 * (B_PF + c), XB);
        tma2d(sb + (c + 1) * XB, (c & 1) ? &tmWv : &tmWk, h * DH + (c >> 1) * 64, 0, bar + 8 * (B_PF + c));
      }
      PTS(30);
      int c = 4 + j;
      tma2d_prefetch((c & 1) ? &tmWv : &tmWk, h * DH + ((c >> 1) & 3) * 64, (c >> 3) * 224);
      c += 7;
      if (c < 16) tma2d_prefetch((c & 1) ? &tmWv : &tmWk, h * DH + ((c >> 1) & 3) * 64, 224);
    }
  } else if (warp == 9) {
    if (elect()) {
#pragma unroll
      for (int i = 0; i < B_N; i++)
        if (i < B_PF || (i >= B_PE && i < B_WQ) || i >= B_T) mbar_init(bar + 8 * i, i >= B_MJ ? 1 : i >= B_T ? 3 : i >= B_PE ? 4 : i >= B_P ? 2 : i >= B_ZX ? 4 : 1);
      sts32v(sb + O_C3, 0);
      mbar_expect(bar + 8 * B_X, XB);
      mbar_expect(bar + 8 * B_OL, 4096);
#pragma unroll
      for (int i = 0; i < 2; i++) { mbar_expect(bar + 8 * (B_RS + i), 2048); mbar_expect(bar + 8 * (B_O + i), 4096); }
      asm volatile("fence.mbarrier_init.release.cluster;" ::: "memory");
    }
  }
  asm volatile("griddepcontrol.launch_dependents;");
  if (warp == 8) PTS(2);
  __syncthreads();
  cluster_arrive_relaxed();
  if (warp == 0) PTS(3);

  if (warp < 4) {
    asm volatile("setmaxnreg.inc.sync.aligned.u32 208;");
    uint32_t w[28][4];
    build_weights<0>(w, sb, lim, lane);
    if (warp == 0) PTS(6);
    cluster_wait();
    cluster_arrive_relaxed();
    uint32_t zst = sb + O_Z + ((2 * warp + ((lane >> 3) & 1)) * 40 + 8 * (lane >> 4) + (lane & 7)) * 16;
    const int mt = warp & 1, n0 = (warp >> 1) * 3;
    const int ch = lane >> 3, chp = (ch >> 1) | ((ch & 1) << 1);
    uint32_t zld = sb + O_Z + ((warp == 2 ? chp : ch) * 40 + (lane & 7)) * 16 + (warp == 2 ? 0 : n0 * 128);
    const int xrow = 16 * mt + (lane & 15);
    uint32_t xq = sb + j * 4096 + xrow * 128 + (((lane >> 4) ^ (xrow & 7)) << 4);
    uint32_t mimg = sb + O_MIMG + lane * 16, sta = sb + O_ST + mt * 2048 + lane * 16;
    uint8_t* p_smm = xch(h) + (XC_R0 + 2 * XC_REG + j * 256 + lane * 8);
    const uint8_t* p_smr = xch(h) + (XC_R0 + 2 * XC_REG + lane * 8);
    const uint32_t aq1 = warp == 2 ? 512 : 32, d_poll = D_S + ((warp + 2) & 3) * D_SS;
    pin(zst); pin(zld); pin(xq); pin(mimg); pin(sta); pinp(p_smm);
    {
      float d[16];
      mbar_wait(bar + 8 * B_X, 0, lim);
      gemm_x(w, sb, d);
      if (warp == 0) PTS(7);
      cluster_wait();
      if (warp == 0) PTS(24);
      stsm4t(zst + 8 * 16, pack2(d[0], d[1]), pack2(d[2], d[3]), pack2(d[4], d[5]), pack2(d[6], d[7]));
      stsm4t(zst + 24 * 16, pack2(d[8], d[9]), pack2(d[10], d[11]), pack2(d[12], d[13]), pack2(d[14], d[15]));
      __syncwarp();
      if (lane == 0) mbar_arrive(bar + 8 * B_ZX);
      p_smr += lds32v(sb + O_NEAR);
      bar_sync(N_INIT, 320);
    }
#pragma unroll 1
    for (int s = 0; s < NSEG; s++) {
      const bool rec = s < NSEG - 1;
      uint32_t img = mimg + (s & 1) * 7168, zs = zst + (s & 1) * 5120, zl = zld + (s & 1) * 5120;
      uint32_t tag = ((s >> 1) + 1) & 3, aq = warp == 2 ? img + j * 1024 : xq + (s & 3) * XB;
      uint8_t* smm = p_smm + (s & 1) * 1792;
      pin(img); pin(zs); pin(zl); pin(tag); pin(aq); pinp(smm);
      if (s) mbar_wait(bar + 8 * (B_M + (s & 1)), ((s - 1) >> 1) & 1, lim);
      if (warp == 2) TS(0);
      float c[4];
      gemm_m(w, img, c);
      stsm2t(zs, pack2(c[0], c[1]), pack2(c[2], c[3]));
      bar_arrive(N_YM, 288);
      uint32_t a[4][4];
      ldsm4(a[0], aq);
      ldsm4(a[1], aq ^ aq1);
      if (warp != 2) { ldsm4(a[2], aq ^ 64); ldsm4(a[3], aq ^ 96); }
      if (__builtin_expect(bar_or(N_ZM, 160, false), 0)) {
        gemm_m(w, img, c);
        stsm2t(zs, pack2(c[0], c[1]), pack2(c[2], c[3]));
        ldsm4(a[0], aq);
        ldsm4(a[1], aq ^ aq1);
        bar_sync(N_REDO, 128);
      }
      uint32_t b0[4], b1[4];
      ldsm4(b0, zl);
      ldsm4(b1, zl + 4 * 640);
      const uint32_t t0 = clk();
      if (warp == 2) {
        TS(1);
        const float2 e = mma_rows8(a[0], a[1], b0, b1);
        if (rec) { stg2r(smm, tagf(e.x, tag), tagf(e.y, tag)); stg2r(smm + XC_TWIN, tagf(e.x, tag), tagf(e.y, tag)); }
        TS(2);
      } else {
        const uint32_t st = sta + (s & 1) * 5632;
#pragma unroll
        for (int n = 0; n < 3; n++) {
          if (n < 2 || n0 == 0) {
            if (n) { ldsm4(b0, zl + n * 128); ldsm4(b1, zl + n * 128 + 4 * 640); }
            float e[4] = {0.f, 0.f, 0.f, 0.f};
            mma16(e, a[0][0], a[0][1], a[0][2], a[0][3], b0[0], b0[1]);
            mma16(e, a[1][0], a[1][1], a[1][2], a[1][3], b0[2], b0[3]);
            mma16(e, a[2][0], a[2][1], a[2][2], a[2][3], b1[0], b1[1]);
            mma16(e, a[3][0], a[3][1], a[3][2], a[3][3], b1[2], b1[3]);
#pragma unroll
            for (int t = 0; t < 4; t++) {
              const int i = (t >> 1) * (mt ? 10 : 6) + 2 * (n0 + n) + (t & 1), c = (i * 11) >> 5;
              sts32v(st + c * 512 + (i - 3 * c) * 4, __float_as_uint(e[t]));
            }
          }
        }
        asm volatile("fence.proxy.async.shared::cta;" ::: "memory");
        __syncwarp();
        if (lane == 0) mbar_arrive(bar + 8 * (B_T + (s & 1)));
      }
      if (rec) {
        const float* pm = reinterpret_cast<const float*>(p_smr + (s & 1) * 1792);
        const uint32_t res = mimg + (O_SX + 1024 - O_MIMG) - lane * 8 + (s & 1) * 256;
        delay_until(t0, d_poll);
        while (__any_sync(0xffffffffu, (lds32v(res) & 3) != tag) && --lim > 0) {
          uint32_t vm[14];
          load7(vm, pm, 64);
          if (!__any_sync(0xffffffffu, stale7(vm, tag))) {
            const float2 sm = add7(vm);
            sts_u2(res, tagf(sm.x, tag), tagf(sm.y, tag));
            break;
          }
        }
        if (warp == 2) TS(6);
      }
      if (rec) {
        float d[16];
        mbar_wait(bar + 8 * (B_X + ((s + 1) & 3)), ((s + 1) >> 2) & 1, lim);
        bar_sync(N_ZX, 256);
        gemm_x(w, sb + ((s + 1) & 3) * XB, d);
        const uint32_t zn = zst + ((s + 1) & 1) * 5120;
        stsm4t(zn + 8 * 16, pack2(d[0], d[1]), pack2(d[2], d[3]), pack2(d[4], d[5]), pack2(d[6], d[7]));
        stsm4t(zn + 24 * 16, pack2(d[8], d[9]), pack2(d[10], d[11]), pack2(d[12], d[13]), pack2(d[14], d[15]));
        __syncwarp();
        if (lane == 0) mbar_arrive(bar + 8 * (B_ZX + ((s + 1) & 1)));
        if (warp == 2) TS(3);
      }
    }
    if (lim <= 0) g_err = 1;
    __syncwarp();
    if (warp == 0) PTS(25);
    cluster_arrive();
    cluster_wait();
  } else if (warp < 8) {
    asm volatile("setmaxnreg.inc.sync.aligned.u32 224;");
    const int wq = warp - 4;
    uint32_t w[28][4];
    build_weights<1>(w, sb, lim, lane);
    cluster_wait();
    cluster_arrive_relaxed();
    uint32_t yx[8], yp[8], ym[2], ymp[2];
    {
      float d[16];
      mbar_wait(bar + 8 * B_X, 0, lim);
      gemm_x(w, sb, d);
#pragma unroll
      for (int i = 0; i < 8; i++) { yx[i] = pack2(d[2 * i], d[2 * i + 1]); yp[i] = 0; }
      ymp[0] = ymp[1] = 0;
      cluster_wait();
    }
    bar_sync(N_INIT, 320);
    const int ri = lane >> 2, q = lane & 3;
    uint32_t zld = sb + O_Z + (((lane >> 4) | ((lane >> 2) & 2)) * 40 + 8 + 8 * wq + (lane & 7)) * 16;
    uint32_t rs_a = mapa(sb + O_RS + h * 128 + ((ri & 1) * 4 + q) * 16, 4 * wq + (ri >> 1));
    uint32_t rs_b = mapa(bar + 8 * B_RS, 4 * wq + (ri >> 1));
    uint32_t o_a = mapa(sb + O_ORS + h * 256 + wq * 64 + q * 16, ri);
    uint32_t o_b = mapa(bar + 8 * B_O, ri);
    const uint32_t o_st = mapa(sb, 8) - mapa(sb, 0);
    uint32_t mimg = sb + O_MIMG + lane * 16, l8 = sb + lane * 8;
    uint8_t* p_smx = xch(h) + (XC_R0 + j * 1024 + wq * 256 + lane * 8);
    const uint8_t* p_smr = xch(h) + (XC_R0 + wq * 256 + lane * 8 + lds32v(sb + O_NEAR));
    pin(zld); pin(rs_a); pin(rs_b); pin(o_a); pin(o_b); pin(mimg); pin(l8); pinp(p_smx); pinp(p_smr);

    uint32_t oh[8];
    auto token_pv = [&](int sp) {
      const uint32_t p16 = mimg + (O_P - O_MIMG) + (sp & 1) * 2560, p8 = l8 + O_P + 1024 + (sp & 1) * 2560;
      mbar_wait(bar + 8 * (B_P + (sp & 1)), (sp >> 1) & 1, lim);
      const uint2 m0 = lds_u2(p8), m1 = lds_u2(p8 + 1280);
      const uint4 p0 = lds_u4(p16), p1 = lds_u4(p16 + 512), p2 = lds_u4(p16 + 1280), p3 = lds_u4(p16 + 1280 + 512);
      float o0[4] = {0.f, 0.f, 0.f, 0.f}, o1[4] = {0.f, 0.f, 0.f, 0.f}, o2[4] = {0.f, 0.f, 0.f, 0.f}, o3[4] = {0.f, 0.f, 0.f, 0.f};
      mma8(o0, m0.x, m0.y, ymp[0]);
      mma8(o1, m0.x, m0.y, ymp[1]);
      mma8(o2, m1.x, m1.y, ymp[0]);
      mma8(o3, m1.x, m1.y, ymp[1]);
      mma16(o0, p0.x, p0.y, p0.z, p0.w, yp[0], yp[4]);
      mma16(o1, p0.x, p0.y, p0.z, p0.w, yp[1], yp[5]);
      mma16(o2, p2.x, p2.y, p2.z, p2.w, yp[0], yp[4]);
      mma16(o3, p2.x, p2.y, p2.z, p2.w, yp[1], yp[5]);
      mma16(o0, p1.x, p1.y, p1.z, p1.w, yp[2], yp[6]);
      mma16(o1, p1.x, p1.y, p1.z, p1.w, yp[3], yp[7]);
      mma16(o2, p3.x, p3.y, p3.z, p3.w, yp[2], yp[6]);
      mma16(o3, p3.x, p3.y, p3.z, p3.w, yp[3], yp[7]);
      oh[0] = pack2(o0[0], o0[1]); oh[1] = pack2(o1[0], o1[1]); oh[2] = pack2(o0[2], o0[3]); oh[3] = pack2(o1[2], o1[3]);
      oh[4] = pack2(o2[0], o2[1]); oh[5] = pack2(o3[0], o3[1]); oh[6] = pack2(o2[2], o2[3]); oh[7] = pack2(o3[2], o3[3]);
    };
    auto token_send = [&](int sp) {
      const bool last = sp == NSEG - 1;
      const uint32_t oa = o_a + (last ? 2 : sp & 1) * 4096, ob = o_b + (last ? B_OL - B_O : sp & 1) * 8;
      st_async4u(oa, oh[0], oh[1], oh[2], oh[3], ob);
      st_async4u(oa + o_st, oh[4], oh[5], oh[6], oh[7], ob + o_st);
    };
    uint32_t zb0[4], zb1[4];
    mbar_wait(bar + 8 * B_ZX, 0, lim);
    ldsm4(zb0, zld);
    ldsm4(zb1, zld + 4 * 640);

#pragma unroll 1
    for (int s = 0; s < NSEG; s++) {
      const bool rec = s < NSEG - 1;
      uint32_t img = mimg + (s & 1) * 7168, tag = ((s >> 1) + 1) & 3;
      uint32_t ra = rs_a + (s & 1) * 2048, rb = rs_b + (s & 1) * 8;
      uint8_t* smx = p_smx + (s & 1) * XC_REG;
      const float* px = reinterpret_cast<const float*>(p_smr + (s & 1) * XC_REG);
      pin(img); pin(tag); pin(ra); pin(rb); pinp(smx); pinp(px);
      uint32_t vx[14], t0 = 0;
      if (rec) {
        uint32_t a0[4], a1[4];
        const uint32_t mj = s ? mimg + (O_MJ - O_MIMG) + (s & 1) * 1024 : img + j * 1024;
        if (s) mbar_wait(bar + 8 * (B_MJ + (s & 1)), ((s - 1) >> 1) & 1, lim);
        ldsm4(a0, mj);
        ldsm4(a1, mj + 512);
        const float2 e = mma_rows8(a0, a1, zb0, zb1);
        const uint32_t r0 = tagf(e.x, tag), r1 = tagf(e.y, tag);
        stg2r(smx, r0, r1);
        stg2r(smx + XC_TWIN, r0, r1);
        t0 = clk();
        if (wq == 0) TS(15);
      }
      if (s) token_pv(s - 1);
      if (wq == 0) TS(5);
      if (rec) {
        delay_until(t0, D_X);
        load7(vx, px, 256);
      }
      if (s) {
        mbar_wait(bar + 8 * (B_M + (s & 1)), ((s - 1) >> 1) & 1, lim);
        token_send(s - 1);
      }
      bar_sync(N_YM, 288);
      {
        float c[4];
        gemm_m(w, img, c);
        ym[0] = pack2(c[0], c[1]);
        ym[1] = pack2(c[2], c[3]);
      }
      if (wq == 0) TS(4);
      if (rec) {
        const float2 sx = sum7(vx, px, 256, tag, lim);
        sts_f2(l8 + O_SX + wq * 256, sx.x, sx.y);
        bar_sync(N_W1, 128);
        float2 v[4];
#pragma unroll
        for (int n = 0; n < 4; n++) v[n] = lds_f2(l8 + O_SX + n * 256);
        const float mxx = qmax(fmaxf(fmaxf(fmaxf(v[0].x, v[0].y), fmaxf(v[1].x, v[1].y)), fmaxf(fmaxf(v[2].x, v[2].y), fmaxf(v[3].x, v[3].y))));
        const float nb = -mxx * SC2;
        float lx = 0.f;
        uint32_t pa[4];
#pragma unroll
        for (int n = 0; n < 4; n++) {
          const float p0 = ex2(fmaf(v[n].x, SC2, nb)), p1 = ex2(fmaf(v[n].y, SC2, nb));
          lx += p0 + p1;
          pa[n] = pack2(p0, p1);
        }
        float o0[4] = {0.f, 0.f, 0.f, 0.f}, o1[4] = {0.f, 0.f, 0.f, 0.f}, u0[4] = {0.f, 0.f, 0.f, 0.f}, u1[4] = {0.f, 0.f, 0.f, 0.f};
        mma16v(o0, pa[0], pa[1], pa[2], pa[3], yx[0], yx[4]);
        mma16v(u0, pa[0], pa[1], pa[2], pa[3], yx[2], yx[6]);
        mma16v(o1, pa[0], pa[1], pa[2], pa[3], yx[1], yx[5]);
        mma16v(u1, pa[0], pa[1], pa[2], pa[3], yx[3], yx[7]);
        o0[0] += u0[2]; o0[1] += u0[3]; o1[0] += u1[2]; o1[1] += u1[3];
        if (wq == 0) TS(7);
        float2 sm;
        do { sm = lds_f2v(l8 + O_SX + 1024 + (s & 1) * 256); } while (__any_sync(0xffffffffu, (__float_as_uint(sm.x) & 3) != tag) && --lim > 0);
        if (wq == 0) TS(8);
        const float mx = fmaxf(mxx, qmax(fmaxf(sm.x, sm.y)));
        const float nm = -mx * SC2;
        const float al = ex2(fmaf(mxx, SC2, nm)), p0 = ex2(fmaf(sm.x, SC2, nm)), p1 = ex2(fmaf(sm.y, SC2, nm));
        const uint32_t pp = pack2(p0, p1);
        o0[0] *= al; o0[1] *= al; o1[0] *= al; o1[1] *= al;
        mma8v(o0, pp, pp, ym[0]);
        mma8v(o1, pp, pp, ym[1]);
        const float inv = rcp(qsum(fmaf(al, lx, p0 + p1)));
        st_async4(ra, o0[0] * inv, o0[1] * inv, o1[0] * inv, o1[1] * inv, rb);
        bar_arrive(N_ZX, 256);
        if (wq == 0) TS(9);
      }
#pragma unroll
      for (int i = 0; i < 8; i++) yp[i] = yx[i];
      ymp[0] = ym[0]; ymp[1] = ym[1];
      if (rec) {
        float d[16];
        mbar_wait(bar + 8 * (B_X + ((s + 1) & 3)), ((s + 1) >> 2) & 1, lim);
        gemm_x(w, sb + ((s + 1) & 3) * XB, d);
#pragma unroll
        for (int i = 0; i < 8; i++) yx[i] = pack2(d[2 * i], d[2 * i + 1]);
        mbar_wait(bar + 8 * (B_ZX + ((s + 1) & 1)), ((s + 1) >> 1) & 1, lim);
        ldsm4(zb0, zld + ((s + 1) & 1) * 5120);
        ldsm4(zb1, zld + ((s + 1) & 1) * 5120 + 4 * 640);
        if (wq == 0) TS(10);
      }
    }
    token_pv(NSEG - 1);
    token_send(NSEG - 1);
    if (lim <= 0) g_err = 1;
    __syncwarp();
    cluster_arrive();
    cluster_wait();
  } else {
    asm volatile("setmaxnreg.dec.sync.aligned.u32 72;");
    if (warp == 8) {
      const int u = lane >> 2, comp = lane & 3;
      uint8_t* gm0 = xch(16) + (XC_R0 + (8 * j + 2 * (h >> 2) + (comp >> 1)) * 128 + (2 * (h & 3) + (u >> 2)) * 16 + ((u & 3) * 2 + (comp & 1)) * 2);
#pragma unroll
      for (int k = 0; k < 6; k++) stg16r(gm0 + k * XC_TWIN, 0xffff);
      cluster_wait();
      if (lane == 0) {
        if (h < 7) tma2d_mc(sb + h * 4096, &tmX, h * 64, 0, bar + 8 * B_X);
#pragma unroll 1
        for (int c = 4; c < 16; c++) {
          const int st = c & 3;
          mbar_wait1(bar + 8 * (B_PE + st), ((c >> 2) - 1) & 1, lim);
          mbar_expect(bar + 8 * (B_PF + st), XB);
          tma2d(sb + (st + 1) * XB, (c & 1) ? &tmWv : &tmWk, h * DH + ((c >> 1) & 3) * 64, (c >> 3) * 224, bar + 8 * (B_PF + st));
        }
      }
      __syncwarp();
      cluster_arrive();
      cluster_wait();
      if (lane == 0) {
        for (int k = 1; k < 3; k++) {
          mbar_expect(bar + 8 * (B_X + k), XB);
          if (h < 7) tma2d_mc(sb + k * XB + h * 4096, &tmX, h * 64, k * 32, bar + 8 * (B_X + k));
        }
      }
      uint32_t chk = sb + O_MIMG + lane * 32 + (lane >> 2) * 4, rs0 = sb + O_RS + lane * 4;
      const uint8_t* gnear = xch(16) + (XC_R0 + lds32v(sb + O_NEAR + 4));
      const uint32_t pc_st = sb + O_PC + ((comp >> 1) * 2 + (u >> 2)) * 16 + ((u & 3) * 2 + (comp & 1)) * 2;
      const uint32_t mj_a = mapa(sb + O_MJ + (2 * (h >> 2) + ((lane >> 1) & 1)) * 128 + (2 * (h & 3) + (lane & 1)) * 16, lane >> 2);
      const uint32_t mj_b = mapa(bar + 8 * B_MJ, lane >> 2), mj_st = mapa(sb, 8) - mapa(sb, 0);
      pin(chk); pin(rs0); pinp(gm0);
      int s3 = 0;
#pragma unroll 1
      for (int s = 0; s < NSEG; s++) {
        uint32_t ck = chk + (s & 1) * 7168;
        pin(ck);
        bool redo = false;
        if (s) {
          mbar_wait(bar + 8 * (B_M + (s & 1)), ((s - 1) >> 1) & 1, lim);
          uint32_t v[7];
#pragma unroll
          for (int k = 0; k < 7; k++) v[k] = lds32v(ck + k * 1024);
          const uint32_t mx = __vimax3_u32(__vimax3_u32(v[0], v[1], v[2]), __vimax3_u32(v[3], v[4], v[5]), v[6]);
          if (__builtin_expect(__any_sync(0xffffffffu, mx == 0xffffffffu), 0)) {
            redo = true;
            uint32_t late = 0;
#pragma unroll
            for (int k = 0; k < 7; k++) late |= __any_sync(0xffffffffu, v[k] == 0xffffffffu) ? 1u << k : 0u;
            const uint8_t* p = gnear + s3 * XC_REG + lane * 16;
            while (late && --lim > 0) {
              const int k0 = __ffs(late) - 1, k1 = 31 - __clz(late);
              uint32_t t[4][4];
#pragma unroll
              for (int i = 0; i < 4; i++)
                asm volatile("ld.relaxed.gpu.global.v4.u32 {%0,%1,%2,%3}, [%4];" : "=r"(t[i][0]), "=r"(t[i][1]), "=r"(t[i][2]), "=r"(t[i][3])
                             : "l"(p + (i & 2 ? k1 : k0) * 1024 + (i & 1) * 512) : "memory");
#pragma unroll
              for (int i = 0; i < 2; i++) {
                const int kk = i ? k1 : k0;
                const uint32_t m2 = __vimax3_u32(__vimax3_u32(t[2 * i][0], t[2 * i][1], t[2 * i][2]), __vimax3_u32(t[2 * i][3], t[2 * i + 1][0], t[2 * i + 1][1]),
                                                 max(t[2 * i + 1][2], t[2 * i + 1][3]));
                if (!__any_sync(0xffffffffu, m2 == 0xffffffffu)) {
                  const uint32_t d = sb + O_MIMG + (s & 1) * 7168 + kk * 1024 + lane * 16;
                  sts_u4(d, t[2 * i][0], t[2 * i][1], t[2 * i][2], t[2 * i][3]);
                  sts_u4(d + 512, t[2 * i + 1][0], t[2 * i + 1][1], t[2 * i + 1][2], t[2 * i + 1][3]);
                  late &= ~(1u << kk);
                }
              }
            }
          }
        }
        bar_arrive(N_YM, 288);
        bar_or(N_ZM, 160, redo);
        if (s == NSEG - 1) break;
        const uint32_t mbar = bar + 8 * (B_M + ((s + 1) & 1));
        if (elect()) {
          mbar_expect(mbar, 7168);
          if (s < NSEG - 2) mbar_expect(bar + 8 * (B_MJ + ((s + 1) & 1)), 1024);
          if (s >= 1 && s + 2 < NSEG) {
            mbar_expect(bar + 8 * (B_X + ((s + 2) & 3)), XB);
            if (h < 7) tma2d_mc(sb + ((s + 2) & 3) * XB + h * 4096, &tmX, h * 64, (s + 2) * 32, bar + 8 * (B_X + ((s + 2) & 3)));
          }
        }
        const int s3n = s3 == 2 ? 0 : s3 + 1, s3p = s3 == 0 ? 2 : s3 - 1;
        stg16r(gm0 + s3p * XC_REG, 0xffff);
        stg16r(gm0 + s3p * XC_REG + XC_TWIN, 0xffff);
        while ((int)lds32v(sb + O_C3) < s - 1 && --lim > 0) {}
        uint32_t rb = rs0 + (s & 1) * 2048;
        uint8_t* gm = gm0 + s3n * XC_REG;
        uint32_t mdst = sb + O_MIMG + ((s + 1) & 1) * 7168 + h * 448, mb = mbar;
        const uint8_t* msrc = gnear + s3n * XC_REG + h * 448;
        s3 = s3n;
        pin(rb); pinp(gm); pin(mdst); pin(mb); pinp(msrc);
        mbar_wait(bar + 8 * (B_RS + (s & 1)), (s >> 1) & 1, lim);
        TS(11);
        float v[16];
#pragma unroll
        for (int k = 0; k < 16; k++) v[k] = lds_f(rb + k * 128);
        const float sum = (((v[0] + v[1]) + (v[2] + v[3])) + ((v[4] + v[5]) + (v[6] + v[7]))) +
                          (((v[8] + v[9]) + (v[10] + v[11])) + ((v[12] + v[13]) + (v[14] + v[15])));
        stg16r(gm, (uint16_t)(pack2(sum, 0.f) & 0xffff));
        stg16r(gm + XC_TWIN, (uint16_t)(pack2(sum, 0.f) & 0xffff));
        const uint32_t t0 = clk();
        TS(12);
        asm volatile("st.shared.u16 [%0], %1;" :: "r"(pc_st), "h"((uint16_t)(pack2(sum, 0.f) & 0xffff)) : "memory");
        __syncwarp();
        const float4 pc = lds_f4(sb + O_PC + (lane & 3) * 16);
        if (s < NSEG - 2) {
          const uint32_t o = ((s + 1) & 1) * 1024, ob = ((s + 1) & 1) * 8;
          st_async4(mj_a + o, pc.x, pc.y, pc.z, pc.w, mj_b + ob);
          st_async4(mj_a + o + mj_st, pc.x, pc.y, pc.z, pc.w, mj_b + ob + mj_st);
        }
        const bool el = elect();
        if (el) mbar_expect(bar + 8 * (B_RS + (s & 1)), 2048);
        delay_until(t0, D_M);
        if (el) bulk_mc(mdst, msrc, 448, mb);
      }
    } else if (warp < 11) {
      const int mt = warp - 9, q = lane & 3;
      for (int t = mt * 32 + lane; t < 448; t += 64) {
        const uint4 v = *reinterpret_cast<const uint4*>(mem0 + (t & 7) * DM + (t >> 3) * 8);
        sts_u4(sb + O_MIMG + t * 16, v.x, v.y, v.z, v.w);
      }
      cluster_wait();
      cluster_arrive();
      cluster_wait();
      if (mt == 1) { sts_u2(sb + O_SX + 1024 + lane * 8, 0, 0); sts_u2(sb + O_SX + 1280 + lane * 8, 0, 0); }
      bar_arrive(N_INIT, 320);
      if (mt == 0) {
        for (int c = 0; c < 22; c++) sts32v(sb + O_ST + c * 512 + lane * 16 + 12, 0x3f800000u);
        sts32v(sb + O_ST + 10 * 512 + lane * 16 + 8, 0);
        sts32v(sb + O_ST + 21 * 512 + lane * 16 + 8, 0);
        asm volatile("fence.proxy.async.shared::cta;" ::: "memory");
        __syncwarp();
      }
#pragma unroll 1
      for (int s = 0; s < NSEG; s++) {
        mbar_wait(bar + 8 * (B_T + (s & 1)), (s >> 1) & 1, lim);
        const uint32_t t0 = clk();
        if (mt == 0 && elect()) {
          asm volatile("cp.reduce.async.bulk.global.shared::cta.bulk_group.add.f32 [%0], [%1], 5632;" :: "l"(&g_sacc[s & 7][h][0]), "r"(sb + O_ST + (s & 1) * 5632) : "memory");
          asm volatile("cp.async.bulk.commit_group;" ::: "memory");
          asm volatile("cp.async.bulk.wait_group.read 0;" ::: "memory");
        }
        __syncwarp();
        delay_until(t0, D_T);
        const float4* sp = reinterpret_cast<const float4*>(&g_sacc[s & 7][h][mt * 512 + lane * 4]);
        float u[7][4];
        bool stale;
        do {
          stale = false;
#pragma unroll
          for (int c = 0; c < 7; c++) {
            u[c][0] = u[c][1] = u[c][2] = 0.f; u[c][3] = 7.f;
            if (c < 4 || mt)
              asm volatile("ld.relaxed.gpu.global.v4.f32 {%0,%1,%2,%3}, [%4];" : "=f"(u[c][0]), "=f"(u[c][1]), "=f"(u[c][2]), "=f"(u[c][3]) : "l"(sp + c * 32) : "memory");
          }
#pragma unroll
          for (int c = 0; c < 7; c++) stale |= u[c][3] != 7.f;
        } while (__any_sync(0xffffffffu, stale) && --lim > 0);
        uint32_t pk[2][5];
        float v[2][10];
#pragma unroll
        for (int e = 0; e < 10; e++) {
          v[0][e] = u[e / 3][e % 3];
          v[1][e] = mt ? u[(10 + e) / 3][(10 + e) % 3] : e < 6 ? u[(6 + e) / 3][(6 + e) % 3] : 0.f;
        }
#pragma unroll
        for (int rg = 0; rg < 2; rg++) {
          const int row = 16 * mt + 8 * rg + (lane >> 2);
#pragma unroll
          for (int e = 2; e < 10; e++)
            if (8 * ((e >> 1) - 1) + 2 * q + (e & 1) > row) v[rg][e] = MASKV;
          float mx = v[rg][0];
#pragma unroll
          for (int e = 1; e < 10; e++) mx = fmaxf(mx, v[rg][e]);
          mx = qmax(mx);
          const float nb = -mx * SC2;
          float l = 0.f;
#pragma unroll
          for (int e = 0; e < 10; e++) { v[rg][e] = ex2(fmaf(v[rg][e], SC2, nb)); l += v[rg][e]; }
          const float inv = rcp(qsum(l));
#pragma unroll
          for (int n = 0; n < 5; n++) pk[rg][n] = pack2(v[rg][2 * n] * inv, v[rg][2 * n + 1] * inv);
        }
        const uint32_t pb = sb + O_P + (s & 1) * 2560 + mt * 1280;
        sts_u4(pb + lane * 16, pk[0][1], pk[1][1], pk[0][3], pk[1][3]);
        sts_u4(pb + 512 + lane * 16, pk[0][2], pk[1][2], pk[0][4], pk[1][4]);
        sts_u2(pb + 1024 + lane * 8, pk[0][0], pk[1][0]);
        __syncwarp();
        if (lane == 0) mbar_arrive(bar + 8 * (B_P + (s & 1)));
        if (mt == 1) TS(13);
        if (j + 7 * mt < 11) asm volatile("st.relaxed.gpu.global.v4.f32 [%0], {%1,%1,%1,%1};" :: "l"(&g_sacc[(s + 4) & 7][h][(j + 7 * mt) * 128 + lane * 4]), "f"(0.f) : "memory");
      }
    } else {
      const int t1 = lane >> 4, l16 = lane & 15;
      uint2 gw[7];
#pragma unroll
      for (int k = 0; k < 7; k++) gw[k] = *reinterpret_cast<const uint2*>(gate_w + (k * 16 + l16) * 4);
      const int col = j * 64 + ((lane >> 2) & 3) * 16 + (lane & 3) * 2;
      const uint32_t mark_t = 2 * (ldg1r(&g_ticket[0]) / 112) + 1, mark_f = mark_t + 1;
      if (lane == 0) {
        sts32v(sb + O_NEAR, near_copy(xch(h)));
        sts32v(sb + O_NEAR + 4, near_copy(xch(16) + 2 * XC_REG - (blockIdx.x % 7) * 128));
      }
      __syncwarp();
      cluster_wait();
      cluster_arrive();
      cluster_wait();
#pragma unroll 1
      for (int s = 0; s < NSEG; s++) {
        const int tok = s * 32 + 16 * (h >> 3) + (h & 7) + 8 * t1;
        uint32_t* mk = &g_mark[s][j * 16 + h];
        bool have_b = ldg1r(mk) == mark_f;
        float z = 0.f;
#pragma unroll
        for (int k = 0; k < 7; k++) {
          const uint2 xv = *reinterpret_cast<const uint2*>(x + tok * DM + (k * 16 + l16) * 4);
          z = fmaf(bf_lo(xv.x), bf_lo(gw[k].x), z); z = fmaf(bf_hi(xv.x), bf_hi(gw[k].x), z);
          z = fmaf(bf_lo(xv.y), bf_lo(gw[k].y), z); z = fmaf(bf_hi(xv.y), bf_hi(gw[k].y), z);
        }
        const float* bp = &g_b[tok * DM + col];
        uint32_t b0 = 0, b1 = 0, b2 = 0, b3 = 0;
        if (have_b) { ldg2r(b0, b1, bp); ldg2r(b2, b3, bp + 8); }
#pragma unroll
        for (int o = 1; o < 16; o <<= 1) z += __shfl_xor_sync(0xffffffffu, z, o);
        const float g = 1.f / (1.f + __expf(-z));
        const bool last = s == NSEG - 1;
        mbar_wait(bar + 8 * (last ? B_OL : B_O + (s & 1)), last ? 0 : (s >> 1) & 1, lim);
        const uint32_t ob = sb + O_ORS + (last ? 2 : s & 1) * 4096 + t1 * 2048 + l16 * 16;
        float e[8] = {0.f, 0.f, 0.f, 0.f, 0.f, 0.f, 0.f, 0.f};
#pragma unroll
        for (int k = 0; k < 8; k++) {
          const uint4 c = lds_u4(ob + k * 256);
          e[0] += bf_lo(c.x); e[1] += bf_hi(c.x); e[2] += bf_lo(c.y); e[3] += bf_hi(c.y);
          e[4] += bf_lo(c.z); e[5] += bf_hi(c.z); e[6] += bf_lo(c.w); e[7] += bf_hi(c.w);
        }
        float4 a;
        a.x = g * ((t1 ? e[4] : e[0]) + __shfl_xor_sync(0xffffffffu, t1 ? e[0] : e[4], 16));
        a.y = g * ((t1 ? e[5] : e[1]) + __shfl_xor_sync(0xffffffffu, t1 ? e[1] : e[5], 16));
        a.z = g * ((t1 ? e[6] : e[2]) + __shfl_xor_sync(0xffffffffu, t1 ? e[2] : e[6], 16));
        a.w = g * ((t1 ? e[7] : e[3]) + __shfl_xor_sync(0xffffffffu, t1 ? e[3] : e[7], 16));
        __syncwarp();
        if (lane == 0 && s < NSEG - 3) mbar_expect(bar + 8 * (B_O + (s & 1)), 4096);
        if (lane == 0) sts32v(sb + O_C3, s + 1);
        const bool dbg_stash = false;
        if (!have_b || dbg_stash) {
          float* sp = &g_stash[tok * DM + col];
          *reinterpret_cast<float2*>(sp) = make_float2(a.x, a.y);
          *reinterpret_cast<float2*>(sp + 8) = make_float2(a.z, a.w);
        }
        if (!have_b) {
          __syncwarp();
          uint32_t old = 0;
          if (lane == 0) old = exch_release(mk, mark_t);
          have_b = __shfl_sync(0xffffffffu, old, 0) == mark_f;
          if (have_b) { ldg2r(b0, b1, bp); ldg2r(b2, b3, bp + 8); }
        }
        if (have_b) {
          uint32_t* op = reinterpret_cast<uint32_t*>(out + tok * DM + col);
          op[0] = pack2(a.x + __uint_as_float(b0), a.y + __uint_as_float(b1));
          op[4] = pack2(a.z + __uint_as_float(b2), a.w + __uint_as_float(b3));
        }
        TS(14);
      }
      if (lane == 0) atomicAdd(&g_ticket[0], 1);
    }
    if (lim <= 0) g_err = 1;
    __syncwarp();
    cluster_arrive();
    cluster_wait();
  }
}

constexpr uint32_t F_STAGE = 49152, F_BAR = 4 * F_STAGE, F_G = F_BAR + 128, F_M = F_G + 512, F_SMEM = F_M + 1024 + 1024;

template <int N>
DEVI void ffn_tile(float (&d)[N / 2], uint32_t sb, int wg, int nk, int& it, int& dead, int lane) {
#pragma unroll 1
  for (int k = 0; k < nk; k++, it++) {
    const int st = it & 3;
    mbar_wait(sb + F_BAR + 8 * st, (it >> 2) & 1, dead);
    const uint64_t da = desc128(sb + st * F_STAGE + wg * 8192, 1), db = desc128(sb + st * F_STAGE + 16384, 512);
    wg_fence();
#pragma unroll
    for (int kk = 0; kk < 4; kk++) {
      if constexpr (N == 256) wgmma_n256_kn(d, da + kk * 2, db + kk * 128, (k | kk) != 0);
      else                    wgmma_n192_kn(d, da + kk * 2, db + kk * 128, (k | kk) != 0);
    }
    wg_commit();
    if (k) { wg_wait<1>(); if (lane == 0) mbar_arrive(sb + F_BAR + 32 + 8 * ((it - 1) & 3)); }
  }
  wg_wait<0>();
  if (lane == 0) mbar_arrive(sb + F_BAR + 32 + 8 * ((it - 1) & 3));
  reg_fence(d);
}

template <int NJ>
DEVI void ffn_finish(float (&d)[NJ * 32], float g0, float g1, uint32_t sb, int r0, int row, int j0, uint32_t mark_t,
                     __nv_bfloat16* __restrict__ out, int tid) {
  const int wg = tid >> 7, t = tid & 127, off = (r0 + row) * DM + j0 * 64 + 2 * (tid & 3);
#pragma unroll
  for (int n = 0; n < NJ * 8; n++) {
    d[4 * n] *= g0; d[4 * n + 1] *= g0; d[4 * n + 2] *= g1; d[4 * n + 3] *= g1;
    *reinterpret_cast<float2*>(g_b + off + n * 8) = make_float2(d[4 * n], d[4 * n + 1]);
    *reinterpret_cast<float2*>(g_b + off + 8 * DM + n * 8) = make_float2(d[4 * n + 2], d[4 * n + 3]);
  }
  asm volatile("fence.release.gpu;" ::: "memory");
  bar_sync(2 + wg, 128);
  const uint32_t fl = sb + F_M + wg * 512;
  if (t < NJ * 32) {
    const int pair = (r0 >> 1) + wg * 32 + (t & 31);
    sts32v(fl + t * 4, exch_release(&g_mark[pair >> 4][(j0 + (t >> 5)) * 16 + (pair & 15)], mark_t + 1) == mark_t);
  }
  bar_sync(2 + wg, 128);
#pragma unroll
  for (int jj = 0; jj < NJ; jj++)
    if (lds32v(fl + (jj * 32 + ((row & 48) >> 1) + (row & 7)) * 4)) {
#pragma unroll
      for (int half = 0; half < 2; half++)
#pragma unroll
        for (int n = jj * 8; n < jj * 8 + 8; n++) {
          uint32_t a0, a1;
          ldg2r(a0, a1, g_stash + off + half * 8 * DM + n * 8);
          *reinterpret_cast<uint32_t*>(out + off + half * 8 * DM + n * 8) =
              pack2(__uint_as_float(a0) + d[4 * n + 2 * half], __uint_as_float(a1) + d[4 * n + 2 * half + 1]);
        }
    }
}

__global__ void __launch_bounds__(384, 1)
ffn_kernel(const __grid_constant__ CUtensorMap tmX, const __grid_constant__ CUtensorMap tmW1,
           const __grid_constant__ CUtensorMap tmH, const __grid_constant__ CUtensorMap tmW2,
           const __nv_bfloat16* __restrict__ x, const __nv_bfloat16* __restrict__ gate_w, __nv_bfloat16* __restrict__ out) {
  extern __shared__ uint8_t smem_raw[];
  const uint32_t sb = (smem_u32(smem_raw) + 1023) & ~1023u;
  const uint32_t hbar = sb + F_BAR + 64;
  int dead = SPIN_LIMIT;
  const int tid = threadIdx.x, lane = tid & 31, warp = __shfl_sync(0xffffffffu, tid >> 5, 0), r0 = blockIdx.x * 128;
  if (tid == 0) {
    for (int i = 0; i < 4; i++) { mbar_init(sb + F_BAR + 8 * i, 1); mbar_init(sb + F_BAR + 32 + 8 * i, 8); }
    mbar_init(hbar, 256);
    asm volatile("fence.mbarrier_init.release.cluster;" ::: "memory");
    asm volatile("fence.proxy.async.shared::cta;" ::: "memory");
  }
  __syncthreads();
  if (warp >= 8) {
    asm volatile("setmaxnreg.dec.sync.aligned.u32 56;");
    if (tid == 256) {
      int it = 0;
#pragma unroll 1
      for (int t = 0; t < 9; t++) {
        const int nk = t < 7 ? 7 : 28, nb = t < 8 ? 4 : 3;
        if (t == 7) mbar_wait1(hbar, 0, dead);
#pragma unroll 1
        for (int k = 0; k < nk; k++, it++) {
          const int st = it & 3;
          const uint32_t fb = sb + F_BAR + 8 * st, a = sb + st * F_STAGE;
          if (it >= 4) mbar_wait1(fb + 32, ((it >> 2) - 1) & 1, dead);
          mbar_expect(fb, 16384 + nb * 8192);
          tma2d(a, t < 7 ? &tmX : &tmH, k * 64, r0, fb);
          for (int b = 0; b < nb; b++) tma2d(a + 16384 + b * 8192, t < 7 ? &tmW1 : &tmW2, (t < 7 ? t : t - 7) * 256 + b * 64, k * 64, fb);
        }
      }
    } else if (warp > 8) {
      const int l16 = lane & 15;
      for (int r = (warp - 9) * 2 + (lane >> 4); r < 132; r += 6) {
        const int rr = r < 128 ? r : 127;
        float z = 0.f;
#pragma unroll
        for (int k = 0; k < 7; k++) {
          const uint2 xv = *reinterpret_cast<const uint2*>(x + (r0 + rr) * DM + (k * 16 + l16) * 4);
          const uint2 gv = *reinterpret_cast<const uint2*>(gate_w + (k * 16 + l16) * 4);
          z = fmaf(bf_lo(xv.x), bf_lo(gv.x), z); z = fmaf(bf_hi(xv.x), bf_hi(gv.x), z);
          z = fmaf(bf_lo(xv.y), bf_lo(gv.y), z); z = fmaf(bf_hi(xv.y), bf_hi(gv.y), z);
        }
#pragma unroll
        for (int o = 1; o < 16; o <<= 1) z += __shfl_xor_sync(0xffffffffu, z, o);
        if (l16 == 0) sts32v(sb + F_G + rr * 4, __float_as_uint(1.f - 1.f / (1.f + __expf(-z))));
      }
      __syncwarp();
      bar_arrive(1, 352);
    }
  } else {
    asm volatile("setmaxnreg.inc.sync.aligned.u32 224;");
    const int wg = warp >> 2, row = wg * 64 + (warp & 3) * 16 + (lane >> 2), q = lane & 3;
    const uint32_t mark_t = 2 * (ldg1r(&g_ticket[1]) >> 4) + 1;
    int it = 0;
#pragma unroll 1
    for (int t = 0; t < 7; t++) {
      float d[128];
      ffn_tile<256>(d, sb, wg, 7, it, dead, lane);
      __nv_bfloat16* hp = g_h + (size_t)(r0 + row) * DFF + t * 256 + 2 * q;
#pragma unroll
      for (int n = 0; n < 32; n++) {
        *reinterpret_cast<uint32_t*>(hp + n * 8) = pack2(fmaxf(d[4 * n], 0.f), fmaxf(d[4 * n + 1], 0.f));
        *reinterpret_cast<uint32_t*>(hp + 8 * DFF + n * 8) = pack2(fmaxf(d[4 * n + 2], 0.f), fmaxf(d[4 * n + 3], 0.f));
      }
    }
    __threadfence();
    asm volatile("fence.proxy.async;" ::: "memory");
    mbar_arrive(hbar);
    bar_sync(1, 352);
    const float g0 = lds_f(sb + F_G + row * 4), g1 = lds_f(sb + F_G + row * 4 + 32);
    {
      float d[128];
      ffn_tile<256>(d, sb, wg, 28, it, dead, lane);
      ffn_finish<4>(d, g0, g1, sb, r0, row, 0, mark_t, out, tid);
    }
    {
      float d[96];
      ffn_tile<192>(d, sb, wg, 28, it, dead, lane);
      ffn_finish<3>(d, g0, g1, sb, r0, row, 4, mark_t, out, tid);
    }
    bar_sync(1, 256);
    if (tid == 0) atomicAdd(&g_ticket[1], 1);
    if (dead <= 0) g_err = 1;
  }
}

typedef CUresult (*EncodeFn)(CUtensorMap*, CUtensorMapDataType, cuuint32_t, void*, const cuuint64_t*, const cuuint64_t*,
                             const cuuint32_t*, const cuuint32_t*, CUtensorMapInterleave, CUtensorMapSwizzle,
                             CUtensorMapL2promotion, CUtensorMapFloatOOBfill);

void make_map(EncodeFn fn, CUtensorMap* m, const void* p, uint64_t rows, uint64_t cols, uint32_t box_rows) {
  const cuuint64_t dims[2] = {cols, rows}, strides[1] = {cols * 2};
  const cuuint32_t box[2] = {64, box_rows}, es[2] = {1, 1};
  fn(m, CU_TENSOR_MAP_DATA_TYPE_BFLOAT16, 2, const_cast<void*>(p), dims, strides, box, es, CU_TENSOR_MAP_INTERLEAVE_NONE,
     CU_TENSOR_MAP_SWIZZLE_128B, CU_TENSOR_MAP_L2_PROMOTION_L2_256B, CU_TENSOR_MAP_FLOAT_OOB_FILL_NONE);
}

}

extern "C" void kernel_launch(void* const* d_in, const int* in_sizes, int n_in, void* d_out, int out_size) {
  (void)in_sizes; (void)n_in; (void)out_size;
  const __nv_bfloat16* x = (const __nv_bfloat16*)d_in[0];
  const __nv_bfloat16* mem0 = (const __nv_bfloat16*)d_in[1];
  const __nv_bfloat16* gate_w = (const __nv_bfloat16*)d_in[10];
  static EncodeFn fn = nullptr;
  static void* hptr = nullptr;
  if (!fn) {
    cudaDriverEntryPointQueryResult qr;
    cudaGetDriverEntryPoint("cuTensorMapEncodeTiled", (void**)&fn, cudaEnableDefault, &qr);
    cudaGetSymbolAddress(&hptr, g_h);
    cudaFuncSetAttribute(rmt_kernel, cudaFuncAttributeMaxDynamicSharedMemorySize, T_SMEM);
    cudaFuncSetAttribute(rmt_kernel, cudaFuncAttributeNonPortableClusterSizeAllowed, 1);
    cudaFuncSetAttribute(ffn_kernel, cudaFuncAttributeMaxDynamicSharedMemorySize, F_SMEM);
  }
  CUtensorMap mWq, mWk, mWv, mWo, mX, mXf, mW1, mH, mW2;
  make_map(fn, &mWq, d_in[2], DM, NH * DH, 64);
  make_map(fn, &mWk, d_in[3], DM, NH * DH, 224);
  make_map(fn, &mWv, d_in[4], DM, NH * DH, 224);
  make_map(fn, &mWo, d_in[5], NH * DH, DM, 256);
  make_map(fn, &mX, x, SEQ, DM, 32);
  make_map(fn, &mXf, x, SEQ, DM, 128);
  make_map(fn, &mW1, d_in[8], DM, DFF, 64);
  make_map(fn, &mH, hptr, SEQ, DFF, 128);
  make_map(fn, &mW2, d_in[9], DFF, DM, 64);

  cudaLaunchConfig_t cfg = {};
  cudaLaunchAttribute at[1];
  cfg.gridDim = dim3(112); cfg.blockDim = dim3(384); cfg.dynamicSmemBytes = T_SMEM; cfg.stream = cudaStreamPerThread;
  at[0].id = cudaLaunchAttributeClusterDimension;
  at[0].val.clusterDim.x = 16; at[0].val.clusterDim.y = 1; at[0].val.clusterDim.z = 1;
  cfg.attrs = at; cfg.numAttrs = 1;
  cudaLaunchKernelEx(&cfg, rmt_kernel, mWq, mWk, mWv, mWo, mX, x, mem0, gate_w, (__nv_bfloat16*)d_out);

  cfg.gridDim = dim3(16); cfg.dynamicSmemBytes = F_SMEM;
  at[0].id = cudaLaunchAttributeProgrammaticStreamSerialization;
  at[0].val.programmaticStreamSerializationAllowed = 1;
  cudaLaunchKernelEx(&cfg, ffn_kernel, mXf, mW1, mH, mW2, x, gate_w, (__nv_bfloat16*)d_out);
}
```

```cpp
#include <cuda_runtime.h>
#include <cuda_bf16.h>
#include <cuda.h>
#include <stdint.h>

namespace {

#define DEVI __device__ __forceinline__

constexpr int SEQ = 2048, DM = 448, NH = 16, DH = 256, NSEG = 64, DFF = 1792;
constexpr float SC2 = 1.4426950408889634f / 16.0f;
constexpr float MASKV = -1.6e10f;
constexpr int SPIN_LIMIT = 1 << 22;

#define D_M 700
#define D_X 350
#define D_T 700
#define D_SS 150
#define O_SEND 1
#define D_S 550

__device__ __align__(1024) uint8_t g_xch_raw[18 * 65536];
DEVI uint8_t* xch(int blk) { return reinterpret_cast<uint8_t*>((reinterpret_cast<uintptr_t>(g_xch_raw) + 65535) & ~(uintptr_t)65535) + blk * 65536; }
constexpr uint32_t XC_R0 = 4096, XC_REG = 16384, XC_TWIN = 8192;
__device__ __align__(1024) float g_sacc[8][NH][1408];
__device__ __align__(1024) float g_stash[SEQ * DM];
__device__ __align__(1024) float g_b[SEQ * DM];
__device__ __align__(1024) __nv_bfloat16 g_h[SEQ * DFF];
__device__ __align__(1024) uint32_t g_mark[NSEG][112];
__device__ uint32_t g_ticket[2];
__device__ int g_err;
#define TS(i)
#define PTS(i)

DEVI uint32_t smem_u32(const void* p) { return (uint32_t)__cvta_generic_to_shared(p); }
DEVI uint32_t clk() { uint32_t c; asm volatile("mov.u32 %0, %%clock;" : "=r"(c) :: "memory"); return c; }
DEVI void mbar_init(uint32_t bar, uint32_t cnt) { asm volatile("mbarrier.init.shared::cta.b64 [%0], %1;" :: "r"(bar), "r"(cnt) : "memory"); }
DEVI void mbar_expect(uint32_t bar, uint32_t bytes) { asm volatile("mbarrier.arrive.expect_tx.shared::cta.b64 _, [%0], %1;" :: "r"(bar), "r"(bytes) : "memory"); }
DEVI void mbar_arrive(uint32_t bar) { asm volatile("mbarrier.arrive.shared::cta.b64 _, [%0];" :: "r"(bar) : "memory"); }
DEVI uint32_t lds32v(uint32_t a) { uint32_t v; asm volatile("ld.volatile.shared::cta.u32 %0, [%1];" : "=r"(v) : "r"(a) : "memory"); return v; }
DEVI void sts32v(uint32_t a, uint32_t v) { asm volatile("st.volatile.shared::cta.u32 [%0], %1;" :: "r"(a), "r"(v) : "memory"); }
DEVI void mbar_wait(uint32_t bar, uint32_t par, int& lim) {
  asm volatile("{\n.reg .pred p, q;\nWAIT_LOOP:\n"
               "mbarrier.try_wait.parity.shared::cta.b64 p, [%1], %2;\n"
               "sub.s32 %0, %0, 1;\nsetp.gt.and.s32 q, %0, 0, !p;\n@q bra.uni WAIT_LOOP;\n}"
               : "+r"(lim) : "r"(bar), "r"(par) : "memory");
}
DEVI void mbar_wait1(uint32_t bar, uint32_t par, int& lim) {
  asm volatile("{\n.reg .pred p, q;\nWAIT_LOOP:\n"
               "mbarrier.try_wait.parity.shared::cta.b64 p, [%1], %2;\n"
               "sub.s32 %0, %0, 1;\nsetp.gt.and.s32 q, %0, 0, !p;\n@q bra WAIT_LOOP;\n}"
               : "+r"(lim) : "r"(bar), "r"(par) : "memory");
}
DEVI bool elect() { uint32_t p; asm volatile("{\n.reg .pred p;\nelect.sync _|p, 0xffffffff;\nselp.u32 %0, 1, 0, p;\n}" : "=r"(p)); return p; }
DEVI bool bar_or(int id, int n, bool v) {
  uint32_t r;
  asm volatile("{\n.reg .pred p, q;\nsetp.ne.u32 q, %3, 0;\nbar.red.or.pred p, %1, %2, q;\nselp.u32 %0, 1, 0, p;\n}"
               : "=r"(r) : "r"(id), "r"(n), "r"((uint32_t)v) : "memory");
  return r;
}
DEVI void delay_until(uint32_t t0, uint32_t d) {
  asm volatile("{\n.reg .pred p;\n.reg .u32 t;\nDELAY_LOOP:\nmov.u32 t, %%clock;\nsub.u32 t, t, %0;\nsetp.lt.u32 p, t, %1;\n@p bra.uni DELAY_LOOP;\n}"
               :: "r"(t0), "r"(d) : "memory");
}
DEVI float rcp(float x) { float y; asm("rcp.approx.ftz.f32 %0, %1;" : "=f"(y) : "f"(x)); return y; }
template <class T> DEVI void pin(T& v) { asm volatile("" : "+r"(v)); }
template <class T> DEVI void pinp(T*& v) { asm volatile("" : "+l"(v)); }
DEVI void bar_sync(int id, int n) { asm volatile("bar.sync %0, %1;" :: "r"(id), "r"(n) : "memory"); }
DEVI void bar_arrive(int id, int n) { asm volatile("bar.arrive %0, %1;" :: "r"(id), "r"(n) : "memory"); }
DEVI void cluster_arrive_relaxed() { asm volatile("barrier.cluster.arrive.relaxed.aligned;" ::: "memory"); }
DEVI void cluster_arrive() { asm volatile("barrier.cluster.arrive.release.aligned;" ::: "memory"); }
DEVI void cluster_wait() { asm volatile("barrier.cluster.wait.acquire.aligned;" ::: "memory"); }
DEVI uint32_t mapa(uint32_t a, uint32_t r) { uint32_t o; asm("mapa.shared::cluster.u32 %0, %1, %2;" : "=r"(o) : "r"(a), "r"(r)); return o; }
DEVI uint32_t pack2(float lo, float hi) { uint32_t r; asm("cvt.rn.bf16x2.f32 %0, %1, %2;" : "=r"(r) : "f"(hi), "f"(lo)); return r; }
DEVI float ex2(float x) { float y; asm("ex2.approx.ftz.f32 %0, %1;" : "=f"(y) : "f"(x)); return y; }
DEVI float bf_lo(uint32_t v) { return __uint_as_float(v << 16); }
DEVI float bf_hi(uint32_t v) { return __uint_as_float(v & 0xffff0000u); }
DEVI void ldsm4(uint32_t (&r)[4], uint32_t a) {
  asm volatile("ldmatrix.sync.aligned.m8n8.x4.shared.b16 {%0,%1,%2,%3}, [%4];" : "=r"(r[0]), "=r"(r[1]), "=r"(r[2]), "=r"(r[3]) : "r"(a) : "memory");
}
DEVI void stsm4t(uint32_t a, uint32_t r0, uint32_t r1, uint32_t r2, uint32_t r3) {
  asm volatile("stmatrix.sync.aligned.m8n8.x4.trans.shared.b16 [%0], {%1,%2,%3,%4};" :: "r"(a), "r"(r0), "r"(r1), "r"(r2), "r"(r3) : "memory");
}
DEVI void stsm2t(uint32_t a, uint32_t r0, uint32_t r1) {
  asm volatile("stmatrix.sync.aligned.m8n8.x2.trans.shared.b16 [%0], {%1,%2};" :: "r"(a), "r"(r0), "r"(r1) : "memory");
}
DEVI void mma16(float (&c)[4], uint32_t a0, uint32_t a1, uint32_t a2, uint32_t a3, uint32_t b0, uint32_t b1) {
  asm("mma.sync.aligned.m16n8k16.row.col.f32.bf16.bf16.f32 {%0,%1,%2,%3},{%4,%5,%6,%7},{%8,%9},{%0,%1,%2,%3};"
      : "+f"(c[0]), "+f"(c[1]), "+f"(c[2]), "+f"(c[3]) : "r"(a0), "r"(a1), "r"(a2), "r"(a3), "r"(b0), "r"(b1));
}
DEVI void mma8(float (&c)[4], uint32_t a0, uint32_t a1, uint32_t b0) {
  asm("mma.sync.aligned.m16n8k8.row.col.f32.bf16.bf16.f32 {%0,%1,%2,%3},{%4,%5},{%6},{%0,%1,%2,%3};"
      : "+f"(c[0]), "+f"(c[1]), "+f"(c[2]), "+f"(c[3]) : "r"(a0), "r"(a1), "r"(b0));
}
DEVI void mma16v(float (&c)[4], uint32_t a0, uint32_t a1, uint32_t a2, uint32_t a3, uint32_t b0, uint32_t b1) {
  asm volatile("mma.sync.aligned.m16n8k16.row.col.f32.bf16.bf16.f32 {%0,%1,%2,%3},{%4,%5,%6,%7},{%8,%9},{%0,%1,%2,%3};"
      : "+f"(c[0]), "+f"(c[1]), "+f"(c[2]), "+f"(c[3]) : "r"(a0), "r"(a1), "r"(a2), "r"(a3), "r"(b0), "r"(b1));
}
DEVI void mma8v(float (&c)[4], uint32_t a0, uint32_t a1, uint32_t b0) {
  asm volatile("mma.sync.aligned.m16n8k8.row.col.f32.bf16.bf16.f32 {%0,%1,%2,%3},{%4,%5},{%6},{%0,%1,%2,%3};"
      : "+f"(c[0]), "+f"(c[1]), "+f"(c[2]), "+f"(c[3]) : "r"(a0), "r"(a1), "r"(b0));
}
DEVI float2 mma_rows8(const uint32_t (&a0)[4], const uint32_t (&a1)[4], const uint32_t (&b0)[4], const uint32_t (&b1)[4]) {
  float e0[4] = {0.f, 0.f, 0.f, 0.f}, e1[4] = {0.f, 0.f, 0.f, 0.f}, e2[4] = {0.f, 0.f, 0.f, 0.f}, e3[4] = {0.f, 0.f, 0.f, 0.f};
  mma16v(e0, a0[0], a0[1], a0[2], a0[3], b0[0], b0[1]);
  mma16v(e1, a0[0], a0[1], a0[2], a0[3], b0[2], b0[3]);
  mma16v(e2, a1[0], a1[1], a1[2], a1[3], b1[0], b1[1]);
  mma16v(e3, a1[0], a1[1], a1[2], a1[3], b1[2], b1[3]);
  return make_float2((e0[0] + e1[2]) + (e2[0] + e3[2]), (e0[1] + e1[3]) + (e2[1] + e3[3]));
}
DEVI void wg_fence() { asm volatile("wgmma.fence.sync.aligned;" ::: "memory"); }
DEVI void wg_commit() { asm volatile("wgmma.commit_group.sync.aligned;" ::: "memory"); }
template <int N> DEVI void wg_wait() { asm volatile("wgmma.wait_group.sync.aligned %0;" :: "n"(N) : "memory"); }
template <int N> DEVI void reg_fence(float (&d)[N]) {
#pragma unroll
  for (int i = 0; i < N; i++) asm volatile("" : "+f"(d[i]) :: "memory");
}
DEVI uint64_t desc128(uint32_t addr, uint32_t lbo16) {
  return (uint64_t)((addr >> 4) & 0x3fff) | ((uint64_t)lbo16 << 16) | (64ull << 32) | (1ull << 62);
}
DEVI void tma2d(uint32_t dst, const CUtensorMap* tm, int c0, int c1, uint32_t bar) {
  asm volatile("cp.async.bulk.tensor.2d.shared::cluster.global.mbarrier::complete_tx::bytes [%0], [%1, {%2, %3}], [%4];"
               :: "r"(dst), "l"(tm), "r"(c0), "r"(c1), "r"(bar) : "memory");
}
DEVI void tma2d_mc(uint32_t dst, const CUtensorMap* tm, int c0, int c1, uint32_t bar) {
  asm volatile("cp.async.bulk.tensor.2d.shared::cluster.global.mbarrier::complete_tx::bytes.multicast::cluster [%0], [%1, {%2, %3}], [%4], %5;"
               :: "r"(dst), "l"(tm), "r"(c0), "r"(c1), "r"(bar), "h"((uint16_t)0xffff) : "memory");
}
DEVI void bulk_mc(uint32_t dst, const void* src, uint32_t bytes, uint32_t bar) {
  asm volatile("cp.async.bulk.shared::cluster.global.mbarrier::complete_tx::bytes.multicast::cluster [%0], [%1], %2, [%3], %4;"
               :: "r"(dst), "l"(src), "r"(bytes), "r"(bar), "h"((uint16_t)0xffff) : "memory");
}
DEVI void st_async4(uint32_t a, float x, float y, float z, float w, uint32_t bar) {
  asm volatile("st.async.weak.shared::cluster.mbarrier::complete_tx::bytes.v4.f32 [%0], {%1,%2,%3,%4}, [%5];"
               :: "r"(a), "f"(x), "f"(y), "f"(z), "f"(w), "r"(bar) : "memory");
}
DEVI void st_async4u(uint32_t a, uint32_t x, uint32_t y, uint32_t z, uint32_t w, uint32_t bar) {
  asm volatile("st.async.weak.shared::cluster.mbarrier::complete_tx::bytes.v4.b32 [%0], {%1,%2,%3,%4}, [%5];"
               :: "r"(a), "r"(x), "r"(y), "r"(z), "r"(w), "r"(bar) : "memory");
}
DEVI uint32_t ldg1r(const void* p) { uint32_t v; asm volatile("ld.relaxed.gpu.global.u32 %0, [%1];" : "=r"(v) : "l"(p) : "memory"); return v; }
DEVI uint32_t exch_release(uint32_t* p, uint32_t v) { uint32_t o; asm volatile("atom.release.gpu.global.exch.b32 %0, [%1], %2;" : "=r"(o) : "l"(p), "r"(v) : "memory"); return o; }
DEVI uint32_t near_copy(uint8_t* blk) {
  uint32_t best[2] = {~0u, ~0u}, v = 0;
#pragma unroll 1
  for (int i = 0; i < 6; i++) {
    const uint8_t* p = blk + XC_R0 + 7936 + (i & 1) * XC_TWIN + (v & 4);
    const uint32_t t0 = clk();
    asm volatile("atom.relaxed.gpu.global.and.b32 %0, [%1], 0;" : "=r"(v) : "l"(p) : "memory");
    uint32_t t1;
    asm volatile("{\n.reg .pred p;\nPROBE_WAIT:\nsetp.eq.u32 p, %1, 0x5a5a5a5a;\n@p nanosleep.u32 32;\nmov.u32 %0, %%clock;\n}" : "=r"(t1) : "r"(v) : "memory");
    const uint32_t d = t1 - t0;
    if (i & 1) best[1] = min(best[1], d); else best[0] = min(best[0], d);
  }
  return best[1] < best[0] ? XC_TWIN : 0;
}
DEVI void tma2d_prefetch(const CUtensorMap* tm, int c0, int c1) {
  asm volatile("cp.async.bulk.prefetch.tensor.2d.L2.global [%0, {%1, %2}];" :: "l"(tm), "r"(c0), "r"(c1) : "memory");
}
DEVI void ldg2r(uint32_t& x, uint32_t& y, const void* p) { asm volatile("ld.relaxed.gpu.global.v2.u32 {%0,%1}, [%2];" : "=r"(x), "=r"(y) : "l"(p) : "memory"); }
DEVI void stg2r(void* p, uint32_t x, uint32_t y) { asm volatile("st.relaxed.gpu.global.v2.u32 [%0], {%1,%2};" :: "l"(p), "r"(x), "r"(y) : "memory"); }
DEVI void stg16r(void* p, uint16_t v) { asm volatile("st.relaxed.gpu.global.u16 [%0], %1;" :: "l"(p), "h"(v) : "memory"); }
DEVI void red2(float* p, float x, float y) { asm volatile("red.relaxed.gpu.global.add.v2.f32 [%0], {%1,%2};" :: "l"(p), "f"(x), "f"(y) : "memory"); }
DEVI float lds_f(uint32_t a) { float v; asm volatile("ld.shared.f32 %0, [%1];" : "=f"(v) : "r"(a) : "memory"); return v; }
DEVI float2 lds_f2(uint32_t a) { float2 v; asm volatile("ld.shared.v2.f32 {%0,%1}, [%2];" : "=f"(v.x), "=f"(v.y) : "r"(a) : "memory"); return v; }
DEVI float2 lds_f2v(uint32_t a) { float2 v; asm volatile("ld.volatile.shared.v2.f32 {%0,%1}, [%2];" : "=f"(v.x), "=f"(v.y) : "r"(a) : "memory"); return v; }
DEVI float4 lds_f4(uint32_t a) { float4 v; asm volatile("ld.shared.v4.f32 {%0,%1,%2,%3}, [%4];" : "=f"(v.x), "=f"(v.y), "=f"(v.z), "=f"(v.w) : "r"(a) : "memory"); return v; }
DEVI uint2 lds_u2(uint32_t a) { uint2 v; asm volatile("ld.shared.v2.u32 {%0,%1}, [%2];" : "=r"(v.x), "=r"(v.y) : "r"(a) : "memory"); return v; }
DEVI uint4 lds_u4(uint32_t a) { uint4 v; asm volatile("ld.shared.v4.u32 {%0,%1,%2,%3}, [%4];" : "=r"(v.x), "=r"(v.y), "=r"(v.z), "=r"(v.w) : "r"(a) : "memory"); return v; }
DEVI void sts_f2(uint32_t a, float x, float y) { asm volatile("st.shared.v2.f32 [%0], {%1,%2};" :: "r"(a), "f"(x), "f"(y) : "memory"); }
DEVI void sts_f4(uint32_t a, float x, float y, float z, float w) { asm volatile("st.shared.v4.f32 [%0], {%1,%2,%3,%4};" :: "r"(a), "f"(x), "f"(y), "f"(z), "f"(w) : "memory"); }
DEVI void sts_u2(uint32_t a, uint32_t x, uint32_t y) { asm volatile("st.shared.v2.u32 [%0], {%1,%2};" :: "r"(a), "r"(x), "r"(y) : "memory"); }
DEVI void sts_u4(uint32_t a, uint32_t x, uint32_t y, uint32_t z, uint32_t w) { asm volatile("st.shared.v4.u32 [%0], {%1,%2,%3,%4};" :: "r"(a), "r"(x), "r"(y), "r"(z), "r"(w) : "memory"); }
DEVI uint32_t tagf(float v, uint32_t tag) { return (__float_as_uint(v) & ~3u) | tag; }
DEVI float qmax(float v) { v = fmaxf(v, __shfl_xor_sync(0xffffffffu, v, 1)); return fmaxf(v, __shfl_xor_sync(0xffffffffu, v, 2)); }
DEVI float qsum(float v) { v += __shfl_xor_sync(0xffffffffu, v, 1); return v + __shfl_xor_sync(0xffffffffu, v, 2); }

__device__ __forceinline__ void wgmma_n224_kk(float (&d)[112], uint64_t da, uint64_t db, int sc) {
  asm volatile("{\n.reg .pred p;\nsetp.ne.b32 p, %114, 0;\n"
    "wgmma.mma_async.sync.aligned.m64n224k16.f32.bf16.bf16 {%0,%1,%2,%3,%4,%5,%6,%7,%8,%9,%10,%11,%12,%13,%14,%15,%16,%17,%18,%19,%20,%21,%22,%23,%24,%25,%26,%27,%28,%29,%30,%31,%32,%33,%34,%35,%36,%37,%38,%39,%40,%41,%42,%43,%44,%45,%46,%47,%48,%49,%50,%51,%52,%53,%54,%55,%56,%57,%58,%59,%60,%61,%62,%63,%64,%65,%66,%67,%68,%69,%70,%71,%72,%73,%74,%75,%76,%77,%78,%79,%80,%81,%82,%83,%84,%85,%86,%87,%88,%89,%90,%91,%92,%93,%94,%95,%96,%97,%98,%99,%100,%101,%102,%103,%104,%105,%106,%107,%108,%109,%110,%111}, %112, %113, p, 1, 1, 0, 0;\n}"
    : "+f"(d[0]),"+f"(d[1]),"+f"(d[2]),"+f"(d[3]),"+f"(d[4]),"+f"(d[5]),"+f"(d[6]),"+f"(d[7]),"+f"(d[8]),"+f"(d[9]),"+f"(d[10]),"+f"(d[11]),"+f"(d[12]),"+f"(d[13]),"+f"(d[14]),"+f"(d[15]),"+f"(d[16]),"+f"(d[17]),"+f"(d[18]),"+f"(d[19]),"+f"(d[20]),"+f"(d[21]),"+f"(d[22]),"+f"(d[23]),"+f"(d[24]),"+f"(d[25]),"+f"(d[26]),"+f"(d[27]),"+f"(d[28]),"+f"(d[29]),"+f"(d[30]),"+f"(d[31]),"+f"(d[32]),"+f"(d[33]),"+f"(d[34]),"+f"(d[35]),"+f"(d[36]),"+f"(d[37]),"+f"(d[38]),"+f"(d[39]),"+f"(d[40]),"+f"(d[41]),"+f"(d[42]),"+f"(d[43]),"+f"(d[44]),"+f"(d[45]),"+f"(d[46]),"+f"(d[47]),"+f"(d[48]),"+f"(d[49]),"+f"(d[50]),"+f"(d[51]),"+f"(d[52]),"+f"(d[53]),"+f"(d[54]),"+f"(d[55]),"+f"(d[56]),"+f"(d[57]),"+f"(d[58]),"+f"(d[59]),"+f"(d[60]),"+f"(d[61]),"+f"(d[62]),"+f"(d[63]),"+f"(d[64]),"+f"(d[65]),"+f"(d[66]),"+f"(d[67]),"+f"(d[68]),"+f"(d[69]),"+f"(d[70]),"+f"(d[71]),"+f"(d[72]),"+f"(d[73]),"+f"(d[74]),"+f"(d[75]),"+f"(d[76]),"+f"(d[77]),"+f"(d[78]),"+f"(d[79]),"+f"(d[80]),"+f"(d[81]),"+f"(d[82]),"+f"(d[83]),"+f"(d[84]),"+f"(d[85]),"+f"(d[86]),"+f"(d[87]),"+f"(d[88]),"+f"(d[89]),"+f"(d[90]),"+f"(d[91]),"+f"(d[92]),"+f"(d[93]),"+f"(d[94]),"+f"(d[95]),"+f"(d[96]),"+f"(d[97]),"+f"(d[98]),"+f"(d[99]),"+f"(d[100]),"+f"(d[101]),"+f"(d[102]),"+f"(d[103]),"+f"(d[104]),"+f"(d[105]),"+f"(d[106]),"+f"(d[107]),"+f"(d[108]),"+f"(d[109]),"+f"(d[110]),"+f"(d[111])
    : "l"(da),"l"(db),"r"(sc));
}
__device__ __forceinline__ void wgmma_n224_mk(float (&d)[112], uint64_t da, uint64_t db, int sc) {
  asm volatile("{\n.reg .pred p;\nsetp.ne.b32 p, %114, 0;\n"
    "wgmma.mma_async.sync.aligned.m64n224k16.f32.bf16.bf16 {%0,%1,%2,%3,%4,%5,%6,%7,%8,%9,%10,%11,%12,%13,%14,%15,%16,%17,%18,%19,%20,%21,%22,%23,%24,%25,%26,%27,%28,%29,%30,%31,%32,%33,%34,%35,%36,%37,%38,%39,%40,%41,%42,%43,%44,%45,%46,%47,%48,%49,%50,%51,%52,%53,%54,%55,%56,%57,%58,%59,%60,%61,%62,%63,%64,%65,%66,%67,%68,%69,%70,%71,%72,%73,%74,%75,%76,%77,%78,%79,%80,%81,%82,%83,%84,%85,%86,%87,%88,%89,%90,%91,%92,%93,%94,%95,%96,%97,%98,%99,%100,%101,%102,%103,%104,%105,%106,%107,%108,%109,%110,%111}, %112, %113, p, 1, 1, 1, 0;\n}"
    : "+f"(d[0]),"+f"(d[1]),"+f"(d[2]),"+f"(d[3]),"+f"(d[4]),"+f"(d[5]),"+f"(d[6]),"+f"(d[7]),"+f"(d[8]),"+f"(d[9]),"+f"(d[10]),"+f"(d[11]),"+f"(d[12]),"+f"(d[13]),"+f"(d[14]),"+f"(d[15]),"+f"(d[16]),"+f"(d[17]),"+f"(d[18]),"+f"(d[19]),"+f"(d[20]),"+f"(d[21]),"+f"(d[22]),"+f"(d[23]),"+f"(d[24]),"+f"(d[25]),"+f"(d[26]),"+f"(d[27]),"+f"(d[28]),"+f"(d[29]),"+f"(d[30]),"+f"(d[31]),"+f"(d[32]),"+f"(d[33]),"+f"(d[34]),"+f"(d[35]),"+f"(d[36]),"+f"(d[37]),"+f"(d[38]),"+f"(d[39]),"+f"(d[40]),"+f"(d[41]),"+f"(d[42]),"+f"(d[43]),"+f"(d[44]),"+f"(d[45]),"+f"(d[46]),"+f"(d[47]),"+f"(d[48]),"+f"(d[49]),"+f"(d[50]),"+f"(d[51]),"+f"(d[52]),"+f"(d[53]),"+f"(d[54]),"+f"(d[55]),"+f"(d[56]),"+f"(d[57]),"+f"(d[58]),"+f"(d[59]),"+f"(d[60]),"+f"(d[61]),"+f"(d[62]),"+f"(d[63]),"+f"(d[64]),"+f"(d[65]),"+f"(d[66]),"+f"(d[67]),"+f"(d[68]),"+f"(d[69]),"+f"(d[70]),"+f"(d[71]),"+f"(d[72]),"+f"(d[73]),"+f"(d[74]),"+f"(d[75]),"+f"(d[76]),"+f"(d[77]),"+f"(d[78]),"+f"(d[79]),"+f"(d[80]),"+f"(d[81]),"+f"(d[82]),"+f"(d[83]),"+f"(d[84]),"+f"(d[85]),"+f"(d[86]),"+f"(d[87]),"+f"(d[88]),"+f"(d[89]),"+f"(d[90]),"+f"(d[91]),"+f"(d[92]),"+f"(d[93]),"+f"(d[94]),"+f"(d[95]),"+f"(d[96]),"+f"(d[97]),"+f"(d[98]),"+f"(d[99]),"+f"(d[100]),"+f"(d[101]),"+f"(d[102]),"+f"(d[103]),"+f"(d[104]),"+f"(d[105]),"+f"(d[106]),"+f"(d[107]),"+f"(d[108]),"+f"(d[109]),"+f"(d[110]),"+f"(d[111])
    : "l"(da),"l"(db),"r"(sc));
}
__device__ __forceinline__ void wgmma_n32_rs(float (&d)[16], const uint32_t (&a)[4], uint64_t db, int sc) {
  asm volatile("{\n.reg .pred p;\nsetp.ne.b32 p, %21, 0;\n"
    "wgmma.mma_async.sync.aligned.m64n32k16.f32.bf16.bf16 {%0,%1,%2,%3,%4,%5,%6,%7,%8,%9,%10,%11,%12,%13,%14,%15}, {%16,%17,%18,%19}, %20, p, 1, 1, 0;\n}"
    : "+f"(d[0]),"+f"(d[1]),"+f"(d[2]),"+f"(d[3]),"+f"(d[4]),"+f"(d[5]),"+f"(d[6]),"+f"(d[7]),"+f"(d[8]),"+f"(d[9]),"+f"(d[10]),"+f"(d[11]),"+f"(d[12]),"+f"(d[13]),"+f"(d[14]),"+f"(d[15])
    : "r"(a[0]),"r"(a[1]),"r"(a[2]),"r"(a[3]),"l"(db),"r"(sc));
}
__device__ __forceinline__ void wgmma_n256_kn(float (&d)[128], uint64_t da, uint64_t db, int sc) {
  asm volatile("{\n.reg .pred p;\nsetp.ne.b32 p, %130, 0;\n"
    "wgmma.mma_async.sync.aligned.m64n256k16.f32.bf16.bf16 {%0,%1,%2,%3,%4,%5,%6,%7,%8,%9,%10,%11,%12,%13,%14,%15,%16,%17,%18,%19,%20,%21,%22,%23,%24,%25,%26,%27,%28,%29,%30,%31,%32,%33,%34,%35,%36,%37,%38,%39,%40,%41,%42,%43,%44,%45,%46,%47,%48,%49,%50,%51,%52,%53,%54,%55,%56,%57,%58,%59,%60,%61,%62,%63,%64,%65,%66,%67,%68,%69,%70,%71,%72,%73,%74,%75,%76,%77,%78,%79,%80,%81,%82,%83,%84,%85,%86,%87,%88,%89,%90,%91,%92,%93,%94,%95,%96,%97,%98,%99,%100,%101,%102,%103,%104,%105,%106,%107,%108,%109,%110,%111,%112,%113,%114,%115,%116,%117,%118,%119,%120,%121,%122,%123,%124,%125,%126,%127}, %128, %129, p, 1, 1, 0, 1;\n}"
    : "+f"(d[0]),"+f"(d[1]),"+f"(d[2]),"+f"(d[3]),"+f"(d[4]),"+f"(d[5]),"+f"(d[6]),"+f"(d[7]),"+f"(d[8]),"+f"(d[9]),"+f"(d[10]),"+f"(d[11]),"+f"(d[12]),"+f"(d[13]),"+f"(d[14]),"+f"(d[15]),"+f"(d[16]),"+f"(d[17]),"+f"(d[18]),"+f"(d[19]),"+f"(d[20]),"+f"(d[21]),"+f"(d[22]),"+f"(d[23]),"+f"(d[24]),"+f"(d[25]),"+f"(d[26]),"+f"(d[27]),"+f"(d[28]),"+f"(d[29]),"+f"(d[30]),"+f"(d[31]),"+f"(d[32]),"+f"(d[33]),"+f"(d[34]),"+f"(d[35]),"+f"(d[36]),"+f"(d[37]),"+f"(d[38]),"+f"(d[39]),"+f"(d[40]),"+f"(d[41]),"+f"(d[42]),"+f"(d[43]),"+f"(d[44]),"+f"(d[45]),"+f"(d[46]),"+f"(d[47]),"+f"(d[48]),"+f"(d[49]),"+f"(d[50]),"+f"(d[51]),"+f"(d[52]),"+f"(d[53]),"+f"(d[54]),"+f"(d[55]),"+f"(d[56]),"+f"(d[57]),"+f"(d[58]),"+f"(d[59]),"+f"(d[60]),"+f"(d[61]),"+f"(d[62]),"+f"(d[63]),"+f"(d[64]),"+f"(d[65]),"+f"(d[66]),"+f"(d[67]),"+f"(d[68]),"+f"(d[69]),"+f"(d[70]),"+f"(d[71]),"+f"(d[72]),"+f"(d[73]),"+f"(d[74]),"+f"(d[75]),"+f"(d[76]),"+f"(d[77]),"+f"(d[78]),"+f"(d[79]),"+f"(d[80]),"+f"(d[81]),"+f"(d[82]),"+f"(d[83]),"+f"(d[84]),"+f"(d[85]),"+f"(d[86]),"+f"(d[87]),"+f"(d[88]),"+f"(d[89]),"+f"(d[90]),"+f"(d[91]),"+f"(d[92]),"+f"(d[93]),"+f"(d[94]),"+f"(d[95]),"+f"(d[96]),"+f"(d[97]),"+f"(d[98]),"+f"(d[99]),"+f"(d[100]),"+f"(d[101]),"+f"(d[102]),"+f"(d[103]),"+f"(d[104]),"+f"(d[105]),"+f"(d[106]),"+f"(d[107]),"+f"(d[108]),"+f"(d[109]),"+f"(d[110]),"+f"(d[111]),"+f"(d[112]),"+f"(d[113]),"+f"(d[114]),"+f"(d[115]),"+f"(d[116]),"+f"(d[117]),"+f"(d[118]),"+f"(d[119]),"+f"(d[120]),"+f"(d[121]),"+f"(d[122]),"+f"(d[123]),"+f"(d[124]),"+f"(d[125]),"+f"(d[126]),"+f"(d[127])
    : "l"(da),"l"(db),"r"(sc));
}
__device__ __forceinline__ void wgmma_n192_kn(float (&d)[96], uint64_t da, uint64_t db, int sc) {
  asm volatile("{\n.reg .pred p;\nsetp.ne.b32 p, %98, 0;\n"
    "wgmma.mma_async.sync.aligned.m64n192k16.f32.bf16.bf16 {%0,%1,%2,%3,%4,%5,%6,%7,%8,%9,%10,%11,%12,%13,%14,%15,%16,%17,%18,%19,%20,%21,%22,%23,%24,%25,%26,%27,%28,%29,%30,%31,%32,%33,%34,%35,%36,%37,%38,%39,%40,%41,%42,%43,%44,%45,%46,%47,%48,%49,%50,%51,%52,%53,%54,%55,%56,%57,%58,%59,%60,%61,%62,%63,%64,%65,%66,%67,%68,%69,%70,%71,%72,%73,%74,%75,%76,%77,%78,%79,%80,%81,%82,%83,%84,%85,%86,%87,%88,%89,%90,%91,%92,%93,%94,%95}, %96, %97, p, 1, 1, 0, 1;\n}"
    : "+f"(d[0]),"+f"(d[1]),"+f"(d[2]),"+f"(d[3]),"+f"(d[4]),"+f"(d[5]),"+f"(d[6]),"+f"(d[7]),"+f"(d[8]),"+f"(d[9]),"+f"(d[10]),"+f"(d[11]),"+f"(d[12]),"+f"(d[13]),"+f"(d[14]),"+f"(d[15]),"+f"(d[16]),"+f"(d[17]),"+f"(d[18]),"+f"(d[19]),"+f"(d[20]),"+f"(d[21]),"+f"(d[22]),"+f"(d[23]),"+f"(d[24]),"+f"(d[25]),"+f"(d[26]),"+f"(d[27]),"+f"(d[28]),"+f"(d[29]),"+f"(d[30]),"+f"(d[31]),"+f"(d[32]),"+f"(d[33]),"+f"(d[34]),"+f"(d[35]),"+f"(d[36]),"+f"(d[37]),"+f"(d[38]),"+f"(d[39]),"+f"(d[40]),"+f"(d[41]),"+f"(d[42]),"+f"(d[43]),"+f"(d[44]),"+f"(d[45]),"+f"(d[46]),"+f"(d[47]),"+f"(d[48]),"+f"(d[49]),"+f"(d[50]),"+f"(d[51]),"+f"(d[52]),"+f"(d[53]),"+f"(d[54]),"+f"(d[55]),"+f"(d[56]),"+f"(d[57]),"+f"(d[58]),"+f"(d[59]),"+f"(d[60]),"+f"(d[61]),"+f"(d[62]),"+f"(d[63]),"+f"(d[64]),"+f"(d[65]),"+f"(d[66]),"+f"(d[67]),"+f"(d[68]),"+f"(d[69]),"+f"(d[70]),"+f"(d[71]),"+f"(d[72]),"+f"(d[73]),"+f"(d[74]),"+f"(d[75]),"+f"(d[76]),"+f"(d[77]),"+f"(d[78]),"+f"(d[79]),"+f"(d[80]),"+f"(d[81]),"+f"(d[82]),"+f"(d[83]),"+f"(d[84]),"+f"(d[85]),"+f"(d[86]),"+f"(d[87]),"+f"(d[88]),"+f"(d[89]),"+f"(d[90]),"+f"(d[91]),"+f"(d[92]),"+f"(d[93]),"+f"(d[94]),"+f"(d[95])
    : "l"(da),"l"(db),"r"(sc));
}

constexpr uint32_t XB = 28672;
constexpr uint32_t O_WQ = 5 * XB;
constexpr uint32_t O_WO = O_WQ + 32768;
constexpr uint32_t O_MIMG = O_WO + 32768;
constexpr uint32_t O_BAR = O_MIMG + 2 * 7168;
constexpr uint32_t O_TS = O_BAR + 256;
constexpr uint32_t T_SMEM = O_TS + 4096 + 128 + 1024;
constexpr uint32_t O_Z = 4 * XB;
constexpr uint32_t O_RS = O_Z + 2 * 5120;
constexpr uint32_t O_ORS = O_RS + 2 * 2048;
constexpr uint32_t O_P = O_ORS + 3 * 4096;
constexpr uint32_t O_SX = O_P + 2 * 2560;
constexpr uint32_t O_MJ = O_SX + 1536;
constexpr uint32_t O_ST = O_MJ + 2048;
constexpr uint32_t O_PC = O_ST + 2 * 5632;
constexpr uint32_t O_YB = O_PC + 128;
enum { B_X = 0, B_M = 4, B_RS = 6, B_O = 8, B_ZX = 10, B_P = 12, B_PF = 14, B_PE = 18, B_WQ = 22, B_WO = 23, B_T = 24, B_MJ = 26, B_OL = 28, B_N = 29 };
constexpr uint32_t O_C3 = O_BAR + 8 * B_N, O_NEAR = O_C3 + 4, O_TZ = O_NEAR + 8;
enum { N_ZM = 1, N_YM = 2, N_W1 = 3, N_INIT = 4, N_ZX = 5, N_REDO = 6, N_YX = 7, N_SS = 8, N_ST = 9 };

DEVI void gemm_m(const uint32_t (&w)[28][4], uint32_t img_lane, float (&c)[4]) {
  float acc[4][4];
#pragma unroll
  for (int i = 0; i < 4; i++) { acc[i][0] = acc[i][1] = acc[i][2] = acc[i][3] = 0.f; }
  uint32_t r[14][4];
#pragma unroll
  for (int u = 0; u < 14; u++) ldsm4(r[u], img_lane + u * 512);
#pragma unroll
  for (int u = 0; u < 14; u++) {
    mma16v(acc[(2 * u) & 3], w[2 * u][0], w[2 * u][1], w[2 * u][2], w[2 * u][3], r[u][0], r[u][1]);
    mma16v(acc[(2 * u + 1) & 3], w[2 * u + 1][0], w[2 * u + 1][1], w[2 * u + 1][2], w[2 * u + 1][3], r[u][2], r[u][3]);
  }
#pragma unroll
  for (int i = 0; i < 4; i++) c[i] = (acc[0][i] + acc[1][i]) + (acc[2][i] + acc[3][i]);
}

DEVI void gemm_x_issue(const uint32_t (&w)[28][4], uint32_t xbuf, float (&d)[16]) {
  const uint64_t b0 = desc128(xbuf, 1);
  wg_fence();
#pragma unroll
  for (int k = 0; k < 28; k++) wgmma_n32_rs(d, w[k], b0 + (uint64_t)((k >> 2) * 256 + (k & 3) * 2), k != 0);
  wg_commit();
}
DEVI void gemm_x(const uint32_t (&w)[28][4], uint32_t xbuf, float (&d)[16]) {
  gemm_x_issue(w, xbuf, d);
  wg_wait<0>();
  reg_fence(d);
}

template <int WHICH>
DEVI void build_weights(uint32_t (&w)[28][4], uint32_t sb, int& dead, int lane) {
  const uint32_t bar = sb + O_BAR;
  mbar_wait(bar + 8 * (WHICH ? B_WO : B_WQ), 0, dead);
  if ((threadIdx.x & 127) == 0) PTS(4 + WHICH);
#pragma unroll
  for (int half = 0; half < 2; half++) {
    float d[112];
#pragma unroll 1
    for (int fk = 0; fk < 4; fk++) {
      const int c = 2 * (4 * half + fk) + WHICH, st = c & 3;
      mbar_wait(bar + 8 * (B_PF + st), (c >> 2) & 1, dead);
      if ((threadIdx.x & 127) == 0) PTS(8 + c);
      const uint64_t db = desc128(sb + (st + 1) * XB, 1);
      wg_fence();
#pragma unroll
      for (int kk = 0; kk < 4; kk++) {
        if (WHICH == 0) wgmma_n224_kk(d, desc128(sb + O_WQ + fk * 8192 + kk * 32, 1), db + kk * 2, (fk | kk) != 0);
        else            wgmma_n224_mk(d, desc128(sb + O_WO + (fk * 4 + kk) * 2048, 1), db + kk * 2, (fk | kk) != 0);
      }
      wg_commit();
      wg_wait<0>();
      if (lane == 0) mbar_arrive(bar + 8 * (B_PE + st));
    }
    reg_fence(d);
#pragma unroll
    for (int kk = 0; kk < 14; kk++) {
      w[14 * half + kk][0] = pack2(d[8 * kk + 0], d[8 * kk + 1]);
      w[14 * half + kk][1] = pack2(d[8 * kk + 2], d[8 * kk + 3]);
      w[14 * half + kk][2] = pack2(d[8 * kk + 4], d[8 * kk + 5]);
      w[14 * half + kk][3] = pack2(d[8 * kk + 6], d[8 * kk + 7]);
    }
  }
}

DEVI void load7(uint32_t (&v)[14], const float* p, int stride) {
#pragma unroll
  for (int k = 0; k < 7; k++) ldg2r(v[2 * k], v[2 * k + 1], p + k * stride);
}
DEVI bool stale7(const uint32_t (&v)[14], uint32_t tag) {
  const uint32_t o = ((v[0] | v[1] | v[2]) | (v[3] | v[4] | v[5]) | (v[6] | v[7] | v[8])) | ((v[9] | v[10] | v[11]) | (v[12] | v[13]));
  const uint32_t a = ((v[0] & v[1] & v[2]) & (v[3] & v[4] & v[5]) & (v[6] & v[7] & v[8])) & ((v[9] & v[10] & v[11]) & (v[12] & v[13]));
  return (((o ^ tag) | (a ^ tag)) & 3u) != 0;
}
DEVI float2 add7(const uint32_t (&v)[14]) {
  float2 r;
  r.x = ((__uint_as_float(v[0]) + __uint_as_float(v[2])) + (__uint_as_float(v[4]) + __uint_as_float(v[6]))) +
        ((__uint_as_float(v[8]) + __uint_as_float(v[10])) + __uint_as_float(v[12]));
  r.y = ((__uint_as_float(v[1]) + __uint_as_float(v[3])) + (__uint_as_float(v[5]) + __uint_as_float(v[7]))) +
        ((__uint_as_float(v[9]) + __uint_as_float(v[11])) + __uint_as_float(v[13]));
  return r;
}

DEVI void poll_smm(const float* pm, uint32_t res, uint32_t tag, uint32_t t0, uint32_t d, int& lim) {
  delay_until(t0, d);
  while (__any_sync(0xffffffffu, (lds32v(res) & 3) != tag) && --lim > 0) {
    uint32_t vm[14];
    load7(vm, pm, 64);
    if (!__any_sync(0xffffffffu, stale7(vm, tag))) {
      const float2 sm = add7(vm);
      sts_u2(res, tagf(sm.x, tag), tagf(sm.y, tag));
      break;
    }
  }
}

__global__ void __launch_bounds__(384, 1)
rmt_kernel(const __grid_constant__ CUtensorMap tmWq, const __grid_constant__ CUtensorMap tmWk,
           const __grid_constant__ CUtensorMap tmWv, const __grid_constant__ CUtensorMap tmWo,
           const __grid_constant__ CUtensorMap tmX, const __nv_bfloat16* __restrict__ x,
           const __nv_bfloat16* __restrict__ mem0, const __nv_bfloat16* __restrict__ gate_w, __nv_bfloat16* __restrict__ out) {
  extern __shared__ uint8_t smem_raw[];
  const uint32_t sb = (smem_u32(smem_raw) + 1023) & ~1023u;
  const uint32_t bar = sb + O_BAR;
  int lim = SPIN_LIMIT;
  int tid;
  uint32_t h, j;
  asm volatile("mov.u32 %0, %%tid.x;" : "=r"(tid));
  asm volatile("mov.u32 %0, %%cluster_ctarank;" : "=r"(h));
  asm volatile("mov.u32 %0, %%clusterid.x;" : "=r"(j));
  const int lane = tid & 31, warp = __shfl_sync(0xffffffffu, tid >> 5, 0);
  if (warp == 0) PTS(0);

  if (warp == 8) {
    if (elect()) {
#pragma unroll
      for (int i = 0; i < 4; i++) mbar_init(bar + 8 * (B_PF + i), 1);
      mbar_init(bar + 8 * B_WQ, 1);
      mbar_init(bar + 8 * B_WO, 1);
      asm volatile("fence.mbarrier_init.release.cluster;" ::: "memory");
      PTS(1);
      mbar_expect(bar + 8 * B_PF, XB);
      tma2d(sb + XB, &tmWk, h * DH, 0, bar + 8 * B_PF);
      PTS(27);
      mbar_expect(bar + 8 * B_WQ, 32768);
#pragma unroll
      for (int k = 0; k < 4; k++) tma2d(sb + O_WQ + k * 8192, &tmWq, h * DH + k * 64, j * 64, bar + 8 * B_WQ);
      PTS(28);
      mbar_expect(bar + 8 * B_WO, 32768);
      tma2d(sb + O_WO, &tmWo, j * 64, h * DH, bar + 8 * B_WO);
      PTS(29);
#pragma unroll
      for (int c = 1; c < 4; c++) {
        mbar_expect(bar + 8 * (B_PF + c), XB);
        tma2d(sb + (c + 1) * XB, (c & 1) ? &tmWv : &tmWk, h * DH + (c >> 1) * 64, 0, bar + 8 * (B_PF + c));
      }
      PTS(30);
      int c = 4 + j;
      tma2d_prefetch((c & 1) ? &tmWv : &tmWk, h * DH + ((c >> 1) & 3) * 64, (c >> 3) * 224);
      c += 7;
      if (c < 16) tma2d_prefetch((c & 1) ? &tmWv : &tmWk, h * DH + ((c >> 1) & 3) * 64, 224);
    }
  } else if (warp == 9) {
    if (elect()) {
#pragma unroll
      for (int i = 0; i < B_N; i++)
        if (i < B_PF || (i >= B_PE && i < B_WQ) || i >= B_T) mbar_init(bar + 8 * i, i >= B_MJ ? 1 : i >= B_T ? 3 : i >= B_PE ? 4 : i >= B_P ? 2 : i >= B_ZX ? 4 : 1);
      sts32v(sb + O_C3, 0);
      mbar_expect(bar + 8 * B_X, XB);
      mbar_expect(bar + 8 * B_OL, 4096);
#pragma unroll
      for (int i = 0; i < 2; i++) { mbar_expect(bar + 8 * (B_RS + i), 2048); mbar_expect(bar + 8 * (B_O + i), 4096); }
      asm volatile("fence.mbarrier_init.release.cluster;" ::: "memory");
    }
  }
  asm volatile("griddepcontrol.launch_dependents;");
  if (warp == 8) PTS(2);
  __syncthreads();
  cluster_arrive_relaxed();
  if (warp == 0) PTS(3);

  if (warp < 4) {
    asm volatile("setmaxnreg.inc.sync.aligned.u32 216;");
    uint32_t w[28][4];
    build_weights<0>(w, sb, lim, lane);
    if (warp == 0) PTS(6);
    cluster_wait();
    cluster_arrive_relaxed();
    uint32_t zst = sb + O_Z + ((2 * warp + ((lane >> 3) & 1)) * 40 + 8 * (lane >> 4) + (lane & 7)) * 16;
    const int mt = warp & 1, n0 = (warp >> 1) * 3;
    const int ch = lane >> 3, chp = (ch >> 1) | ((ch & 1) << 1);
    uint32_t zld = sb + O_Z + ((warp == 2 ? chp : ch) * 40 + (lane & 7)) * 16 + (warp == 2 ? 0 : n0 * 128);
    const int xrow = 16 * mt + (lane & 15);
    uint32_t xq = sb + j * 4096 + xrow * 128 + (((lane >> 4) ^ (xrow & 7)) << 4);
    uint32_t mimg = sb + O_MIMG + lane * 16, sta = sb + O_ST + (warp == 3 ? 4096 : mt * 2048) + lane * 16;
    uint8_t* p_smm = xch(h) + (XC_R0 + 2 * XC_REG + j * 256 + lane * 8);
    pin(zst); pin(zld); pin(xq); pin(mimg); pin(sta); pinp(p_smm);
    {
      float d[16];
      mbar_wait(bar + 8 * B_X, 0, lim);
      gemm_x(w, sb, d);
      if (warp == 0) PTS(7);
      cluster_wait();
      if (warp == 0) PTS(24);
      stsm4t(zst + 8 * 16, pack2(d[0], d[1]), pack2(d[2], d[3]), pack2(d[4], d[5]), pack2(d[6], d[7]));
      stsm4t(zst + 24 * 16, pack2(d[8], d[9]), pack2(d[10], d[11]), pack2(d[12], d[13]), pack2(d[14], d[15]));
      __syncwarp();
      if (lane == 0) mbar_arrive(bar + 8 * B_ZX);
      bar_sync(N_INIT, 352);
    }
    const uint8_t* p_sxr = xch(h) + (XC_R0 + (warp & 1) * 512 + lane * 16 + lds32v(sb + O_NEAR));
    const uint32_t o_a = mapa(sb + O_ORS + h * 256 + warp * 64 + (lane & 3) * 16, lane >> 2);
    const uint32_t o_b = mapa(bar + 8 * B_O, lane >> 2);
    const uint32_t o_st = mapa(sb, 8) - mapa(sb, 0);
    uint32_t oh[8];
    auto token_pv = [&](int sp) {
      const uint32_t p16 = mimg + (O_P - O_MIMG) + (sp & 1) * 2560, p8 = p16 + 1024 - lane * 8, yb = sb + O_YB + (sp & 1) * 5120 + tid * 16;
      const uint4 y0 = lds_u4(yb), y1 = lds_u4(yb + 2048);
      const uint2 ymp = lds_u2(yb + 4096 - tid * 8);
      mbar_wait(bar + 8 * (B_P + (sp & 1)), (sp >> 1) & 1, lim);
      const uint2 m0 = lds_u2(p8), m1 = lds_u2(p8 + 1280);
      const uint4 p0 = lds_u4(p16), p1 = lds_u4(p16 + 512), p2 = lds_u4(p16 + 1280), p3 = lds_u4(p16 + 1280 + 512);
      float o0[4] = {0.f, 0.f, 0.f, 0.f}, o1[4] = {0.f, 0.f, 0.f, 0.f}, o2[4] = {0.f, 0.f, 0.f, 0.f}, o3[4] = {0.f, 0.f, 0.f, 0.f};
      mma8(o0, m0.x, m0.y, ymp.x);
      mma8(o1, m0.x, m0.y, ymp.y);
      mma8(o2, m1.x, m1.y, ymp.x);
      mma8(o3, m1.x, m1.y, ymp.y);
      mma16(o0, p0.x, p0.y, p0.z, p0.w, y0.x, y0.y);
      mma16(o1, p0.x, p0.y, p0.z, p0.w, y0.z, y0.w);
      mma16(o2, p2.x, p2.y, p2.z, p2.w, y0.x, y0.y);
      mma16(o3, p2.x, p2.y, p2.z, p2.w, y0.z, y0.w);
      mma16(o0, p1.x, p1.y, p1.z, p1.w, y1.x, y1.y);
      mma16(o1, p1.x, p1.y, p1.z, p1.w, y1.z, y1.w);
      mma16(o2, p3.x, p3.y, p3.z, p3.w, y1.x, y1.y);
      mma16(o3, p3.x, p3.y, p3.z, p3.w, y1.z, y1.w);
      oh[0] = pack2(o0[0], o0[1]); oh[1] = pack2(o1[0], o1[1]); oh[2] = pack2(o0[2], o0[3]); oh[3] = pack2(o1[2], o1[3]);
      oh[4] = pack2(o2[0], o2[1]); oh[5] = pack2(o3[0], o3[1]); oh[6] = pack2(o2[2], o2[3]); oh[7] = pack2(o3[2], o3[3]);
    };
    auto token_send = [&](int sp) {
      const bool last = sp == NSEG - 1;
      const uint32_t oa = o_a + (last ? 2 : sp & 1) * 4096, ob = o_b + (last ? B_OL - B_O : sp & 1) * 8;
      st_async4u(oa, oh[0], oh[1], oh[2], oh[3], ob);
      st_async4u(oa + o_st, oh[4], oh[5], oh[6], oh[7], ob + o_st);
    };
#pragma unroll 1
    for (int s = 0; s < NSEG; s++) {
      const bool rec = s < NSEG - 1;
      uint32_t img = mimg + (s & 1) * 7168, zs = zst + (s & 1) * 5120, zl = zld + (s & 1) * 5120;
      uint32_t tag = ((s >> 1) + 1) & 3;
      uint8_t* smm = p_smm + (s & 1) * 1792;
      pin(img); pin(zs); pin(zl); pin(tag); pinp(smm);
      uint32_t a[4][4];
      if (warp == 2 && rec) {
        const uint32_t mj = s ? mimg + (O_MJ - O_MIMG) + (s & 1) * 1024 : img + j * 1024;
        if (s) mbar_wait(bar + 8 * (B_MJ + (s & 1)), ((s - 1) >> 1) & 1, lim);
        ldsm4(a[0], mj);
        ldsm4(a[1], mj + 512);
      }
      if (s) mbar_wait(bar + 8 * (B_M + (s & 1)), ((s - 1) >> 1) & 1, lim);
      if (warp == 2) TS(0);
      float c[4];
      gemm_m(w, img, c);
      stsm2t(zs, pack2(c[0], c[1]), pack2(c[2], c[3]));
      if (warp == 1) TS(24);
      if (__builtin_expect(bar_or(N_ZM, 160, false), 0)) {
        gemm_m(w, img, c);
        stsm2t(zs, pack2(c[0], c[1]), pack2(c[2], c[3]));
        bar_sync(N_REDO, 128);
      }
      uint32_t b0[4], b1[4];
      if (warp == 2) {
        ldsm4(b0, zl);
        ldsm4(b1, zl + 4 * 640);
        bar_arrive(N_YM, 160);
        const float2 e = mma_rows8(a[0], a[1], b0, b1);
        if (rec) { stg2r(smm, tagf(e.x, tag), tagf(e.y, tag)); stg2r(smm + XC_TWIN, tagf(e.x, tag), tagf(e.y, tag)); }
        TS(2);
      }
      else if (warp < 2 && rec) {
        const uint8_t* px = p_sxr + (s & 1) * XC_REG;
        uint32_t v[7][4], bad;
        do {
#pragma unroll
          for (int k = 0; k < 7; k++)
            asm volatile("ld.relaxed.gpu.global.v4.u32 {%0,%1,%2,%3}, [%4];" : "=r"(v[k][0]), "=r"(v[k][1]), "=r"(v[k][2]), "=r"(v[k][3]) : "l"(px + k * 1024) : "memory");
          bad = 0;
#pragma unroll
          for (int k = 0; k < 7; k++) bad |= (v[k][0] ^ tag) | (v[k][1] ^ tag) | (v[k][2] ^ tag) | (v[k][3] ^ tag);
        } while (__any_sync(0xffffffffu, bad & 3) && --lim > 0);
        float r[4];
#pragma unroll
        for (int i = 0; i < 4; i++)
          r[i] = ((__uint_as_float(v[0][i]) + __uint_as_float(v[1][i])) + (__uint_as_float(v[2][i]) + __uint_as_float(v[3][i]))) +
                 ((__uint_as_float(v[4][i]) + __uint_as_float(v[5][i])) + __uint_as_float(v[6][i]));
        sts_f4(mimg + (O_SX - O_MIMG) + warp * 512, r[0], r[1], r[2], r[3]);
        bar_arrive(N_W1, 192);
      }
      bar_sync(N_SS, 128);
      if (s >= 2) token_send(s - 2);
      bar_sync(N_ST, 256);
      if (warp != 2) {
        const uint32_t st = sta + (s & 1) * 5632, aq = xq + (s & 3) * XB;
        uint32_t b2[4], b3[4], b4[4], b5[4];
        ldsm4(a[0], aq); ldsm4(b0, zl); ldsm4(b2, zl + 128); ldsm4(b4, zl + 256); ldsm4(a[1], aq ^ 32);
        ldsm4(a[2], aq ^ 64); ldsm4(b1, zl + 2560); ldsm4(b3, zl + 2560 + 128); ldsm4(b5, zl + 2560 + 256); ldsm4(a[3], aq ^ 96);
        float e0[4] = {0.f, 0.f, 0.f, 0.f}, e1[4] = {0.f, 0.f, 0.f, 0.f}, e2[4] = {0.f, 0.f, 0.f, 0.f};
        mma16(e0, a[0][0], a[0][1], a[0][2], a[0][3], b0[0], b0[1]);
        mma16(e1, a[0][0], a[0][1], a[0][2], a[0][3], b2[0], b2[1]);
        mma16(e2, a[0][0], a[0][1], a[0][2], a[0][3], b4[0], b4[1]);
        mma16(e0, a[1][0], a[1][1], a[1][2], a[1][3], b0[2], b0[3]);
        mma16(e1, a[1][0], a[1][1], a[1][2], a[1][3], b2[2], b2[3]);
        mma16(e2, a[1][0], a[1][1], a[1][2], a[1][3], b4[2], b4[3]);
        mma16(e0, a[2][0], a[2][1], a[2][2], a[2][3], b1[0], b1[1]);
        mma16(e1, a[2][0], a[2][1], a[2][2], a[2][3], b3[0], b3[1]);
        mma16(e2, a[2][0], a[2][1], a[2][2], a[2][3], b5[0], b5[1]);
        mma16(e0, a[3][0], a[3][1], a[3][2], a[3][3], b1[2], b1[3]);
        mma16(e1, a[3][0], a[3][1], a[3][2], a[3][3], b3[2], b3[3]);
        mma16(e2, a[3][0], a[3][1], a[3][2], a[3][3], b5[2], b5[3]);
        sts_f4(st, e0[0], e0[1], e0[2], 1.f);
        sts_f4(st + 512, e0[3], e1[0], e1[1], 1.f);
        sts_f4(st + 1024, e1[2], e1[3], n0 ? 0.f : e2[0], 1.f);
        if (n0 == 0) sts_f4(st + 1536, e2[1], e2[2], e2[3], 1.f);
        if (warp == 1) TS(19);
        asm volatile("fence.proxy.async.shared::cta;" ::: "memory");
        __syncwarp();
        if (lane == 0) mbar_arrive(bar + 8 * (B_T + (s & 1)));
      }
      if (s) token_pv(s - 1);
      if (warp == 1) TS(5);
      if (rec) {
        float d[16];
        if (warp == 1) TS(16);
        mbar_wait(bar + 8 * (B_X + ((s + 1) & 3)), ((s + 1) >> 2) & 1, lim);
        bar_sync(N_ZX, 256);
        if (warp == 1) TS(17);
        gemm_x_issue(w, sb + ((s + 1) & 3) * XB, d);
        bar_arrive(N_YX, 256);
        wg_wait<0>();
        reg_fence(d);
        if (warp == 1) TS(18);
        const uint32_t zn = zst + ((s + 1) & 1) * 5120;
        stsm4t(zn + 8 * 16, pack2(d[0], d[1]), pack2(d[2], d[3]), pack2(d[4], d[5]), pack2(d[6], d[7]));
        stsm4t(zn + 24 * 16, pack2(d[8], d[9]), pack2(d[10], d[11]), pack2(d[12], d[13]), pack2(d[14], d[15]));
        __syncwarp();
        if (lane == 0) mbar_arrive(bar + 8 * (B_ZX + ((s + 1) & 1)));
        if (warp == 2) TS(3);
      }
    }
    token_send(NSEG - 2);
    token_pv(NSEG - 1);
    token_send(NSEG - 1);
    if (lim <= 0) g_err = 1;
    __syncwarp();
    if (warp == 0) PTS(25);
    cluster_arrive();
    cluster_wait();
  } else if (warp < 8) {
    asm volatile("setmaxnreg.inc.sync.aligned.u32 216;");
    const int wq = warp - 4;
    uint32_t w[28][4];
    build_weights<1>(w, sb, lim, lane);
    cluster_wait();
    cluster_arrive_relaxed();
    uint32_t yx[8], ym[2];
    {
      float d[16];
      mbar_wait(bar + 8 * B_X, 0, lim);
      gemm_x(w, sb, d);
#pragma unroll
      for (int i = 0; i < 8; i++) yx[i] = pack2(d[2 * i], d[2 * i + 1]);
      cluster_wait();
    }
    bar_sync(N_INIT, 352);
    const int ri = lane >> 2, q = lane & 3;
    uint32_t zld = sb + O_Z + (((lane >> 4) | ((lane >> 2) & 2)) * 40 + 8 + 8 * wq + (lane & 7)) * 16;
    uint32_t rs_a = mapa(sb + O_RS + h * 128 + ((ri & 1) * 4 + q) * 16, 4 * wq + (ri >> 1));
    uint32_t rs_b = mapa(bar + 8 * B_RS, 4 * wq + (ri >> 1));
    uint32_t mimg = sb + O_MIMG + lane * 16, l8 = sb + lane * 8;
    uint8_t* p_smx = xch(h) + (XC_R0 + j * 1024 + wq * 256 + lane * 8);
    const uint32_t yb = sb + O_YB + (tid & 127) * 16;
    sts_u4(yb, yx[0], yx[4], yx[1], yx[5]);
    sts_u4(yb + 2048, yx[2], yx[6], yx[3], yx[7]);
    pin(zld); pin(rs_a); pin(rs_b); pin(mimg); pin(l8); pinp(p_smx);

    uint32_t zb0[4], zb1[4];
    mbar_wait(bar + 8 * B_ZX, 0, lim);
    ldsm4(zb0, zld);
    ldsm4(zb1, zld + 4 * 640);

#pragma unroll 1
    for (int s = 0; s < NSEG; s++) {
      const bool rec = s < NSEG - 1;
      uint32_t img = mimg + (s & 1) * 7168, tag = ((s >> 1) + 1) & 3;
      uint32_t ra = rs_a + (s & 1) * 2048, rb = rs_b + (s & 1) * 8;
      uint8_t* smx = p_smx + (s & 1) * XC_REG;
      pin(img); pin(tag); pin(ra); pin(rb); pinp(smx);
      if (rec) {
        uint32_t a0[4], a1[4];
        const uint32_t mj = s ? mimg + (O_MJ - O_MIMG) + (s & 1) * 1024 : img + j * 1024;
        if (wq == 0) TS(26);
        if (s) mbar_wait(bar + 8 * (B_MJ + (s & 1)), ((s - 1) >> 1) & 1, lim);
        if (wq == 0) TS(27);
        ldsm4(a0, mj);
        ldsm4(a1, mj + 512);
        const float2 e = mma_rows8(a0, a1, zb0, zb1);
        const uint32_t r0 = tagf(e.x, tag), r1 = tagf(e.y, tag);
        stg2r(smx, r0, r1);
        stg2r(smx + XC_TWIN, r0, r1);
        if (wq == 0) TS(15);
      }
      if (wq == 0) TS(20);
      bar_sync(N_YM, 160);
      if (wq == 0) TS(21);
      {
        float c[4];
        gemm_m(w, img, c);
        ym[0] = pack2(c[0], c[1]);
        ym[1] = pack2(c[2], c[3]);
        sts_u2(yb + 4096 - (tid & 127) * 8 + (s & 1) * 5120, ym[0], ym[1]);
        bar_arrive(N_ST, 256);
      }
      if (wq == 0) TS(4);
      if (rec) {
        bar_sync(N_W1, 192);
        if (wq == 0) TS(22);
        float2 v[4];
#pragma unroll
        for (int n = 0; n < 4; n++) v[n] = lds_f2(l8 + O_SX + n * 256);
        const float mxx = qmax(fmaxf(fmaxf(fmaxf(v[0].x, v[0].y), fmaxf(v[1].x, v[1].y)), fmaxf(fmaxf(v[2].x, v[2].y), fmaxf(v[3].x, v[3].y))));
        const float nb = -mxx * SC2;
        float lx = 0.f;
        uint32_t pa[4];
#pragma unroll
        for (int n = 0; n < 4; n++) {
          const float p0 = ex2(fmaf(v[n].x, SC2, nb)), p1 = ex2(fmaf(v[n].y, SC2, nb));
          lx += p0 + p1;
          pa[n] = pack2(p0, p1);
        }
        float o0[4] = {0.f, 0.f, 0.f, 0.f}, o1[4] = {0.f, 0.f, 0.f, 0.f}, u0[4] = {0.f, 0.f, 0.f, 0.f}, u1[4] = {0.f, 0.f, 0.f, 0.f};
        mma16v(o0, pa[0], pa[1], pa[2], pa[3], yx[0], yx[4]);
        mma16v(u0, pa[0], pa[1], pa[2], pa[3], yx[2], yx[6]);
        mma16v(o1, pa[0], pa[1], pa[2], pa[3], yx[1], yx[5]);
        mma16v(u1, pa[0], pa[1], pa[2], pa[3], yx[3], yx[7]);
        o0[0] += u0[2]; o0[1] += u0[3]; o1[0] += u1[2]; o1[1] += u1[3];
        if (wq == 0) TS(7);
        float2 sm;
        do { sm = lds_f2v(l8 + O_SX + 1024 + (s & 1) * 256); } while (__any_sync(0xffffffffu, (__float_as_uint(sm.x) & 3) != tag) && --lim > 0);
        if (wq == 0) TS(8);
        const float mx = fmaxf(mxx, qmax(fmaxf(sm.x, sm.y)));
        const float nm = -mx * SC2;
        const float al = ex2(fmaf(mxx, SC2, nm)), p0 = ex2(fmaf(sm.x, SC2, nm)), p1 = ex2(fmaf(sm.y, SC2, nm));
        const uint32_t pp = pack2(p0, p1);
        o0[0] *= al; o0[1] *= al; o1[0] *= al; o1[1] *= al;
        mma8v(o0, pp, pp, ym[0]);
        mma8v(o1, pp, pp, ym[1]);
        bar_arrive(N_ZX, 256);
        const float inv = rcp(qsum(fmaf(al, lx, p0 + p1)));
        st_async4(ra, o0[0] * inv, o0[1] * inv, o1[0] * inv, o1[1] * inv, rb);
        if (wq == 0) TS(9);
      }
      if (rec) {
        float d[16];
        bar_sync(N_YX, 256);
        gemm_x(w, sb + ((s + 1) & 3) * XB, d);
#pragma unroll
        for (int i = 0; i < 8; i++) yx[i] = pack2(d[2 * i], d[2 * i + 1]);
        sts_u4(yb + ((s + 1) & 1) * 5120, yx[0], yx[4], yx[1], yx[5]);
        sts_u4(yb + ((s + 1) & 1) * 5120 + 2048, yx[2], yx[6], yx[3], yx[7]);
        mbar_wait(bar + 8 * (B_ZX + ((s + 1) & 1)), ((s + 1) >> 1) & 1, lim);
        ldsm4(zb0, zld + ((s + 1) & 1) * 5120);
        ldsm4(zb1, zld + ((s + 1) & 1) * 5120 + 4 * 640);
        if (wq == 0) TS(10);
      }
    }
    if (lim <= 0) g_err = 1;
    __syncwarp();
    cluster_arrive();
    cluster_wait();
  } else {
    asm volatile("setmaxnreg.dec.sync.aligned.u32 72;");
    if (warp == 8) {
      const int u = lane >> 2, comp = lane & 3;
      uint8_t* gm0 = xch(16) + (XC_R0 + (8 * j + 2 * (h >> 2) + (comp >> 1)) * 128 + (2 * (h & 3) + (u >> 2)) * 16 + ((u & 3) * 2 + (comp & 1)) * 2);
#pragma unroll
      for (int k = 0; k < 6; k++) stg16r(gm0 + k * XC_TWIN, 0xffff);
      cluster_wait();
      if (lane == 0) {
        if (h < 7) tma2d_mc(sb + h * 4096, &tmX, h * 64, 0, bar + 8 * B_X);
#pragma unroll 1
        for (int c = 4; c < 16; c++) {
          const int st = c & 3;
          mbar_wait1(bar + 8 * (B_PE + st), ((c >> 2) - 1) & 1, lim);
          mbar_expect(bar + 8 * (B_PF + st), XB);
          tma2d(sb + (st + 1) * XB, (c & 1) ? &tmWv : &tmWk, h * DH + ((c >> 1) & 3) * 64, (c >> 3) * 224, bar + 8 * (B_PF + st));
        }
      }
      __syncwarp();
      cluster_arrive();
      cluster_wait();
      if (lane == 0) {
        for (int k = 1; k < 3; k++) {
          mbar_expect(bar + 8 * (B_X + k), XB);
          if (h < 7) tma2d_mc(sb + k * XB + h * 4096, &tmX, h * 64, k * 32, bar + 8 * (B_X + k));
        }
      }
      uint32_t chk = sb + O_MIMG + lane * 32 + (lane >> 2) * 4, rs0 = sb + O_RS + lane * 4;
      const uint8_t* gnear = xch(16) + (XC_R0 + lds32v(sb + O_NEAR + 4));
      const uint32_t pc_st = sb + O_PC + ((comp >> 1) * 2 + (u >> 2)) * 16 + ((u & 3) * 2 + (comp & 1)) * 2;
      const uint32_t mj_a = mapa(sb + O_MJ + (2 * (h >> 2) + ((lane >> 1) & 1)) * 128 + (2 * (h & 3) + (lane & 1)) * 16, lane >> 2);
      const uint32_t mj_b = mapa(bar + 8 * B_MJ, lane >> 2), mj_st = mapa(sb, 8) - mapa(sb, 0);
      const uint8_t* p_smr = xch(h) + (XC_R0 + 2 * XC_REG + lane * 8 + lds32v(sb + O_NEAR));
      bar_sync(N_INIT, 352);
      pin(chk); pin(rs0); pinp(gm0);
      int s3 = 0;
#pragma unroll 1
      for (int s = 0; s < NSEG; s++) {
        uint32_t ck = chk + (s & 1) * 7168;
        pin(ck);
        bool redo = false;
        if (s) {
          mbar_wait(bar + 8 * (B_M + (s & 1)), ((s - 1) >> 1) & 1, lim);
          uint32_t v[7];
#pragma unroll
          for (int k = 0; k < 7; k++) v[k] = lds32v(ck + k * 1024);
          const uint32_t mx = __vimax3_u32(__vimax3_u32(v[0], v[1], v[2]), __vimax3_u32(v[3], v[4], v[5]), v[6]);
          if (__builtin_expect(__any_sync(0xffffffffu, mx == 0xffffffffu), 0)) {
            redo = true;
            uint32_t late = 0;
#pragma unroll
            for (int k = 0; k < 7; k++) late |= __any_sync(0xffffffffu, v[k] == 0xffffffffu) ? 1u << k : 0u;
            const uint8_t* p = gnear + s3 * XC_REG + lane * 16;
            while (late && --lim > 0) {
              const int k0 = __ffs(late) - 1, k1 = 31 - __clz(late);
              uint32_t t[4][4];
#pragma unroll
              for (int i = 0; i < 4; i++)
                asm volatile("ld.relaxed.gpu.global.v4.u32 {%0,%1,%2,%3}, [%4];" : "=r"(t[i][0]), "=r"(t[i][1]), "=r"(t[i][2]), "=r"(t[i][3])
                             : "l"(p + (i & 2 ? k1 : k0) * 1024 + (i & 1) * 512) : "memory");
#pragma unroll
              for (int i = 0; i < 2; i++) {
                const int kk = i ? k1 : k0;
                const uint32_t m2 = __vimax3_u32(__vimax3_u32(t[2 * i][0], t[2 * i][1], t[2 * i][2]), __vimax3_u32(t[2 * i][3], t[2 * i + 1][0], t[2 * i + 1][1]),
                                                 max(t[2 * i + 1][2], t[2 * i + 1][3]));
                if (!__any_sync(0xffffffffu, m2 == 0xffffffffu)) {
                  const uint32_t d = sb + O_MIMG + (s & 1) * 7168 + kk * 1024 + lane * 16;
                  sts_u4(d, t[2 * i][0], t[2 * i][1], t[2 * i][2], t[2 * i][3]);
                  sts_u4(d + 512, t[2 * i + 1][0], t[2 * i + 1][1], t[2 * i + 1][2], t[2 * i + 1][3]);
                  late &= ~(1u << kk);
                }
              }
            }
          }
        }
        TS(23);
        bar_or(N_ZM, 160, redo);
        if (s == NSEG - 1) break;
        const uint32_t tz = clk();
        if (lane == 0) sts32v(sb + O_TZ, tz);
        poll_smm(reinterpret_cast<const float*>(p_smr + (s & 1) * 1792), sb + O_SX + 1024 + (s & 1) * 256 + lane * 8, ((s >> 1) + 1) & 3, tz, D_S, lim);
        TS(6);
        const uint32_t mbar = bar + 8 * (B_M + ((s + 1) & 1));
        if (elect()) {
          mbar_expect(mbar, 7168);
          if (s < NSEG - 2) mbar_expect(bar + 8 * (B_MJ + ((s + 1) & 1)), 1024);
          if (s >= 1 && s + 2 < NSEG) {
            mbar_expect(bar + 8 * (B_X + ((s + 2) & 3)), XB);
            if (h < 7) tma2d_mc(sb + ((s + 2) & 3) * XB + h * 4096, &tmX, h * 64, (s + 2) * 32, bar + 8 * (B_X + ((s + 2) & 3)));
          }
        }
        const int s3n = s3 == 2 ? 0 : s3 + 1, s3p = s3 == 0 ? 2 : s3 - 1;
        stg16r(gm0 + s3p * XC_REG, 0xffff);
        stg16r(gm0 + s3p * XC_REG + XC_TWIN, 0xffff);
        while ((int)lds32v(sb + O_C3) < s - 2 + (s == NSEG - 2) && --lim > 0) {}
        uint32_t rb = rs0 + (s & 1) * 2048;
        uint8_t* gm = gm0 + s3n * XC_REG;
        uint32_t mdst = sb + O_MIMG + ((s + 1) & 1) * 7168 + h * 448, mb = mbar;
        const uint8_t* msrc = gnear + s3n * XC_REG + h * 448;
        s3 = s3n;
        pin(rb); pinp(gm); pin(mdst); pin(mb); pinp(msrc);
        mbar_wait(bar + 8 * (B_RS + (s & 1)), (s >> 1) & 1, lim);
        TS(11);
        float v[16];
#pragma unroll
        for (int k = 0; k < 16; k++) v[k] = lds_f(rb + k * 128);
        const float sum = (((v[0] + v[1]) + (v[2] + v[3])) + ((v[4] + v[5]) + (v[6] + v[7]))) +
                          (((v[8] + v[9]) + (v[10] + v[11])) + ((v[12] + v[13]) + (v[14] + v[15])));
        stg16r(gm, (uint16_t)(pack2(sum, 0.f) & 0xffff));
        stg16r(gm + XC_TWIN, (uint16_t)(pack2(sum, 0.f) & 0xffff));
        const uint32_t t0 = clk();
        TS(12);
        asm volatile("st.shared.u16 [%0], %1;" :: "r"(pc_st), "h"((uint16_t)(pack2(sum, 0.f) & 0xffff)) : "memory");
        __syncwarp();
        const float4 pc = lds_f4(sb + O_PC + (lane & 3) * 16);
        if (s < NSEG - 2) {
          const uint32_t o = ((s + 1) & 1) * 1024, ob = ((s + 1) & 1) * 8;
          st_async4(mj_a + o, pc.x, pc.y, pc.z, pc.w, mj_b + ob);
          st_async4(mj_a + o + mj_st, pc.x, pc.y, pc.z, pc.w, mj_b + ob + mj_st);
        }
        const bool el = elect();
        if (el) mbar_expect(bar + 8 * (B_RS + (s & 1)), 2048);
        TS(25);
        delay_until(t0, D_M);
        if (el) bulk_mc(mdst, msrc, 448, mb);
      }
    } else if (warp < 11) {
      const int mt = warp - 9, q = lane & 3;
      for (int t = mt * 32 + lane; t < 448; t += 64) {
        const uint4 v = *reinterpret_cast<const uint4*>(mem0 + (t & 7) * DM + (t >> 3) * 8);
        sts_u4(sb + O_MIMG + t * 16, v.x, v.y, v.z, v.w);
      }
      if (mt == 1 && lane == 0) sts32v(sb + O_NEAR + 4, near_copy(xch(16) + 2 * XC_REG - (blockIdx.x % 7) * 128));
      __syncwarp();
      cluster_wait();
      cluster_arrive();
      cluster_wait();
      const uint8_t* p_smr = xch(h) + (XC_R0 + 2 * XC_REG + lane * 8 + lds32v(sb + O_NEAR));
      if (mt == 1) { sts_u2(sb + O_SX + 1024 + lane * 8, 0, 0); sts_u2(sb + O_SX + 1280 + lane * 8, 0, 0); }
      bar_arrive(N_INIT, 352);
#pragma unroll 1
      for (int s = 0; s < NSEG; s++) {
        mbar_wait(bar + 8 * (B_T + (s & 1)), (s >> 1) & 1, lim);
        if (s < NSEG - 1)
          poll_smm(reinterpret_cast<const float*>(p_smr + (s & 1) * 1792), sb + O_SX + 1024 + (s & 1) * 256 + lane * 8, ((s >> 1) + 1) & 3,
                   lds32v(sb + O_TZ), D_S + (2 - mt) * D_SS, lim);
        const uint32_t t0 = clk();
        if (mt == 0 && elect()) {
          asm volatile("cp.reduce.async.bulk.global.shared::cta.bulk_group.add.f32 [%0], [%1], 5632;" :: "l"(&g_sacc[s & 7][h][0]), "r"(sb + O_ST + (s & 1) * 5632) : "memory");
          asm volatile("cp.async.bulk.commit_group;" ::: "memory");
          asm volatile("cp.async.bulk.wait_group.read 0;" ::: "memory");
        }
        __syncwarp();
        delay_until(t0, D_T);
        if (mt) TS(28);
        const float4* sp = reinterpret_cast<const float4*>(&g_sacc[s & 7][h][mt * 512 + lane * 4]);
        float u[7][4];
        bool stale;
        do {
          stale = false;
#pragma unroll
          for (int c = 0; c < 7; c++) {
            u[c][0] = u[c][1] = u[c][2] = 0.f; u[c][3] = 7.f;
            if (c < 4 || mt)
              asm volatile("ld.relaxed.gpu.global.v4.f32 {%0,%1,%2,%3}, [%4];" : "=f"(u[c][0]), "=f"(u[c][1]), "=f"(u[c][2]), "=f"(u[c][3]) : "l"(sp + c * 32) : "memory");
          }
#pragma unroll
          for (int c = 0; c < 7; c++) stale |= u[c][3] != 7.f;
        } while (__any_sync(0xffffffffu, stale) && --lim > 0);
        if (mt) TS(29);
        uint32_t pk[2][5];
        float v[2][10];
#pragma unroll
        for (int e = 0; e < 10; e++) {
          const int i = 4 * (e >> 1) + (e & 1);
          v[0][e] = u[i / 3][i % 3];
          v[1][e] = u[(i + 2) / 3][(i + 2) % 3];
        }
#pragma unroll
        for (int rg = 0; rg < 2; rg++) {
          const int row = 16 * mt + 8 * rg + (lane >> 2);
#pragma unroll
          for (int e = 2; e < 10; e++)
            if (8 * ((e >> 1) - 1) + 2 * q + (e & 1) > row) v[rg][e] = MASKV;
          float mx = v[rg][0];
#pragma unroll
          for (int e = 1; e < 10; e++) mx = fmaxf(mx, v[rg][e]);
          mx = qmax(mx);
          const float nb = -mx * SC2;
          float l = 0.f;
#pragma unroll
          for (int e = 0; e < 10; e++) { v[rg][e] = ex2(fmaf(v[rg][e], SC2, nb)); l += v[rg][e]; }
          const float inv = rcp(qsum(l));
#pragma unroll
          for (int n = 0; n < 5; n++) pk[rg][n] = pack2(v[rg][2 * n] * inv, v[rg][2 * n + 1] * inv);
        }
        const uint32_t pb = sb + O_P + (s & 1) * 2560 + mt * 1280;
        sts_u4(pb + lane * 16, pk[0][1], pk[1][1], pk[0][3], pk[1][3]);
        sts_u4(pb + 512 + lane * 16, pk[0][2], pk[1][2], pk[0][4], pk[1][4]);
        sts_u2(pb + 1024 + lane * 8, pk[0][0], pk[1][0]);
        __syncwarp();
        if (lane == 0) mbar_arrive(bar + 8 * (B_P + (s & 1)));
        if (mt == 1) TS(13);
        if (j + 7 * mt < 11) asm volatile("st.relaxed.gpu.global.v4.f32 [%0], {%1,%1,%1,%1};" :: "l"(&g_sacc[(s + 4) & 7][h][(j + 7 * mt) * 128 + lane * 4]), "f"(0.f) : "memory");
      }
    } else {
      const int t1 = lane >> 4, l16 = lane & 15;
      uint2 gw[7];
#pragma unroll
      for (int k = 0; k < 7; k++) gw[k] = *reinterpret_cast<const uint2*>(gate_w + (k * 16 + l16) * 4);
      const int col = j * 64 + ((lane >> 2) & 3) * 16 + (lane & 3) * 2;
      const uint32_t mark_t = 2 * (ldg1r(&g_ticket[0]) / 112) + 1, mark_f = mark_t + 1;
      if (lane == 0) {
        sts32v(sb + O_NEAR, near_copy(xch(h)));
      }
      __syncwarp();
      cluster_wait();
      cluster_arrive();
      cluster_wait();
#pragma unroll 1
      for (int s = 0; s < NSEG; s++) {
        const int tok = s * 32 + 16 * (h >> 3) + (h & 7) + 8 * t1;
        uint32_t* mk = &g_mark[s][j * 16 + h];
        bool have_b = ldg1r(mk) == mark_f;
        float z = 0.f;
#pragma unroll
        for (int k = 0; k < 7; k++) {
          const uint2 xv = *reinterpret_cast<const uint2*>(x + tok * DM + (k * 16 + l16) * 4);
          z = fmaf(bf_lo(xv.x), bf_lo(gw[k].x), z); z = fmaf(bf_hi(xv.x), bf_hi(gw[k].x), z);
          z = fmaf(bf_lo(xv.y), bf_lo(gw[k].y), z); z = fmaf(bf_hi(xv.y), bf_hi(gw[k].y), z);
        }
        const float* bp = &g_b[tok * DM + col];
        uint32_t b0 = 0, b1 = 0, b2 = 0, b3 = 0;
        if (have_b) { ldg2r(b0, b1, bp); ldg2r(b2, b3, bp + 8); }
#pragma unroll
        for (int o = 1; o < 16; o <<= 1) z += __shfl_xor_sync(0xffffffffu, z, o);
        const float g = 1.f / (1.f + __expf(-z));
        const bool last = s == NSEG - 1;
        mbar_wait(bar + 8 * (last ? B_OL : B_O + (s & 1)), last ? 0 : (s >> 1) & 1, lim);
        const uint32_t ob = sb + O_ORS + (last ? 2 : s & 1) * 4096 + t1 * 2048 + l16 * 16;
        float e[8] = {0.f, 0.f, 0.f, 0.f, 0.f, 0.f, 0.f, 0.f};
#pragma unroll
        for (int k = 0; k < 8; k++) {
          const uint4 c = lds_u4(ob + k * 256);
          e[0] += bf_lo(c.x); e[1] += bf_hi(c.x); e[2] += bf_lo(c.y); e[3] += bf_hi(c.y);
          e[4] += bf_lo(c.z); e[5] += bf_hi(c.z); e[6] += bf_lo(c.w); e[7] += bf_hi(c.w);
        }
        float4 a;
        a.x = g * ((t1 ? e[4] : e[0]) + __shfl_xor_sync(0xffffffffu, t1 ? e[0] : e[4], 16));
        a.y = g * ((t1 ? e[5] : e[1]) + __shfl_xor_sync(0xffffffffu, t1 ? e[1] : e[5], 16));
        a.z = g * ((t1 ? e[6] : e[2]) + __shfl_xor_sync(0xffffffffu, t1 ? e[2] : e[6], 16));
        a.w = g * ((t1 ? e[7] : e[3]) + __shfl_xor_sync(0xffffffffu, t1 ? e[3] : e[7], 16));
        __syncwarp();
        if (lane == 0 && s < NSEG - 3) mbar_expect(bar + 8 * (B_O + (s & 1)), 4096);
        if (lane == 0) sts32v(sb + O_C3, s + 1);
        const bool dbg_stash = false;
        if (!have_b || dbg_stash) {
          float* sp = &g_stash[tok * DM + col];
          *reinterpret_cast<float2*>(sp) = make_float2(a.x, a.y);
          *reinterpret_cast<float2*>(sp + 8) = make_float2(a.z, a.w);
        }
        if (!have_b) {
          __syncwarp();
          uint32_t old = 0;
          if (lane == 0) old = exch_release(mk, mark_t);
          have_b = __shfl_sync(0xffffffffu, old, 0) == mark_f;
          if (have_b) { ldg2r(b0, b1, bp); ldg2r(b2, b3, bp + 8); }
        }
        if (have_b) {
          uint32_t* op = reinterpret_cast<uint32_t*>(out + tok * DM + col);
          op[0] = pack2(a.x + __uint_as_float(b0), a.y + __uint_as_float(b1));
          op[4] = pack2(a.z + __uint_as_float(b2), a.w + __uint_as_float(b3));
        }
        TS(14);
      }
      if (lane == 0) atomicAdd(&g_ticket[0], 1);
    }
    if (lim <= 0) g_err = 1;
    __syncwarp();
    cluster_arrive();
    cluster_wait();
  }
}

constexpr uint32_t F_STAGE = 49152, F_BAR = 4 * F_STAGE, F_G = F_BAR + 128, F_M = F_G + 512, F_SMEM = F_M + 1024 + 1024;

template <int N>
DEVI void ffn_tile(float (&d)[N / 2], uint32_t sb, int wg, int nk, int& it, int& dead, int lane) {
#pragma unroll 1
  for (int k = 0; k < nk; k++, it++) {
    const int st = it & 3;
    mbar_wait(sb + F_BAR + 8 * st, (it >> 2) & 1, dead);
    const uint64_t da = desc128(sb + st * F_STAGE + wg * 8192, 1), db = desc128(sb + st * F_STAGE + 16384, 512);
    wg_fence();
#pragma unroll
    for (int kk = 0; kk < 4; kk++) {
      if constexpr (N == 256) wgmma_n256_kn(d, da + kk * 2, db + kk * 128, (k | kk) != 0);
      else                    wgmma_n192_kn(d, da + kk * 2, db + kk * 128, (k | kk) != 0);
    }
    wg_commit();
    if (k) { wg_wait<1>(); if (lane == 0) mbar_arrive(sb + F_BAR + 32 + 8 * ((it - 1) & 3)); }
  }
  wg_wait<0>();
  if (lane == 0) mbar_arrive(sb + F_BAR + 32 + 8 * ((it - 1) & 3));
  reg_fence(d);
}

template <int NJ>
DEVI void ffn_finish(float (&d)[NJ * 32], float g0, float g1, uint32_t sb, int r0, int row, int j0, uint32_t mark_t,
                     __nv_bfloat16* __restrict__ out, int tid) {
  const int wg = tid >> 7, t = tid & 127, off = (r0 + row) * DM + j0 * 64 + 2 * (tid & 3);
#pragma unroll
  for (int n = 0; n < NJ * 8; n++) {
    d[4 * n] *= g0; d[4 * n + 1] *= g0; d[4 * n + 2] *= g1; d[4 * n + 3] *= g1;
    *reinterpret_cast<float2*>(g_b + off + n * 8) = make_float2(d[4 * n], d[4 * n + 1]);
    *reinterpret_cast<float2*>(g_b + off + 8 * DM + n * 8) = make_float2(d[4 * n + 2], d[4 * n + 3]);
  }
  asm volatile("fence.release.gpu;" ::: "memory");
  bar_sync(2 + wg, 128);
  const uint32_t fl = sb + F_M + wg * 512;
  if (t < NJ * 32) {
    const int pair = (r0 >> 1) + wg * 32 + (t & 31);
    sts32v(fl + t * 4, exch_release(&g_mark[pair >> 4][(j0 + (t >> 5)) * 16 + (pair & 15)], mark_t + 1) == mark_t);
  }
  bar_sync(2 + wg, 128);
#pragma unroll
  for (int jj = 0; jj < NJ; jj++)
    if (lds32v(fl + (jj * 32 + ((row & 48) >> 1) + (row & 7)) * 4)) {
#pragma unroll
      for (int half = 0; half < 2; half++)
#pragma unroll
        for (int n = jj * 8; n < jj * 8 + 8; n++) {
          uint32_t a0, a1;
          ldg2r(a0, a1, g_stash + off + half * 8 * DM + n * 8);
          *reinterpret_cast<uint32_t*>(out + off + half * 8 * DM + n * 8) =
              pack2(__uint_as_float(a0) + d[4 * n + 2 * half], __uint_as_float(a1) + d[4 * n + 2 * half + 1]);
        }
    }
}

__global__ void __launch_bounds__(384, 1)
ffn_kernel(const __grid_constant__ CUtensorMap tmX, const __grid_constant__ CUtensorMap tmW1,
           const __grid_constant__ CUtensorMap tmH, const __grid_constant__ CUtensorMap tmW2,
           const __nv_bfloat16* __restrict__ x, const __nv_bfloat16* __restrict__ gate_w, __nv_bfloat16* __restrict__ out) {
  extern __shared__ uint8_t smem_raw[];
  const uint32_t sb = (smem_u32(smem_raw) + 1023) & ~1023u;
  const uint32_t hbar = sb + F_BAR + 64;
  int dead = SPIN_LIMIT;
  const int tid = threadIdx.x, lane = tid & 31, warp = __shfl_sync(0xffffffffu, tid >> 5, 0), r0 = blockIdx.x * 128;
  if (tid == 0) {
    for (int i = 0; i < 4; i++) { mbar_init(sb + F_BAR + 8 * i, 1); mbar_init(sb + F_BAR + 32 + 8 * i, 8); }
    mbar_init(hbar, 256);
    asm volatile("fence.mbarrier_init.release.cluster;" ::: "memory");
    asm volatile("fence.proxy.async.shared::cta;" ::: "memory");
  }
  __syncthreads();
  if (warp >= 8) {
    asm volatile("setmaxnreg.dec.sync.aligned.u32 56;");
    if (tid == 256) {
      int it = 0;
#pragma unroll 1
      for (int t = 0; t < 9; t++) {
        const int nk = t < 7 ? 7 : 28, nb = t < 8 ? 4 : 3;
        if (t == 7) mbar_wait1(hbar, 0, dead);
#pragma unroll 1
        for (int k = 0; k < nk; k++, it++) {
          const int st = it & 3;
          const uint32_t fb = sb + F_BAR + 8 * st, a = sb + st * F_STAGE;
          if (it >= 4) mbar_wait1(fb + 32, ((it >> 2) - 1) & 1, dead);
          mbar_expect(fb, 16384 + nb * 8192);
          tma2d(a, t < 7 ? &tmX : &tmH, k * 64, r0, fb);
          for (int b = 0; b < nb; b++) tma2d(a + 16384 + b * 8192, t < 7 ? &tmW1 : &tmW2, (t < 7 ? t : t - 7) * 256 + b * 64, k * 64, fb);
        }
      }
    } else if (warp > 8) {
      const int l16 = lane & 15;
      for (int r = (warp - 9) * 2 + (lane >> 4); r < 132; r += 6) {
        const int rr = r < 128 ? r : 127;
        float z = 0.f;
#pragma unroll
        for (int k = 0; k < 7; k++) {
          const uint2 xv = *reinterpret_cast<const uint2*>(x + (r0 + rr) * DM + (k * 16 + l16) * 4);
          const uint2 gv = *reinterpret_cast<const uint2*>(gate_w + (k * 16 + l16) * 4);
          z = fmaf(bf_lo(xv.x), bf_lo(gv.x), z); z = fmaf(bf_hi(xv.x), bf_hi(gv.x), z);
          z = fmaf(bf_lo(xv.y), bf_lo(gv.y), z); z = fmaf(bf_hi(xv.y), bf_hi(gv.y), z);
        }
#pragma unroll
        for (int o = 1; o < 16; o <<= 1) z += __shfl_xor_sync(0xffffffffu, z, o);
        if (l16 == 0) sts32v(sb + F_G + rr * 4, __float_as_uint(1.f - 1.f / (1.f + __expf(-z))));
      }
      __syncwarp();
      bar_arrive(1, 352);
    }
  } else {
    asm volatile("setmaxnreg.inc.sync.aligned.u32 224;");
    const int wg = warp >> 2, row = wg * 64 + (warp & 3) * 16 + (lane >> 2), q = lane & 3;
    const uint32_t mark_t = 2 * (ldg1r(&g_ticket[1]) >> 4) + 1;
    int it = 0;
#pragma unroll 1
    for (int t = 0; t < 7; t++) {
      float d[128];
      ffn_tile<256>(d, sb, wg, 7, it, dead, lane);
      __nv_bfloat16* hp = g_h + (size_t)(r0 + row) * DFF + t * 256 + 2 * q;
#pragma unroll
      for (int n = 0; n < 32; n++) {
        *reinterpret_cast<uint32_t*>(hp + n * 8) = pack2(fmaxf(d[4 * n], 0.f), fmaxf(d[4 * n + 1], 0.f));
        *reinterpret_cast<uint32_t*>(hp + 8 * DFF + n * 8) = pack2(fmaxf(d[4 * n + 2], 0.f), fmaxf(d[4 * n + 3], 0.f));
      }
    }
    __threadfence();
    asm volatile("fence.proxy.async;" ::: "memory");
    mbar_arrive(hbar);
    bar_sync(1, 352);
    const float g0 = lds_f(sb + F_G + row * 4), g1 = lds_f(sb + F_G + row * 4 + 32);
    {
      float d[128];
      ffn_tile<256>(d, sb, wg, 28, it, dead, lane);
      ffn_finish<4>(d, g0, g1, sb, r0, row, 0, mark_t, out, tid);
    }
    {
      float d[96];
      ffn_tile<192>(d, sb, wg, 28, it, dead, lane);
      ffn_finish<3>(d, g0, g1, sb, r0, row, 4, mark_t, out, tid);
    }
    bar_sync(1, 256);
    if (tid == 0) atomicAdd(&g_ticket[1], 1);
    if (dead <= 0) g_err = 1;
  }
}

typedef CUresult (*EncodeFn)(CUtensorMap*, CUtensorMapDataType, cuuint32_t, void*, const cuuint64_t*, const cuuint64_t*,
                             const cuuint32_t*, const cuuint32_t*, CUtensorMapInterleave, CUtensorMapSwizzle,
                             CUtensorMapL2promotion, CUtensorMapFloatOOBfill);

void make_map(EncodeFn fn, CUtensorMap* m, const void* p, uint64_t rows, uint64_t cols, uint32_t box_rows) {
  const cuuint64_t dims[2] = {cols, rows}, strides[1] = {cols * 2};
  const cuuint32_t box[2] = {64, box_rows}, es[2] = {1, 1};
  fn(m, CU_TENSOR_MAP_DATA_TYPE_BFLOAT16, 2, const_cast<void*>(p), dims, strides, box, es, CU_TENSOR_MAP_INTERLEAVE_NONE,
     CU_TENSOR_MAP_SWIZZLE_128B, CU_TENSOR_MAP_L2_PROMOTION_L2_256B, CU_TENSOR_MAP_FLOAT_OOB_FILL_NONE);
}

}

extern "C" void kernel_launch(void* const* d_in, const int* in_sizes, int n_in, void* d_out, int out_size) {
  (void)in_sizes; (void)n_in; (void)out_size;
  const __nv_bfloat16* x = (const __nv_bfloat16*)d_in[0];
  const __nv_bfloat16* mem0 = (const __nv_bfloat16*)d_in[1];
  const __nv_bfloat16* gate_w = (const __nv_bfloat16*)d_in[10];
  static EncodeFn fn = nullptr;
  static void* hptr = nullptr;
  if (!fn) {
    cudaDriverEntryPointQueryResult qr;
    cudaGetDriverEntryPoint("cuTensorMapEncodeTiled", (void**)&fn, cudaEnableDefault, &qr);
    cudaGetSymbolAddress(&hptr, g_h);
    cudaFuncSetAttribute(rmt_kernel, cudaFuncAttributeMaxDynamicSharedMemorySize, T_SMEM);
    cudaFuncSetAttribute(rmt_kernel, cudaFuncAttributeNonPortableClusterSizeAllowed, 1);
    cudaFuncSetAttribute(ffn_kernel, cudaFuncAttributeMaxDynamicSharedMemorySize, F_SMEM);
  }
  CUtensorMap mWq, mWk, mWv, mWo, mX, mXf, mW1, mH, mW2;
  make_map(fn, &mWq, d_in[2], DM, NH * DH, 64);
  make_map(fn, &mWk, d_in[3], DM, NH * DH, 224);
  make_map(fn, &mWv, d_in[4], DM, NH * DH, 224);
  make_map(fn, &mWo, d_in[5], NH * DH, DM, 256);
  make_map(fn, &mX, x, SEQ, DM, 32);
  make_map(fn, &mXf, x, SEQ, DM, 128);
  make_map(fn, &mW1, d_in[8], DM, DFF, 64);
  make_map(fn, &mH, hptr, SEQ, DFF, 128);
  make_map(fn, &mW2, d_in[9], DFF, DM, 64);

  cudaLaunchConfig_t cfg = {};
  cudaLaunchAttribute at[1];
  cfg.gridDim = dim3(112); cfg.blockDim = dim3(384); cfg.dynamicSmemBytes = T_SMEM; cfg.stream = cudaStreamPerThread;
  at[0].id = cudaLaunchAttributeClusterDimension;
  at[0].val.clusterDim.x = 16; at[0].val.clusterDim.y = 1; at[0].val.clusterDim.z = 1;
  cfg.attrs = at; cfg.numAttrs = 1;
  cudaLaunchKernelEx(&cfg, rmt_kernel, mWq, mWk, mWv, mWo, mX, x, mem0, gate_w, (__nv_bfloat16*)d_out);

  cfg.gridDim = dim3(16); cfg.dynamicSmemBytes = F_SMEM;
  at[0].id = cudaLaunchAttributeProgrammaticStreamSerialization;
  at[0].val.programmaticStreamSerializationAllowed = 1;
  cudaLaunchKernelEx(&cfg, ffn_kernel, mXf, mW1, mH, mW2, x, gate_w, (__nv_bfloat16*)d_out);
}
```

```cpp
#include <cuda_runtime.h>
#include <cuda_bf16.h>
#include <cuda.h>
#include <stdint.h>

namespace {

#define DEVI __device__ __forceinline__

constexpr int SEQ = 2048, DM = 448, NH = 16, DH = 256, NSEG = 64, DFF = 1792;
constexpr float SC2 = 1.4426950408889634f / 16.0f;
constexpr float MASKV = -1.6e10f;
constexpr int SPIN_LIMIT = 1 << 22;

#define D_M 100
#define D_X 150
#define D_T 700
#define D_SS 150
#define O_SEND 1
#define XP 2
#define D_S 200

__device__ __align__(1024) uint8_t g_xch_raw[18 * 65536];
DEVI uint8_t* xch(int blk) { return reinterpret_cast<uint8_t*>((reinterpret_cast<uintptr_t>(g_xch_raw) + 65535) & ~(uintptr_t)65535) + blk * 65536; }
constexpr uint32_t XC_R0 = 4096, XC_REG = 16384, XC_TWIN = 8192;
__device__ __align__(1024) float g_xacc[4][NH][512];
__device__ __align__(1024) float g_sacc[8][NH][1408];
__device__ __align__(1024) float g_stash[SEQ * DM];
__device__ __align__(1024) float g_b[SEQ * DM];
__device__ __align__(1024) __nv_bfloat16 g_h[SEQ * DFF];
__device__ __align__(1024) uint32_t g_bflag[32][2][8];
__device__ uint32_t g_ticket[2];
__device__ int g_err;
#define TS(i)
#define PTS(i)

DEVI uint32_t smem_u32(const void* p) { return (uint32_t)__cvta_generic_to_shared(p); }
DEVI uint32_t clk() { uint32_t c; asm volatile("mov.u32 %0, %%clock;" : "=r"(c) :: "memory"); return c; }
DEVI void mbar_init(uint32_t bar, uint32_t cnt) { asm volatile("mbarrier.init.shared::cta.b64 [%0], %1;" :: "r"(bar), "r"(cnt) : "memory"); }
DEVI void mbar_expect(uint32_t bar, uint32_t bytes) { asm volatile("mbarrier.arrive.expect_tx.shared::cta.b64 _, [%0], %1;" :: "r"(bar), "r"(bytes) : "memory"); }
DEVI void mbar_arrive(uint32_t bar) { asm volatile("mbarrier.arrive.shared::cta.b64 _, [%0];" :: "r"(bar) : "memory"); }
DEVI uint32_t lds32v(uint32_t a) { uint32_t v; asm volatile("ld.volatile.shared::cta.u32 %0, [%1];" : "=r"(v) : "r"(a) : "memory"); return v; }
DEVI void sts32v(uint32_t a, uint32_t v) { asm volatile("st.volatile.shared::cta.u32 [%0], %1;" :: "r"(a), "r"(v) : "memory"); }
DEVI void mbar_wait(uint32_t bar, uint32_t par, int& lim) {
  asm volatile("{\n.reg .pred p, q;\nWAIT_LOOP:\n"
               "mbarrier.try_wait.parity.shared::cta.b64 p, [%1], %2;\n"
               "sub.s32 %0, %0, 1;\nsetp.gt.and.s32 q, %0, 0, !p;\n@q bra.uni WAIT_LOOP;\n}"
               : "+r"(lim) : "r"(bar), "r"(par) : "memory");
}
DEVI void mbar_wait1(uint32_t bar, uint32_t par, int& lim) {
  asm volatile("{\n.reg .pred p, q;\nWAIT_LOOP:\n"
               "mbarrier.try_wait.parity.shared::cta.b64 p, [%1], %2;\n"
               "sub.s32 %0, %0, 1;\nsetp.gt.and.s32 q, %0, 0, !p;\n@q bra WAIT_LOOP;\n}"
               : "+r"(lim) : "r"(bar), "r"(par) : "memory");
}
DEVI bool elect() { uint32_t p; asm volatile("{\n.reg .pred p;\nelect.sync _|p, 0xffffffff;\nselp.u32 %0, 1, 0, p;\n}" : "=r"(p)); return p; }
DEVI bool bar_or(int id, int n, bool v) {
  uint32_t r;
  asm volatile("{\n.reg .pred p, q;\nsetp.ne.u32 q, %3, 0;\nbar.red.or.pred p, %1, %2, q;\nselp.u32 %0, 1, 0, p;\n}"
               : "=r"(r) : "r"(id), "r"(n), "r"((uint32_t)v) : "memory");
  return r;
}
DEVI void delay_until(uint32_t t0, uint32_t d) {
  asm volatile("{\n.reg .pred p;\n.reg .u32 t, u;\n.reg .u64 c;\nDELAY_LOOP:\nmov.u64 c, %%clock64;\nmov.b64 {t, u}, c;\nsub.u32 t, t, %0;\nsetp.lt.u32 p, t, %1;\n@p bra.uni DELAY_LOOP;\n}"
               :: "r"(t0), "r"(d) : "memory");
}
DEVI float rcp(float x) { float y; asm("rcp.approx.ftz.f32 %0, %1;" : "=f"(y) : "f"(x)); return y; }
template <class T> DEVI void pin(T& v) { asm volatile("" : "+r"(v)); }
template <class T> DEVI void pinp(T*& v) { asm volatile("" : "+l"(v)); }
DEVI void bar_sync(int id, int n) { asm volatile("bar.sync %0, %1;" :: "r"(id), "r"(n) : "memory"); }
DEVI void bar_arrive(int id, int n) { asm volatile("bar.arrive %0, %1;" :: "r"(id), "r"(n) : "memory"); }
DEVI void cluster_arrive_relaxed() { asm volatile("barrier.cluster.arrive.relaxed.aligned;" ::: "memory"); }
DEVI void cluster_arrive() { asm volatile("barrier.cluster.arrive.release.aligned;" ::: "memory"); }
DEVI void cluster_wait() { asm volatile("barrier.cluster.wait.acquire.aligned;" ::: "memory"); }
DEVI uint32_t mapa(uint32_t a, uint32_t r) { uint32_t o; asm("mapa.shared::cluster.u32 %0, %1, %2;" : "=r"(o) : "r"(a), "r"(r)); return o; }
DEVI uint32_t pack2(float lo, float hi) { uint32_t r; asm("cvt.rn.bf16x2.f32 %0, %1, %2;" : "=r"(r) : "f"(hi), "f"(lo)); return r; }
DEVI float ex2(float x) { float y; asm("ex2.approx.ftz.f32 %0, %1;" : "=f"(y) : "f"(x)); return y; }
DEVI float bf_lo(uint32_t v) { return __uint_as_float(v << 16); }
DEVI float bf_hi(uint32_t v) { return __uint_as_float(v & 0xffff0000u); }
DEVI void ldsm4(uint32_t (&r)[4], uint32_t a) {
  asm volatile("ldmatrix.sync.aligned.m8n8.x4.shared.b16 {%0,%1,%2,%3}, [%4];" : "=r"(r[0]), "=r"(r[1]), "=r"(r[2]), "=r"(r[3]) : "r"(a) : "memory");
}
DEVI void stsm4t(uint32_t a, uint32_t r0, uint32_t r1, uint32_t r2, uint32_t r3) {
  asm volatile("stmatrix.sync.aligned.m8n8.x4.trans.shared.b16 [%0], {%1,%2,%3,%4};" :: "r"(a), "r"(r0), "r"(r1), "r"(r2), "r"(r3) : "memory");
}
DEVI void stsm2t(uint32_t a, uint32_t r0, uint32_t r1) {
  asm volatile("stmatrix.sync.aligned.m8n8.x2.trans.shared.b16 [%0], {%1,%2};" :: "r"(a), "r"(r0), "r"(r1) : "memory");
}
DEVI void mma16(float (&c)[4], uint32_t a0, uint32_t a1, uint32_t a2, uint32_t a3, uint32_t b0, uint32_t b1) {
  asm("mma.sync.aligned.m16n8k16.row.col.f32.bf16.bf16.f32 {%0,%1,%2,%3},{%4,%5,%6,%7},{%8,%9},{%0,%1,%2,%3};"
      : "+f"(c[0]), "+f"(c[1]), "+f"(c[2]), "+f"(c[3]) : "r"(a0), "r"(a1), "r"(a2), "r"(a3), "r"(b0), "r"(b1));
}
DEVI void mma8(float (&c)[4], uint32_t a0, uint32_t a1, uint32_t b0) {
  asm("mma.sync.aligned.m16n8k8.row.col.f32.bf16.bf16.f32 {%0,%1,%2,%3},{%4,%5},{%6},{%0,%1,%2,%3};"
      : "+f"(c[0]), "+f"(c[1]), "+f"(c[2]), "+f"(c[3]) : "r"(a0), "r"(a1), "r"(b0));
}
DEVI void mma16v(float (&c)[4], uint32_t a0, uint32_t a1, uint32_t a2, uint32_t a3, uint32_t b0, uint32_t b1) {
  asm volatile("mma.sync.aligned.m16n8k16.row.col.f32.bf16.bf16.f32 {%0,%1,%2,%3},{%4,%5,%6,%7},{%8,%9},{%0,%1,%2,%3};"
      : "+f"(c[0]), "+f"(c[1]), "+f"(c[2]), "+f"(c[3]) : "r"(a0), "r"(a1), "r"(a2), "r"(a3), "r"(b0), "r"(b1));
}
DEVI void mma8v(float (&c)[4], uint32_t a0, uint32_t a1, uint32_t b0) {
  asm volatile("mma.sync.aligned.m16n8k8.row.col.f32.bf16.bf16.f32 {%0,%1,%2,%3},{%4,%5},{%6},{%0,%1,%2,%3};"
      : "+f"(c[0]), "+f"(c[1]), "+f"(c[2]), "+f"(c[3]) : "r"(a0), "r"(a1), "r"(b0));
}
DEVI float2 mma_rows8(const uint32_t (&a0)[4], const uint32_t (&a1)[4], const uint32_t (&b0)[4], const uint32_t (&b1)[4]) {
  float e0[4] = {0.f, 0.f, 0.f, 0.f}, e1[4] = {0.f, 0.f, 0.f, 0.f}, e2[4] = {0.f, 0.f, 0.f, 0.f}, e3[4] = {0.f, 0.f, 0.f, 0.f};
  mma16v(e0, a0[0], a0[1], a0[2], a0[3], b0[0], b0[1]);
  mma16v(e1, a0[0], a0[1], a0[2], a0[3], b0[2], b0[3]);
  mma16v(e2, a1[0], a1[1], a1[2], a1[3], b1[0], b1[1]);
  mma16v(e3, a1[0], a1[1], a1[2], a1[3], b1[2], b1[3]);
  return make_float2((e0[0] + e1[2]) + (e2[0] + e3[2]), (e0[1] + e1[3]) + (e2[1] + e3[3]));
}
DEVI void wg_fence() { asm volatile("wgmma.fence.sync.aligned;" ::: "memory"); }
DEVI void wg_commit() { asm volatile("wgmma.commit_group.sync.aligned;" ::: "memory"); }
template <int N> DEVI void wg_wait() { asm volatile("wgmma.wait_group.sync.aligned %0;" :: "n"(N) : "memory"); }
template <int N> DEVI void reg_fence(float (&d)[N]) {
#pragma unroll
  for (int i = 0; i < N; i++) asm volatile("" : "+f"(d[i]) :: "memory");
}
DEVI uint64_t desc128(uint32_t addr, uint32_t lbo16) {
  return (uint64_t)((addr >> 4) & 0x3fff) | ((uint64_t)lbo16 << 16) | (64ull << 32) | (1ull << 62);
}
DEVI void tma2d(uint32_t dst, const CUtensorMap* tm, int c0, int c1, uint32_t bar) {
  asm volatile("cp.async.bulk.tensor.2d.shared::cluster.global.mbarrier::complete_tx::bytes [%0], [%1, {%2, %3}], [%4];"
               :: "r"(dst), "l"(tm), "r"(c0), "r"(c1), "r"(bar) : "memory");
}
DEVI void tma2d_mc(uint32_t dst, const CUtensorMap* tm, int c0, int c1, uint32_t bar) {
  asm volatile("cp.async.bulk.tensor.2d.shared::cluster.global.mbarrier::complete_tx::bytes.multicast::cluster [%0], [%1, {%2, %3}], [%4], %5;"
               :: "r"(dst), "l"(tm), "r"(c0), "r"(c1), "r"(bar), "h"((uint16_t)0xffff) : "memory");
}
DEVI void bulk_ld(uint32_t dst, const void* src, uint32_t bytes, uint32_t bar) {
  asm volatile("cp.async.bulk.shared::cluster.global.mbarrier::complete_tx::bytes [%0], [%1], %2, [%3];"
               :: "r"(dst), "l"(src), "r"(bytes), "r"(bar) : "memory");
}
DEVI void bulk_mc(uint32_t dst, const void* src, uint32_t bytes, uint32_t bar) {
  asm volatile("cp.async.bulk.shared::cluster.global.mbarrier::complete_tx::bytes.multicast::cluster [%0], [%1], %2, [%3], %4;"
               :: "r"(dst), "l"(src), "r"(bytes), "r"(bar), "h"((uint16_t)0xffff) : "memory");
}
DEVI void st_async4(uint32_t a, float x, float y, float z, float w, uint32_t bar) {
  asm volatile("st.async.weak.shared::cluster.mbarrier::complete_tx::bytes.v4.f32 [%0], {%1,%2,%3,%4}, [%5];"
               :: "r"(a), "f"(x), "f"(y), "f"(z), "f"(w), "r"(bar) : "memory");
}
DEVI void st_async4u(uint32_t a, uint32_t x, uint32_t y, uint32_t z, uint32_t w, uint32_t bar) {
  asm volatile("st.async.weak.shared::cluster.mbarrier::complete_tx::bytes.v4.b32 [%0], {%1,%2,%3,%4}, [%5];"
               :: "r"(a), "r"(x), "r"(y), "r"(z), "r"(w), "r"(bar) : "memory");
}
DEVI uint32_t ldg1r(const void* p) { uint32_t v; asm volatile("ld.relaxed.gpu.global.u32 %0, [%1];" : "=r"(v) : "l"(p) : "memory"); return v; }
DEVI uint32_t near_copy(uint8_t* blk) {
  uint32_t best[2] = {~0u, ~0u}, v = 0;
#pragma unroll 1
  for (int i = 0; i < 6; i++) {
    const uint8_t* p = blk + XC_R0 + 7936 + (i & 1) * XC_TWIN + (v & 4);
    const uint32_t t0 = clk();
    asm volatile("atom.relaxed.gpu.global.and.b32 %0, [%1], 0;" : "=r"(v) : "l"(p) : "memory");
    uint32_t t1;
    asm volatile("{\n.reg .pred p;\nPROBE_WAIT:\nsetp.eq.u32 p, %1, 0x5a5a5a5a;\n@p nanosleep.u32 32;\nmov.u32 %0, %%clock;\n}" : "=r"(t1) : "r"(v) : "memory");
    const uint32_t d = t1 - t0;
    if (i & 1) best[1] = min(best[1], d); else best[0] = min(best[0], d);
  }
  return best[1] < best[0] ? XC_TWIN : 0;
}
DEVI void tma2d_prefetch(const CUtensorMap* tm, int c0, int c1) {
  asm volatile("cp.async.bulk.prefetch.tensor.2d.L2.global [%0, {%1, %2}];" :: "l"(tm), "r"(c0), "r"(c1) : "memory");
}
DEVI void ldg2r(uint32_t& x, uint32_t& y, const void* p) { asm volatile("ld.relaxed.gpu.global.v2.u32 {%0,%1}, [%2];" : "=r"(x), "=r"(y) : "l"(p) : "memory"); }
DEVI void stg2r(void* p, uint32_t x, uint32_t y) { asm volatile("st.relaxed.gpu.global.v2.u32 [%0], {%1,%2};" :: "l"(p), "r"(x), "r"(y) : "memory"); }
DEVI void stg16r(void* p, uint16_t v) { asm volatile("st.relaxed.gpu.global.u16 [%0], %1;" :: "l"(p), "h"(v) : "memory"); }
DEVI float lds_f(uint32_t a) { float v; asm volatile("ld.shared.f32 %0, [%1];" : "=f"(v) : "r"(a) : "memory"); return v; }
DEVI float2 lds_f2(uint32_t a) { float2 v; asm volatile("ld.shared.v2.f32 {%0,%1}, [%2];" : "=f"(v.x), "=f"(v.y) : "r"(a) : "memory"); return v; }
DEVI float4 lds_f4(uint32_t a) { float4 v; asm volatile("ld.shared.v4.f32 {%0,%1,%2,%3}, [%4];" : "=f"(v.x), "=f"(v.y), "=f"(v.z), "=f"(v.w) : "r"(a) : "memory"); return v; }
DEVI uint2 lds_u2(uint32_t a) { uint2 v; asm volatile("ld.shared.v2.u32 {%0,%1}, [%2];" : "=r"(v.x), "=r"(v.y) : "r"(a) : "memory"); return v; }
DEVI uint4 lds_u4(uint32_t a) { uint4 v; asm volatile("ld.shared.v4.u32 {%0,%1,%2,%3}, [%4];" : "=r"(v.x), "=r"(v.y), "=r"(v.z), "=r"(v.w) : "r"(a) : "memory"); return v; }
DEVI void sts_f2(uint32_t a, float x, float y) { asm volatile("st.shared.v2.f32 [%0], {%1,%2};" :: "r"(a), "f"(x), "f"(y) : "memory"); }
DEVI void sts_f4(uint32_t a, float x, float y, float z, float w) { asm volatile("st.shared.v4.f32 [%0], {%1,%2,%3,%4};" :: "r"(a), "f"(x), "f"(y), "f"(z), "f"(w) : "memory"); }
DEVI void sts_u2(uint32_t a, uint32_t x, uint32_t y) { asm volatile("st.shared.v2.u32 [%0], {%1,%2};" :: "r"(a), "r"(x), "r"(y) : "memory"); }
DEVI void sts_u4(uint32_t a, uint32_t x, uint32_t y, uint32_t z, uint32_t w) { asm volatile("st.shared.v4.u32 [%0], {%1,%2,%3,%4};" :: "r"(a), "r"(x), "r"(y), "r"(z), "r"(w) : "memory"); }
DEVI uint32_t tagf(float v, uint32_t tag) { return (__float_as_uint(v) & ~3u) | tag; }
DEVI float qmax(float v) { v = fmaxf(v, __shfl_xor_sync(0xffffffffu, v, 1)); return fmaxf(v, __shfl_xor_sync(0xffffffffu, v, 2)); }
DEVI float qsum(float v) { v += __shfl_xor_sync(0xffffffffu, v, 1); return v + __shfl_xor_sync(0xffffffffu, v, 2); }

__device__ __forceinline__ void wgmma_n224_kk(float (&d)[112], uint64_t da, uint64_t db, int sc) {
  asm volatile("{\n.reg .pred p;\nsetp.ne.b32 p, %114, 0;\n"
    "wgmma.mma_async.sync.aligned.m64n224k16.f32.bf16.bf16 {%0,%1,%2,%3,%4,%5,%6,%7,%8,%9,%10,%11,%12,%13,%14,%15,%16,%17,%18,%19,%20,%21,%22,%23,%24,%25,%26,%27,%28,%29,%30,%31,%32,%33,%34,%35,%36,%37,%38,%39,%40,%41,%42,%43,%44,%45,%46,%47,%48,%49,%50,%51,%52,%53,%54,%55,%56,%57,%58,%59,%60,%61,%62,%63,%64,%65,%66,%67,%68,%69,%70,%71,%72,%73,%74,%75,%76,%77,%78,%79,%80,%81,%82,%83,%84,%85,%86,%87,%88,%89,%90,%91,%92,%93,%94,%95,%96,%97,%98,%99,%100,%101,%102,%103,%104,%105,%106,%107,%108,%109,%110,%111}, %112, %113, p, 1, 1, 0, 0;\n}"
    : "+f"(d[0]),"+f"(d[1]),"+f"(d[2]),"+f"(d[3]),"+f"(d[4]),"+f"(d[5]),"+f"(d[6]),"+f"(d[7]),"+f"(d[8]),"+f"(d[9]),"+f"(d[10]),"+f"(d[11]),"+f"(d[12]),"+f"(d[13]),"+f"(d[14]),"+f"(d[15]),"+f"(d[16]),"+f"(d[17]),"+f"(d[18]),"+f"(d[19]),"+f"(d[20]),"+f"(d[21]),"+f"(d[22]),"+f"(d[23]),"+f"(d[24]),"+f"(d[25]),"+f"(d[26]),"+f"(d[27]),"+f"(d[28]),"+f"(d[29]),"+f"(d[30]),"+f"(d[31]),"+f"(d[32]),"+f"(d[33]),"+f"(d[34]),"+f"(d[35]),"+f"(d[36]),"+f"(d[37]),"+f"(d[38]),"+f"(d[39]),"+f"(d[40]),"+f"(d[41]),"+f"(d[42]),"+f"(d[43]),"+f"(d[44]),"+f"(d[45]),"+f"(d[46]),"+f"(d[47]),"+f"(d[48]),"+f"(d[49]),"+f"(d[50]),"+f"(d[51]),"+f"(d[52]),"+f"(d[53]),"+f"(d[54]),"+f"(d[55]),"+f"(d[56]),"+f"(d[57]),"+f"(d[58]),"+f"(d[59]),"+f"(d[60]),"+f"(d[61]),"+f"(d[62]),"+f"(d[63]),"+f"(d[64]),"+f"(d[65]),"+f"(d[66]),"+f"(d[67]),"+f"(d[68]),"+f"(d[69]),"+f"(d[70]),"+f"(d[71]),"+f"(d[72]),"+f"(d[73]),"+f"(d[74]),"+f"(d[75]),"+f"(d[76]),"+f"(d[77]),"+f"(d[78]),"+f"(d[79]),"+f"(d[80]),"+f"(d[81]),"+f"(d[82]),"+f"(d[83]),"+f"(d[84]),"+f"(d[85]),"+f"(d[86]),"+f"(d[87]),"+f"(d[88]),"+f"(d[89]),"+f"(d[90]),"+f"(d[91]),"+f"(d[92]),"+f"(d[93]),"+f"(d[94]),"+f"(d[95]),"+f"(d[96]),"+f"(d[97]),"+f"(d[98]),"+f"(d[99]),"+f"(d[100]),"+f"(d[101]),"+f"(d[102]),"+f"(d[103]),"+f"(d[104]),"+f"(d[105]),"+f"(d[106]),"+f"(d[107]),"+f"(d[108]),"+f"(d[109]),"+f"(d[110]),"+f"(d[111])
    : "l"(da),"l"(db),"r"(sc));
}
__device__ __forceinline__ void wgmma_n224_mk(float (&d)[112], uint64_t da, uint64_t db, int sc) {
  asm volatile("{\n.reg .pred p;\nsetp.ne.b32 p, %114, 0;\n"
    "wgmma.mma_async.sync.aligned.m64n224k16.f32.bf16.bf16 {%0,%1,%2,%3,%4,%5,%6,%7,%8,%9,%10,%11,%12,%13,%14,%15,%16,%17,%18,%19,%20,%21,%22,%23,%24,%25,%26,%27,%28,%29,%30,%31,%32,%33,%34,%35,%36,%37,%38,%39,%40,%41,%42,%43,%44,%45,%46,%47,%48,%49,%50,%51,%52,%53,%54,%55,%56,%57,%58,%59,%60,%61,%62,%63,%64,%65,%66,%67,%68,%69,%70,%71,%72,%73,%74,%75,%76,%77,%78,%79,%80,%81,%82,%83,%84,%85,%86,%87,%88,%89,%90,%91,%92,%93,%94,%95,%96,%97,%98,%99,%100,%101,%102,%103,%104,%105,%106,%107,%108,%109,%110,%111}, %112, %113, p, 1, 1, 1, 0;\n}"
    : "+f"(d[0]),"+f"(d[1]),"+f"(d[2]),"+f"(d[3]),"+f"(d[4]),"+f"(d[5]),"+f"(d[6]),"+f"(d[7]),"+f"(d[8]),"+f"(d[9]),"+f"(d[10]),"+f"(d[11]),"+f"(d[12]),"+f"(d[13]),"+f"(d[14]),"+f"(d[15]),"+f"(d[16]),"+f"(d[17]),"+f"(d[18]),"+f"(d[19]),"+f"(d[20]),"+f"(d[21]),"+f"(d[22]),"+f"(d[23]),"+f"(d[24]),"+f"(d[25]),"+f"(d[26]),"+f"(d[27]),"+f"(d[28]),"+f"(d[29]),"+f"(d[30]),"+f"(d[31]),"+f"(d[32]),"+f"(d[33]),"+f"(d[34]),"+f"(d[35]),"+f"(d[36]),"+f"(d[37]),"+f"(d[38]),"+f"(d[39]),"+f"(d[40]),"+f"(d[41]),"+f"(d[42]),"+f"(d[43]),"+f"(d[44]),"+f"(d[45]),"+f"(d[46]),"+f"(d[47]),"+f"(d[48]),"+f"(d[49]),"+f"(d[50]),"+f"(d[51]),"+f"(d[52]),"+f"(d[53]),"+f"(d[54]),"+f"(d[55]),"+f"(d[56]),"+f"(d[57]),"+f"(d[58]),"+f"(d[59]),"+f"(d[60]),"+f"(d[61]),"+f"(d[62]),"+f"(d[63]),"+f"(d[64]),"+f"(d[65]),"+f"(d[66]),"+f"(d[67]),"+f"(d[68]),"+f"(d[69]),"+f"(d[70]),"+f"(d[71]),"+f"(d[72]),"+f"(d[73]),"+f"(d[74]),"+f"(d[75]),"+f"(d[76]),"+f"(d[77]),"+f"(d[78]),"+f"(d[79]),"+f"(d[80]),"+f"(d[81]),"+f"(d[82]),"+f"(d[83]),"+f"(d[84]),"+f"(d[85]),"+f"(d[86]),"+f"(d[87]),"+f"(d[88]),"+f"(d[89]),"+f"(d[90]),"+f"(d[91]),"+f"(d[92]),"+f"(d[93]),"+f"(d[94]),"+f"(d[95]),"+f"(d[96]),"+f"(d[97]),"+f"(d[98]),"+f"(d[99]),"+f"(d[100]),"+f"(d[101]),"+f"(d[102]),"+f"(d[103]),"+f"(d[104]),"+f"(d[105]),"+f"(d[106]),"+f"(d[107]),"+f"(d[108]),"+f"(d[109]),"+f"(d[110]),"+f"(d[111])
    : "l"(da),"l"(db),"r"(sc));
}
__device__ __forceinline__ void wgmma_n32_rs(float (&d)[16], const uint32_t (&a)[4], uint64_t db, int sc) {
  asm volatile("{\n.reg .pred p;\nsetp.ne.b32 p, %21, 0;\n"
    "wgmma.mma_async.sync.aligned.m64n32k16.f32.bf16.bf16 {%0,%1,%2,%3,%4,%5,%6,%7,%8,%9,%10,%11,%12,%13,%14,%15}, {%16,%17,%18,%19}, %20, p, 1, 1, 0;\n}"
    : "+f"(d[0]),"+f"(d[1]),"+f"(d[2]),"+f"(d[3]),"+f"(d[4]),"+f"(d[5]),"+f"(d[6]),"+f"(d[7]),"+f"(d[8]),"+f"(d[9]),"+f"(d[10]),"+f"(d[11]),"+f"(d[12]),"+f"(d[13]),"+f"(d[14]),"+f"(d[15])
    : "r"(a[0]),"r"(a[1]),"r"(a[2]),"r"(a[3]),"l"(db),"r"(sc));
}
__device__ __forceinline__ void wgmma_n8_rs(float (&d)[4], const uint32_t (&a)[4], uint64_t db, int sc) {
  asm volatile("{\n.reg .pred p;\nsetp.ne.b32 p, %9, 0;\n"
    "wgmma.mma_async.sync.aligned.m64n8k16.f32.bf16.bf16 {%0,%1,%2,%3}, {%4,%5,%6,%7}, %8, p, 1, 1, 0;\n}"
    : "+f"(d[0]),"+f"(d[1]),"+f"(d[2]),"+f"(d[3])
    : "r"(a[0]),"r"(a[1]),"r"(a[2]),"r"(a[3]),"l"(db),"r"(sc));
}
__device__ __forceinline__ void wgmma_n256_kn(float (&d)[128], uint64_t da, uint64_t db, int sc) {
  asm volatile("{\n.reg .pred p;\nsetp.ne.b32 p, %130, 0;\n"
    "wgmma.mma_async.sync.aligned.m64n256k16.f32.bf16.bf16 {%0,%1,%2,%3,%4,%5,%6,%7,%8,%9,%10,%11,%12,%13,%14,%15,%16,%17,%18,%19,%20,%21,%22,%23,%24,%25,%26,%27,%28,%29,%30,%31,%32,%33,%34,%35,%36,%37,%38,%39,%40,%41,%42,%43,%44,%45,%46,%47,%48,%49,%50,%51,%52,%53,%54,%55,%56,%57,%58,%59,%60,%61,%62,%63,%64,%65,%66,%67,%68,%69,%70,%71,%72,%73,%74,%75,%76,%77,%78,%79,%80,%81,%82,%83,%84,%85,%86,%87,%88,%89,%90,%91,%92,%93,%94,%95,%96,%97,%98,%99,%100,%101,%102,%103,%104,%105,%106,%107,%108,%109,%110,%111,%112,%113,%114,%115,%116,%117,%118,%119,%120,%121,%122,%123,%124,%125,%126,%127}, %128, %129, p, 1, 1, 0, 1;\n}"
    : "+f"(d[0]),"+f"(d[1]),"+f"(d[2]),"+f"(d[3]),"+f"(d[4]),"+f"(d[5]),"+f"(d[6]),"+f"(d[7]),"+f"(d[8]),"+f"(d[9]),"+f"(d[10]),"+f"(d[11]),"+f"(d[12]),"+f"(d[13]),"+f"(d[14]),"+f"(d[15]),"+f"(d[16]),"+f"(d[17]),"+f"(d[18]),"+f"(d[19]),"+f"(d[20]),"+f"(d[21]),"+f"(d[22]),"+f"(d[23]),"+f"(d[24]),"+f"(d[25]),"+f"(d[26]),"+f"(d[27]),"+f"(d[28]),"+f"(d[29]),"+f"(d[30]),"+f"(d[31]),"+f"(d[32]),"+f"(d[33]),"+f"(d[34]),"+f"(d[35]),"+f"(d[36]),"+f"(d[37]),"+f"(d[38]),"+f"(d[39]),"+f"(d[40]),"+f"(d[41]),"+f"(d[42]),"+f"(d[43]),"+f"(d[44]),"+f"(d[45]),"+f"(d[46]),"+f"(d[47]),"+f"(d[48]),"+f"(d[49]),"+f"(d[50]),"+f"(d[51]),"+f"(d[52]),"+f"(d[53]),"+f"(d[54]),"+f"(d[55]),"+f"(d[56]),"+f"(d[57]),"+f"(d[58]),"+f"(d[59]),"+f"(d[60]),"+f"(d[61]),"+f"(d[62]),"+f"(d[63]),"+f"(d[64]),"+f"(d[65]),"+f"(d[66]),"+f"(d[67]),"+f"(d[68]),"+f"(d[69]),"+f"(d[70]),"+f"(d[71]),"+f"(d[72]),"+f"(d[73]),"+f"(d[74]),"+f"(d[75]),"+f"(d[76]),"+f"(d[77]),"+f"(d[78]),"+f"(d[79]),"+f"(d[80]),"+f"(d[81]),"+f"(d[82]),"+f"(d[83]),"+f"(d[84]),"+f"(d[85]),"+f"(d[86]),"+f"(d[87]),"+f"(d[88]),"+f"(d[89]),"+f"(d[90]),"+f"(d[91]),"+f"(d[92]),"+f"(d[93]),"+f"(d[94]),"+f"(d[95]),"+f"(d[96]),"+f"(d[97]),"+f"(d[98]),"+f"(d[99]),"+f"(d[100]),"+f"(d[101]),"+f"(d[102]),"+f"(d[103]),"+f"(d[104]),"+f"(d[105]),"+f"(d[106]),"+f"(d[107]),"+f"(d[108]),"+f"(d[109]),"+f"(d[110]),"+f"(d[111]),"+f"(d[112]),"+f"(d[113]),"+f"(d[114]),"+f"(d[115]),"+f"(d[116]),"+f"(d[117]),"+f"(d[118]),"+f"(d[119]),"+f"(d[120]),"+f"(d[121]),"+f"(d[122]),"+f"(d[123]),"+f"(d[124]),"+f"(d[125]),"+f"(d[126]),"+f"(d[127])
    : "l"(da),"l"(db),"r"(sc));
}
__device__ __forceinline__ void wgmma_n192_kn(float (&d)[96], uint64_t da, uint64_t db, int sc) {
  asm volatile("{\n.reg .pred p;\nsetp.ne.b32 p, %98, 0;\n"
    "wgmma.mma_async.sync.aligned.m64n192k16.f32.bf16.bf16 {%0,%1,%2,%3,%4,%5,%6,%7,%8,%9,%10,%11,%12,%13,%14,%15,%16,%17,%18,%19,%20,%21,%22,%23,%24,%25,%26,%27,%28,%29,%30,%31,%32,%33,%34,%35,%36,%37,%38,%39,%40,%41,%42,%43,%44,%45,%46,%47,%48,%49,%50,%51,%52,%53,%54,%55,%56,%57,%58,%59,%60,%61,%62,%63,%64,%65,%66,%67,%68,%69,%70,%71,%72,%73,%74,%75,%76,%77,%78,%79,%80,%81,%82,%83,%84,%85,%86,%87,%88,%89,%90,%91,%92,%93,%94,%95}, %96, %97, p, 1, 1, 0, 1;\n}"
    : "+f"(d[0]),"+f"(d[1]),"+f"(d[2]),"+f"(d[3]),"+f"(d[4]),"+f"(d[5]),"+f"(d[6]),"+f"(d[7]),"+f"(d[8]),"+f"(d[9]),"+f"(d[10]),"+f"(d[11]),"+f"(d[12]),"+f"(d[13]),"+f"(d[14]),"+f"(d[15]),"+f"(d[16]),"+f"(d[17]),"+f"(d[18]),"+f"(d[19]),"+f"(d[20]),"+f"(d[21]),"+f"(d[22]),"+f"(d[23]),"+f"(d[24]),"+f"(d[25]),"+f"(d[26]),"+f"(d[27]),"+f"(d[28]),"+f"(d[29]),"+f"(d[30]),"+f"(d[31]),"+f"(d[32]),"+f"(d[33]),"+f"(d[34]),"+f"(d[35]),"+f"(d[36]),"+f"(d[37]),"+f"(d[38]),"+f"(d[39]),"+f"(d[40]),"+f"(d[41]),"+f"(d[42]),"+f"(d[43]),"+f"(d[44]),"+f"(d[45]),"+f"(d[46]),"+f"(d[47]),"+f"(d[48]),"+f"(d[49]),"+f"(d[50]),"+f"(d[51]),"+f"(d[52]),"+f"(d[53]),"+f"(d[54]),"+f"(d[55]),"+f"(d[56]),"+f"(d[57]),"+f"(d[58]),"+f"(d[59]),"+f"(d[60]),"+f"(d[61]),"+f"(d[62]),"+f"(d[63]),"+f"(d[64]),"+f"(d[65]),"+f"(d[66]),"+f"(d[67]),"+f"(d[68]),"+f"(d[69]),"+f"(d[70]),"+f"(d[71]),"+f"(d[72]),"+f"(d[73]),"+f"(d[74]),"+f"(d[75]),"+f"(d[76]),"+f"(d[77]),"+f"(d[78]),"+f"(d[79]),"+f"(d[80]),"+f"(d[81]),"+f"(d[82]),"+f"(d[83]),"+f"(d[84]),"+f"(d[85]),"+f"(d[86]),"+f"(d[87]),"+f"(d[88]),"+f"(d[89]),"+f"(d[90]),"+f"(d[91]),"+f"(d[92]),"+f"(d[93]),"+f"(d[94]),"+f"(d[95])
    : "l"(da),"l"(db),"r"(sc));
}

constexpr uint32_t XB = 28672;
constexpr uint32_t O_WQ = 5 * XB;
constexpr uint32_t O_WO = O_WQ + 32768;
constexpr uint32_t O_MIMG = O_WO + 32768;
constexpr uint32_t O_BAR = O_MIMG + 2 * 7168;
constexpr uint32_t O_TS = O_BAR + 384;
constexpr uint32_t T_SMEM = O_TS + 4096 + 128 + 1024;
constexpr uint32_t O_Z = 4 * XB;
constexpr uint32_t O_RS = O_Z + 2 * 5120;
constexpr uint32_t O_ORS = O_RS + 2 * 2048;
constexpr uint32_t O_P = O_ORS + 3 * 4096;
constexpr uint32_t O_SX = O_P + 2 * 2560;
constexpr uint32_t O_MJ = O_SX + 1536;
constexpr uint32_t O_ST = O_MJ + 2048;
constexpr uint32_t O_PC = O_ST + 2 * 5632;
constexpr uint32_t O_YB = O_PC + 128;
constexpr uint32_t O_GX = O_YB + 2 * 5120;
enum { B_X = 0, B_M = 4, B_RS = 6, B_O = 8, B_ZX = 10, B_P = 12, B_PF = 14, B_PE = 18, B_WQ = 22, B_WO = 23, B_T = 24, B_MJ = 26, B_OL = 28, B_G = 29, B_N = 37 };
constexpr uint32_t O_C3 = O_BAR + 8 * B_N, O_NEAR = O_C3 + 4, O_DONE = O_NEAR + 8;
enum { N_ZM = 1, N_YM = 2, N_W1 = 3, N_INIT = 4, N_ZX = 5, N_REDO = 6, N_YX = 7, N_SS = 8, N_ST = 9 };

DEVI void gemm_m(const uint32_t (&w)[28][4], uint32_t img_lane, float (&c)[4]) {
  float acc[4][4];
#pragma unroll
  for (int i = 0; i < 4; i++) { acc[i][0] = acc[i][1] = acc[i][2] = acc[i][3] = 0.f; }
  uint32_t r[14][4];
#pragma unroll
  for (int u = 0; u < 14; u++) ldsm4(r[u], img_lane + u * 512);
#pragma unroll
  for (int u = 0; u < 14; u++) {
    mma16v(acc[(2 * u) & 3], w[2 * u][0], w[2 * u][1], w[2 * u][2], w[2 * u][3], r[u][0], r[u][1]);
    mma16v(acc[(2 * u + 1) & 3], w[2 * u + 1][0], w[2 * u + 1][1], w[2 * u + 1][2], w[2 * u + 1][3], r[u][2], r[u][3]);
  }
#pragma unroll
  for (int i = 0; i < 4; i++) c[i] = (acc[0][i] + acc[1][i]) + (acc[2][i] + acc[3][i]);
}

DEVI void gemm_x_issue(const uint32_t (&w)[28][4], uint32_t xbuf, float (&d)[16]) {
  const uint64_t b0 = desc128(xbuf, 1);
  wg_fence();
#pragma unroll
  for (int k = 0; k < 28; k++) wgmma_n32_rs(d, w[k], b0 + (uint64_t)((k >> 2) * 256 + (k & 3) * 2), k != 0);
  wg_commit();
}
DEVI void gemm_x(const uint32_t (&w)[28][4], uint32_t xbuf, float (&d)[16]) {
  gemm_x_issue(w, xbuf, d);
  wg_wait<0>();
  reg_fence(d);
}

template <int WHICH>
DEVI void build_weights(uint32_t (&w)[28][4], uint32_t sb, int& dead, int lane) {
  const uint32_t bar = sb + O_BAR;
  mbar_wait(bar + 8 * (WHICH ? B_WO : B_WQ), 0, dead);
  if ((threadIdx.x & 127) == 0) PTS(4 + WHICH);
#pragma unroll
  for (int half = 0; half < 2; half++) {
    float d[112];
#pragma unroll 1
    for (int fk = 0; fk < 4; fk++) {
      const int c = 2 * (4 * half + fk) + WHICH, st = c & 3;
      mbar_wait(bar + 8 * (B_PF + st), (c >> 2) & 1, dead);
      if ((threadIdx.x & 127) == 0) PTS(8 + c);
      const uint64_t db = desc128(sb + (st + 1) * XB, 1);
      wg_fence();
#pragma unroll
      for (int kk = 0; kk < 4; kk++) {
        if (WHICH == 0) wgmma_n224_kk(d, desc128(sb + O_WQ + fk * 8192 + kk * 32, 1), db + kk * 2, (fk | kk) != 0);
        else            wgmma_n224_mk(d, desc128(sb + O_WO + (fk * 4 + kk) * 2048, 1), db + kk * 2, (fk | kk) != 0);
      }
      wg_commit();
      wg_wait<0>();
      if (lane == 0) mbar_arrive(bar + 8 * (B_PE + st));
    }
    reg_fence(d);
#pragma unroll
    for (int kk = 0; kk < 14; kk++) {
      w[14 * half + kk][0] = pack2(d[8 * kk + 0], d[8 * kk + 1]);
      w[14 * half + kk][1] = pack2(d[8 * kk + 2], d[8 * kk + 3]);
      w[14 * half + kk][2] = pack2(d[8 * kk + 4], d[8 * kk + 5]);
      w[14 * half + kk][3] = pack2(d[8 * kk + 6], d[8 * kk + 7]);
    }
  }
}

DEVI void load7(uint32_t (&v)[14], const float* p, int stride) {
#pragma unroll
  for (int k = 0; k < 7; k++) ldg2r(v[2 * k], v[2 * k + 1], p + k * stride);
}
DEVI bool stale7(const uint32_t (&v)[14], uint32_t tag) {
  const uint32_t o = ((v[0] | v[1] | v[2]) | (v[3] | v[4] | v[5]) | (v[6] | v[7] | v[8])) | ((v[9] | v[10] | v[11]) | (v[12] | v[13]));
  const uint32_t a = ((v[0] & v[1] & v[2]) & (v[3] & v[4] & v[5]) & (v[6] & v[7] & v[8])) & ((v[9] & v[10] & v[11]) & (v[12] & v[13]));
  return (((o ^ tag) | (a ^ tag)) & 3u) != 0;
}
DEVI float2 add7(const uint32_t (&v)[14]) {
  float2 r;
  r.x = ((__uint_as_float(v[0]) + __uint_as_float(v[2])) + (__uint_as_float(v[4]) + __uint_as_float(v[6]))) +
        ((__uint_as_float(v[8]) + __uint_as_float(v[10])) + __uint_as_float(v[12]));
  r.y = ((__uint_as_float(v[1]) + __uint_as_float(v[3])) + (__uint_as_float(v[5]) + __uint_as_float(v[7]))) +
        ((__uint_as_float(v[9]) + __uint_as_float(v[11])) + __uint_as_float(v[13]));
  return r;
}

__global__ void __launch_bounds__(384, 1)
rmt_kernel(const __grid_constant__ CUtensorMap tmWq, const __grid_constant__ CUtensorMap tmWk,
           const __grid_constant__ CUtensorMap tmWv, const __grid_constant__ CUtensorMap tmWo,
           const __grid_constant__ CUtensorMap tmX, const __nv_bfloat16* __restrict__ x,
           const __nv_bfloat16* __restrict__ mem0, const __nv_bfloat16* __restrict__ gate_w, __nv_bfloat16* __restrict__ out) {
  extern __shared__ uint8_t smem_raw[];
  const uint32_t sb = (smem_u32(smem_raw) + 1023) & ~1023u;
  const uint32_t bar = sb + O_BAR;
  int lim = SPIN_LIMIT;
  int tid;
  uint32_t h, j;
  asm volatile("mov.u32 %0, %%tid.x;" : "=r"(tid));
  asm volatile("mov.u32 %0, %%cluster_ctarank;" : "=r"(h));
  asm volatile("mov.u32 %0, %%clusterid.x;" : "=r"(j));
  tid = __shfl_sync(0xffffffffu, tid, tid & 31);
  const int lane = tid & 31, warp = __shfl_sync(0xffffffffu, tid >> 5, 0);
  if (warp == 0) PTS(0);

  if (warp == 8) {
    if (elect()) {
#pragma unroll
      for (int i = 0; i < 4; i++) mbar_init(bar + 8 * (B_PF + i), 1);
      mbar_init(bar + 8 * B_WQ, 1);
      mbar_init(bar + 8 * B_WO, 1);
      asm volatile("fence.mbarrier_init.release.cluster;" ::: "memory");
      PTS(1);
      mbar_expect(bar + 8 * B_PF, XB);
      tma2d(sb + XB, &tmWk, h * DH, 0, bar + 8 * B_PF);
      PTS(27);
      mbar_expect(bar + 8 * B_WQ, 32768);
#pragma unroll
      for (int k = 0; k < 4; k++) tma2d(sb + O_WQ + k * 8192, &tmWq, h * DH + k * 64, j * 64, bar + 8 * B_WQ);
      PTS(28);
      mbar_expect(bar + 8 * B_WO, 32768);
      tma2d(sb + O_WO, &tmWo, j * 64, h * DH, bar + 8 * B_WO);
      PTS(29);
#pragma unroll
      for (int c = 1; c < 4; c++) {
        mbar_expect(bar + 8 * (B_PF + c), XB);
        tma2d(sb + (c + 1) * XB, (c & 1) ? &tmWv : &tmWk, h * DH + (c >> 1) * 64, 0, bar + 8 * (B_PF + c));
      }
      PTS(30);
      int c = 4 + j;
      tma2d_prefetch((c & 1) ? &tmWv : &tmWk, h * DH + ((c >> 1) & 3) * 64, (c >> 3) * 224);
      c += 7;
      if (c < 16) tma2d_prefetch((c & 1) ? &tmWv : &tmWk, h * DH + ((c >> 1) & 3) * 64, 224);
    }
  } else if (warp == 9) {
    if (elect()) {
#pragma unroll
      for (int i = 0; i < B_N; i++)
        if (i < B_PF || (i >= B_PE && i < B_WQ) || i >= B_T) mbar_init(bar + 8 * i, i >= B_MJ ? 1 : i >= B_T ? 3 : i >= B_PE ? 4 : i >= B_P ? 2 : i >= B_ZX ? 4 : 1);
      sts32v(sb + O_C3, 0);
      sts32v(sb + O_DONE, 0);
      mbar_expect(bar + 8 * B_X, XB);
      mbar_expect(bar + 8 * B_OL, 4096);
      mbar_expect(bar + 8 * (B_MJ + 1), 1024);
#pragma unroll
      for (int i = 0; i < 2; i++) { mbar_expect(bar + 8 * (B_RS + i), 2048); mbar_expect(bar + 8 * (B_O + i), 4096); }
      asm volatile("fence.mbarrier_init.release.cluster;" ::: "memory");
    }
  }
  asm volatile("griddepcontrol.launch_dependents;");
  if (warp == 8) PTS(2);
  __syncthreads();
  cluster_arrive_relaxed();
  if (warp == 0) PTS(3);

  if (warp < 4) {
    asm volatile("setmaxnreg.inc.sync.aligned.u32 216;");
    uint32_t w[28][4];
    build_weights<0>(w, sb, lim, lane);
    if (warp == 0) PTS(6);
    cluster_wait();
    cluster_arrive_relaxed();
    uint32_t zst = sb + O_Z + ((2 * warp + ((lane >> 3) & 1)) * 40 + 8 * (lane >> 4) + (lane & 7)) * 16;
    const int mt = warp & 1, n0 = (warp >> 1) * 3;
    const int ch = lane >> 3, chp = (ch >> 1) | ((ch & 1) << 1);
    uint32_t zld = sb + O_Z + ((warp == 2 ? chp : ch) * 40 + (lane & 7)) * 16 + (warp == 2 ? 0 : n0 * 128);
    const int xrow = 16 * mt + (lane & 15);
    uint32_t xq = sb + j * 4096 + xrow * 128 + (((lane >> 4) ^ (xrow & 7)) << 4);
    uint32_t mimg = sb + O_MIMG + lane * 16, sta = sb + O_ST + (warp == 3 ? 4096 : mt * 2048) + lane * 16;
    uint8_t* p_smm = xch(h) + (XC_R0 + 2 * XC_REG + j * 256 + lane * 8);
    pin(zst); pin(zld); pin(xq); pin(mimg); pin(sta); pinp(p_smm);
    {
      float d[16];
      mbar_wait(bar + 8 * B_X, 0, lim);
      gemm_x(w, sb, d);
      if (warp == 0) PTS(7);
      cluster_wait();
      if (warp == 0) PTS(24);
      stsm4t(zst + 8 * 16, pack2(d[0], d[1]), pack2(d[2], d[3]), pack2(d[4], d[5]), pack2(d[6], d[7]));
      stsm4t(zst + 24 * 16, pack2(d[8], d[9]), pack2(d[10], d[11]), pack2(d[12], d[13]), pack2(d[14], d[15]));
      __syncwarp();
      if (lane == 0) mbar_arrive(bar + 8 * B_ZX);
    }
    const uint32_t o_a = mapa(sb + O_ORS + h * 256 + warp * 64 + (lane & 3) * 16, lane >> 2);
    const uint32_t o_b = mapa(bar + 8 * B_O, lane >> 2);
    const uint32_t o_st = mapa(sb, 8) - mapa(sb, 0);
    uint32_t oh[8];
    auto token_pv = [&](int sp) {
      const uint32_t p16 = mimg + (O_P - O_MIMG) + (sp & 1) * 2560, p8 = p16 + 1024 - lane * 8, yb = sb + O_YB + (sp & 1) * 5120 + tid * 16;
      const uint4 y0 = lds_u4(yb), y1 = lds_u4(yb + 2048);
      const uint2 ymp = lds_u2(yb + 4096 - tid * 8);
      mbar_wait(bar + 8 * (B_P + (sp & 1)), (sp >> 1) & 1, lim);
      const uint2 m0 = lds_u2(p8), m1 = lds_u2(p8 + 1280);
      const uint4 p0 = lds_u4(p16), p1 = lds_u4(p16 + 512), p2 = lds_u4(p16 + 1280), p3 = lds_u4(p16 + 1280 + 512);
      float o0[4] = {0.f, 0.f, 0.f, 0.f}, o1[4] = {0.f, 0.f, 0.f, 0.f}, o2[4] = {0.f, 0.f, 0.f, 0.f}, o3[4] = {0.f, 0.f, 0.f, 0.f};
      mma8(o0, m0.x, m0.y, ymp.x);
      mma8(o1, m0.x, m0.y, ymp.y);
      mma8(o2, m1.x, m1.y, ymp.x);
      mma8(o3, m1.x, m1.y, ymp.y);
      mma16(o0, p0.x, p0.y, p0.z, p0.w, y0.x, y0.y);
      mma16(o1, p0.x, p0.y, p0.z, p0.w, y0.z, y0.w);
      mma16(o2, p2.x, p2.y, p2.z, p2.w, y0.x, y0.y);
      mma16(o3, p2.x, p2.y, p2.z, p2.w, y0.z, y0.w);
      mma16(o0, p1.x, p1.y, p1.z, p1.w, y1.x, y1.y);
      mma16(o1, p1.x, p1.y, p1.z, p1.w, y1.z, y1.w);
      mma16(o2, p3.x, p3.y, p3.z, p3.w, y1.x, y1.y);
      mma16(o3, p3.x, p3.y, p3.z, p3.w, y1.z, y1.w);
      oh[0] = pack2(o0[0], o0[1]); oh[1] = pack2(o1[0], o1[1]); oh[2] = pack2(o0[2], o0[3]); oh[3] = pack2(o1[2], o1[3]);
      oh[4] = pack2(o2[0], o2[1]); oh[5] = pack2(o3[0], o3[1]); oh[6] = pack2(o2[2], o2[3]); oh[7] = pack2(o3[2], o3[3]);
    };
    auto token_send = [&](int sp) {
      const bool last = sp == NSEG - 1;
      const uint32_t oa = o_a + (last ? 2 : sp & 1) * 4096, ob = o_b + (last ? B_OL - B_O : sp & 1) * 8;
      st_async4u(oa, oh[0], oh[1], oh[2], oh[3], ob);
      st_async4u(oa + o_st, oh[4], oh[5], oh[6], oh[7], ob + o_st);
    };
#pragma unroll 1
    for (int s = 0; s < NSEG; s++) {
      const bool rec = s < NSEG - 1;
      uint32_t img = mimg + (s & 1) * 7168, zs = zst + (s & 1) * 5120, zl = zld + (s & 1) * 5120;
      uint32_t tag = ((s >> 1) + 1) & 3;
      uint8_t* smm = p_smm + (s & 1) * 1792;
      pin(img); pin(zs); pin(zl); pin(tag); pinp(smm);
      uint32_t a[4][4];
      if (warp == 2 && rec) {
        const uint32_t mj = s ? mimg + (O_MJ - O_MIMG) + (s & 1) * 1024 : img + j * 1024;
        if (s) mbar_wait(bar + 8 * (B_MJ + (s & 1)), ((s - 1) >> 1) & 1, lim);
        ldsm4(a[0], mj);
        ldsm4(a[1], mj + 512);
      }
      if (s) mbar_wait(bar + 8 * (B_M + (s & 1)), ((s - 1) >> 1) & 1, lim);
      if (warp == 2) TS(0);
      float c[4];
      do {
        gemm_m(w, img, c);
        stsm2t(zs, pack2(c[0], c[1]), pack2(c[2], c[3]));
        if (warp == 1) TS(24);
      } while (__builtin_expect(bar_or(N_ZM, 160, false), 0));
      uint32_t b0[4], b1[4];
      if (warp == 2) {
        TS(1);
        ldsm4(b0, zl);
        ldsm4(b1, zl + 4 * 640);
        const float2 e = mma_rows8(a[0], a[1], b0, b1);
        if (rec) { stg2r(smm, tagf(e.x, tag), tagf(e.y, tag)); stg2r(smm + XC_TWIN, tagf(e.x, tag), tagf(e.y, tag)); }
        bar_arrive(N_YM, 160);
        TS(2);
      }
      bar_sync(N_SS, 128);
      if (s >= 2) token_send(s - 2);
      if (warp != 2) {
        const uint32_t st = sta + (s & 1) * 5632, aq = xq + (s & 3) * XB;
        uint32_t b2[4], b3[4], b4[4], b5[4];
        ldsm4(a[0], aq); ldsm4(b0, zl); ldsm4(b2, zl + 128); ldsm4(b4, zl + 256); ldsm4(a[1], aq ^ 32);
        ldsm4(a[2], aq ^ 64); ldsm4(b1, zl + 2560); ldsm4(b3, zl + 2560 + 128); ldsm4(b5, zl + 2560 + 256); ldsm4(a[3], aq ^ 96);
        float e0[4] = {0.f, 0.f, 0.f, 0.f}, e1[4] = {0.f, 0.f, 0.f, 0.f}, e2[4] = {0.f, 0.f, 0.f, 0.f};
        mma16(e0, a[0][0], a[0][1], a[0][2], a[0][3], b0[0], b0[1]);
        mma16(e1, a[0][0], a[0][1], a[0][2], a[0][3], b2[0], b2[1]);
        mma16(e2, a[0][0], a[0][1], a[0][2], a[0][3], b4[0], b4[1]);
        mma16(e0, a[1][0], a[1][1], a[1][2], a[1][3], b0[2], b0[3]);
        mma16(e1, a[1][0], a[1][1], a[1][2], a[1][3], b2[2], b2[3]);
        mma16(e2, a[1][0], a[1][1], a[1][2], a[1][3], b4[2], b4[3]);
        mma16(e0, a[2][0], a[2][1], a[2][2], a[2][3], b1[0], b1[1]);
        mma16(e1, a[2][0], a[2][1], a[2][2], a[2][3], b3[0], b3[1]);
        mma16(e2, a[2][0], a[2][1], a[2][2], a[2][3], b5[0], b5[1]);
        mma16(e0, a[3][0], a[3][1], a[3][2], a[3][3], b1[2], b1[3]);
        mma16(e1, a[3][0], a[3][1], a[3][2], a[3][3], b3[2], b3[3]);
        mma16(e2, a[3][0], a[3][1], a[3][2], a[3][3], b5[2], b5[3]);
        sts_f4(st, e0[0], e0[1], e0[2], 1.f);
        sts_f4(st + 512, e0[3], e1[0], e1[1], 1.f);
        sts_f4(st + 1024, e1[2], e1[3], n0 ? 0.f : e2[0], 1.f);
        if (n0 == 0) sts_f4(st + 1536, e2[1], e2[2], e2[3], 1.f);
        if (warp == 1) TS(19);
        asm volatile("fence.proxy.async.shared::cta;" ::: "memory");
        __syncwarp();
        if (lane == 0) mbar_arrive(bar + 8 * (B_T + (s & 1)));
      }
      if (s) token_pv(s - 1);
      if (warp == 1) TS(5);
      if (rec) {
        float d[16];
        if (warp == 1) TS(16);
        mbar_wait(bar + 8 * (B_X + ((s + 1) & 3)), ((s + 1) >> 2) & 1, lim);
        bar_sync(N_ZX, 256);
        if (warp == 1) TS(17);
        gemm_x_issue(w, sb + ((s + 1) & 3) * XB, d);
        bar_arrive(N_YX, 256);
        wg_wait<0>();
        reg_fence(d);
        if (warp == 1) TS(18);
        const uint32_t zn = zst + ((s + 1) & 1) * 5120;
        stsm4t(zn + 8 * 16, pack2(d[0], d[1]), pack2(d[2], d[3]), pack2(d[4], d[5]), pack2(d[6], d[7]));
        stsm4t(zn + 24 * 16, pack2(d[8], d[9]), pack2(d[10], d[11]), pack2(d[12], d[13]), pack2(d[14], d[15]));
        __syncwarp();
        if (lane == 0) mbar_arrive(bar + 8 * (B_ZX + ((s + 1) & 1)));
        if (warp == 2) TS(3);
      }
    }
    token_send(NSEG - 2);
    bar_sync(N_ST, 256);
    token_pv(NSEG - 1);
    token_send(NSEG - 1);
    if (lim <= 0) g_err = 1;
    __syncwarp();
    if (warp == 0) PTS(25);
    cluster_arrive();
    cluster_wait();
  } else if (warp < 8) {
    asm volatile("setmaxnreg.inc.sync.aligned.u32 216;");
    const int wq = warp - 4;
    uint32_t w[28][4];
    build_weights<1>(w, sb, lim, lane);
    cluster_wait();
    cluster_arrive_relaxed();
    uint32_t yx[8], ym[2];
    {
      float d[16];
      mbar_wait(bar + 8 * B_X, 0, lim);
      gemm_x(w, sb, d);
#pragma unroll
      for (int i = 0; i < 8; i++) yx[i] = pack2(d[2 * i], d[2 * i + 1]);
      cluster_wait();
    }
    const int ri = lane >> 2, q = lane & 3;
    uint32_t zld = sb + O_Z + (((lane >> 4) | ((lane >> 2) & 2)) * 40 + 8 + 8 * wq + (lane & 7)) * 16;
    uint32_t rs_a = mapa(sb + O_RS + h * 128 + ((ri & 1) * 4 + q) * 16, 4 * wq + (ri >> 1));
    uint32_t rs_b = mapa(bar + 8 * B_RS, 4 * wq + (ri >> 1));
    uint32_t mimg = sb + O_MIMG + lane * 16, l8 = sb + lane * 8;
    float* p_smx = &g_xacc[0][h][wq * 128 + lane * 4];
    const uint8_t* p_smr = xch(h) + (XC_R0 + 2 * XC_REG + lane * 8 + lds32v(sb + O_NEAR));
    const uint32_t yb = sb + O_YB + (tid & 127) * 16;
    sts_u4(yb, yx[0], yx[4], yx[1], yx[5]);
    sts_u4(yb + 2048, yx[2], yx[6], yx[3], yx[7]);
    pin(zld); pin(rs_a); pin(rs_b); pin(mimg); pin(l8); pinp(p_smx);

    uint32_t zb0[4], zb1[4];
    mbar_wait(bar + 8 * B_ZX, 0, lim);
    ldsm4(zb0, zld);
    ldsm4(zb1, zld + 4 * 640);

#pragma unroll 1
    for (int s = 0; s < NSEG; s++) {
      const bool rec = s < NSEG - 1;
      uint32_t img = mimg + (s & 1) * 7168, tag = ((s >> 1) + 1) & 3;
      uint32_t ra = rs_a + (s & 1) * 2048, rb = rs_b + (s & 1) * 8;
      float* smx = p_smx + (s & 3) * (NH * 512);
      pin(img); pin(tag); pin(ra); pin(rb); pinp(smx);
      if (rec) {
        uint32_t a0[4], a1[4];
        const uint32_t mj = s ? mimg + (O_MJ - O_MIMG) + (s & 1) * 1024 : img + j * 1024;
        if (wq == 0) TS(26);
        if (s) mbar_wait(bar + 8 * (B_MJ + (s & 1)), ((s - 1) >> 1) & 1, lim);
        if (wq == 0) TS(27);
        ldsm4(a0, mj);
        ldsm4(a1, mj + 512);
        const float2 e = mma_rows8(a0, a1, zb0, zb1);
        asm volatile("red.relaxed.gpu.global.add.v4.f32 [%0], {%1,%2,%3,%4};" :: "l"(smx), "f"(e.x), "f"(e.y), "f"(1.f), "f"(0.f) : "memory");
        if (wq == 0) TS(15);
      }
      if (wq == 0) TS(20);
      bar_sync(N_YM, 160);
      float c[4];
      {
        const uint64_t dm = (uint64_t)(((sb + O_MIMG + (s & 1) * 7168) >> 4) & 0x3fff) | (8ull << 16) | (8ull << 32);
        wg_fence();
#pragma unroll
        for (int k = 0; k < 28; k++) wgmma_n8_rs(c, w[k], dm + k * 16, k != 0);
        wg_commit();
      }
      wg_wait<0>();
      reg_fence(c);
      ym[0] = pack2(c[0], c[1]);
      ym[1] = pack2(c[2], c[3]);
      sts_u2(yb + 4096 - (tid & 127) * 8 + (s & 1) * 5120, ym[0], ym[1]);
      if (!rec) bar_arrive(N_ST, 256);
      if (wq == 0) TS(4);
      if (rec) {
        bar_sync(N_W1, 160);
        const uint4 pa = lds_u4(mimg + (O_SX - O_MIMG));
        const float2 st = lds_f2(l8 + O_SX + 512);
        const float mxx = st.x, lx = st.y;
        float o0[4] = {0.f, 0.f, 0.f, 0.f}, o1[4] = {0.f, 0.f, 0.f, 0.f}, u0[4] = {0.f, 0.f, 0.f, 0.f}, u1[4] = {0.f, 0.f, 0.f, 0.f};
        mma16v(o0, pa.x, pa.y, pa.z, pa.w, yx[0], yx[4]);
        mma16v(u0, pa.x, pa.y, pa.z, pa.w, yx[2], yx[6]);
        mma16v(o1, pa.x, pa.y, pa.z, pa.w, yx[1], yx[5]);
        mma16v(u1, pa.x, pa.y, pa.z, pa.w, yx[3], yx[7]);
        o0[0] += u0[2]; o0[1] += u0[3]; o1[0] += u1[2]; o1[1] += u1[3];
        if (wq == 0) TS(7);
        uint32_t vm[14];
        int att = 0;
        do {
          mbar_wait(bar + 8 * (B_G + att), s & 1, lim);
#pragma unroll
          for (int k = 0; k < 7; k++) { const uint2 t = lds_u2(l8 + O_GX + att * 1792 + k * 256); vm[2 * k] = t.x; vm[2 * k + 1] = t.y; }
        } while (__any_sync(0xffffffffu, stale7(vm, tag)) && ++att < 8);
        if (tid == 128) sts32v(sb + O_DONE, s + 1);
        if (__builtin_expect(att == 8, 0)) {
          do { load7(vm, reinterpret_cast<const float*>(p_smr + (s & 1) * 1792), 64); } while (__any_sync(0xffffffffu, stale7(vm, tag)) && --lim > 0);
        }
        const float2 sm = add7(vm);
        if (wq == 0) TS(8);
        const float mx = fmaxf(mxx, qmax(fmaxf(sm.x, sm.y)));
        const float nm = -mx * SC2;
        const float al = ex2(fmaf(mxx, SC2, nm)), p0 = ex2(fmaf(sm.x, SC2, nm)), p1 = ex2(fmaf(sm.y, SC2, nm));
        const uint32_t pp = pack2(p0, p1);
        o0[0] *= al; o0[1] *= al; o1[0] *= al; o1[1] *= al;
        mma8v(o0, pp, pp, ym[0]);
        mma8v(o1, pp, pp, ym[1]);
        const float inv = rcp(qsum(fmaf(al, lx, p0 + p1)));
        st_async4(ra, o0[0] * inv, o0[1] * inv, o1[0] * inv, o1[1] * inv, rb);
        bar_arrive(N_ZX, 256);
        if (wq == 0) TS(9);
      }
      if (rec) {
        float d[16];
        bar_sync(N_YX, 256);
        gemm_x(w, sb + ((s + 1) & 3) * XB, d);
#pragma unroll
        for (int i = 0; i < 8; i++) yx[i] = pack2(d[2 * i], d[2 * i + 1]);
        sts_u4(yb + ((s + 1) & 1) * 5120, yx[0], yx[4], yx[1], yx[5]);
        sts_u4(yb + ((s + 1) & 1) * 5120 + 2048, yx[2], yx[6], yx[3], yx[7]);
        mbar_wait(bar + 8 * (B_ZX + ((s + 1) & 1)), ((s + 1) >> 1) & 1, lim);
        ldsm4(zb0, zld + ((s + 1) & 1) * 5120);
        ldsm4(zb1, zld + ((s + 1) & 1) * 5120 + 4 * 640);
        if (wq == 0) TS(10);
      }
    }
    if (lim <= 0) g_err = 1;
    __syncwarp();
    cluster_arrive();
    cluster_wait();
  } else {
    asm volatile("setmaxnreg.dec.sync.aligned.u32 72;");
    if (warp == 8) {
      const int u = lane >> 2, comp = lane & 3;
      uint8_t* gm0 = xch(16) + (XC_R0 + (8 * j + 2 * (h >> 2) + (comp >> 1)) * 128 + (2 * (h & 3) + (u >> 2)) * 16 + ((u & 3) * 2 + (comp & 1)) * 2);
#pragma unroll
      for (int k = 0; k < 6; k++) stg16r(gm0 + k * XC_TWIN, 0xffff);
      cluster_wait();
      if (lane == 0) {
        if (h < 7) tma2d_mc(sb + h * 4096, &tmX, h * 64, 0, bar + 8 * B_X);
#pragma unroll 1
        for (int c = 4; c < 16; c++) {
          const int st = c & 3;
          mbar_wait1(bar + 8 * (B_PE + st), ((c >> 2) - 1) & 1, lim);
          mbar_expect(bar + 8 * (B_PF + st), XB);
          tma2d(sb + (st + 1) * XB, (c & 1) ? &tmWv : &tmWk, h * DH + ((c >> 1) & 3) * 64, (c >> 3) * 224, bar + 8 * (B_PF + st));
        }
      }
      __syncwarp();
      cluster_arrive();
      cluster_wait();
      if (lane == 0) {
        for (int k = 1; k < 3; k++) {
          mbar_expect(bar + 8 * (B_X + k), XB);
          if (h < 7) tma2d_mc(sb + k * XB + h * 4096, &tmX, h * 64, k * 32, bar + 8 * (B_X + k));
        }
      }
      uint32_t chk = sb + O_MIMG + lane * 32 + (lane >> 2) * 4, rs0 = sb + O_RS + lane * 4;
      const uint8_t* gnear = xch(16) + (XC_R0 + lds32v(sb + O_NEAR + 4));
      const uint32_t pc_st = sb + O_PC + ((comp >> 1) * 2 + (u >> 2)) * 16 + ((u & 3) * 2 + (comp & 1)) * 2;
      const uint32_t mj_a = mapa(sb + O_MJ + (2 * (h >> 2) + ((lane >> 1) & 1)) * 128 + (2 * (h & 3) + (lane & 1)) * 16, lane >> 2);
      const uint32_t mj_b = mapa(bar + 8 * B_MJ, lane >> 2), mj_st = mapa(sb, 8) - mapa(sb, 0);
      const uint8_t* p_smr = xch(h) + (XC_R0 + 2 * XC_REG + lds32v(sb + O_NEAR));
      pin(chk); pin(rs0); pinp(gm0);
      auto load_x = [&](int sg) {
        if (sg < NSEG && h < 7) tma2d_mc(sb + (sg & 3) * XB + h * 4096, &tmX, h * 64, sg * 32, bar + 8 * (B_X + (sg & 3)));
      };
      int s3 = 0;
#pragma unroll 1
      for (int s = 0; s < NSEG; s++) {
        uint32_t ck = chk + (s & 1) * 7168;
        pin(ck);
        bool redo = false;
        if (s) {
          mbar_wait(bar + 8 * (B_M + (s & 1)), ((s - 1) >> 1) & 1, lim);
          uint32_t v[7];
#pragma unroll
          for (int k = 0; k < 7; k++) v[k] = lds32v(ck + k * 1024);
          const uint32_t mx = __vimax3_u32(__vimax3_u32(v[0], v[1], v[2]), __vimax3_u32(v[3], v[4], v[5]), v[6]);
          if (__builtin_expect(__any_sync(0xffffffffu, mx == 0xffffffffu), 0)) {
            redo = true;
            uint32_t late = 0;
#pragma unroll
            for (int k = 0; k < 7; k++) late |= __any_sync(0xffffffffu, v[k] == 0xffffffffu) ? 1u << k : 0u;
            const uint8_t* p = gnear + s3 * XC_REG + lane * 16;
            while (late && --lim > 0) {
              const int k0 = __ffs(late) - 1, k1 = 31 - __clz(late);
              uint32_t t[4][4];
#pragma unroll
              for (int i = 0; i < 4; i++)
                asm volatile("ld.relaxed.gpu.global.v4.u32 {%0,%1,%2,%3}, [%4];" : "=r"(t[i][0]), "=r"(t[i][1]), "=r"(t[i][2]), "=r"(t[i][3])
                             : "l"(p + (i & 2 ? k1 : k0) * 1024 + (i & 1) * 512) : "memory");
#pragma unroll
              for (int i = 0; i < 2; i++) {
                const int kk = i ? k1 : k0;
                const uint32_t m2 = __vimax3_u32(__vimax3_u32(t[2 * i][0], t[2 * i][1], t[2 * i][2]), __vimax3_u32(t[2 * i][3], t[2 * i + 1][0], t[2 * i + 1][1]),
                                                 max(t[2 * i + 1][2], t[2 * i + 1][3]));
                if (!__any_sync(0xffffffffu, m2 == 0xffffffffu)) {
                  const uint32_t d = sb + O_MIMG + (s & 1) * 7168 + kk * 1024 + lane * 16;
                  sts_u4(d, t[2 * i][0], t[2 * i][1], t[2 * i][2], t[2 * i][3]);
                  sts_u4(d + 512, t[2 * i + 1][0], t[2 * i + 1][1], t[2 * i + 1][2], t[2 * i + 1][3]);
                  late &= ~(1u << kk);
                }
              }
            }
            asm volatile("fence.proxy.async.shared::cta;" ::: "memory");
          }
        }
        TS(23);
        if (bar_or(N_ZM, 160, redo)) bar_or(N_ZM, 160, false);
        if (s == NSEG - 1) break;
        const uint32_t tz = clk();
        const uint8_t* gsrc = p_smr + (s & 1) * 1792;
        const bool el0 = elect();
        if (XP == 1 && el0 && s) load_x(s + 2);
        int k = 0;
        uint32_t gdst = sb + O_GX, gbar = bar + 8 * B_G, td = D_S;
        do {
          delay_until(tz, td);
          if (el0) { mbar_expect(gbar, 1792); bulk_ld(gdst, gsrc, 1792, gbar); }
          gdst += 1792; gbar += 8; td += D_SS;
        } while (++k < 8 && (int)lds32v(sb + O_DONE) <= s);
        const uint32_t glast = gbar - 8;
        if (el0) { for (; k < 8; k++, gbar += 8) mbar_arrive(gbar); if (XP == 2 && s) load_x(s + 2); }
        __syncwarp();
        const uint32_t mbar = bar + 8 * (B_M + ((s + 1) & 1));
        const int s3n = s3 == 2 ? 0 : s3 + 1, s3c = s3;
        while ((int)lds32v(sb + O_C3) < s - 2 + (s == NSEG - 2) && --lim > 0) {}
        uint32_t rb = rs0 + (s & 1) * 2048;
        uint8_t* gm = gm0 + s3n * XC_REG;
        uint32_t mdst = sb + O_MIMG + ((s + 1) & 1) * 7168 + h * 448, mb = mbar;
        const uint8_t* msrc = gnear + s3n * XC_REG + h * 448;
        s3 = s3n;
        pin(rb); pinp(gm); pin(mdst); pin(mb); pinp(msrc);
        mbar_wait(bar + 8 * (B_RS + (s & 1)), (s >> 1) & 1, lim);
        TS(11);
        float v[16];
#pragma unroll
        for (int k = 0; k < 16; k++) v[k] = lds_f(rb + k * 128);
        const float sum = (((v[0] + v[1]) + (v[2] + v[3])) + ((v[4] + v[5]) + (v[6] + v[7]))) +
                          (((v[8] + v[9]) + (v[10] + v[11])) + ((v[12] + v[13]) + (v[14] + v[15])));
        stg16r(gm, (uint16_t)(pack2(sum, 0.f) & 0xffff));
        stg16r(gm + XC_TWIN, (uint16_t)(pack2(sum, 0.f) & 0xffff));
        const uint32_t tm = clk();
        TS(12);
        asm volatile("st.shared.u16 [%0], %1;" :: "r"(pc_st), "h"((uint16_t)(pack2(sum, 0.f) & 0xffff)) : "memory");
        __syncwarp();
        const float4 pc = lds_f4(sb + O_PC + (lane & 3) * 16);
        {
          const uint32_t o = ((s + 1) & 1) * 1024, ob = ((s + 1) & 1) * 8;
          st_async4(mj_a + o, pc.x, pc.y, pc.z, pc.w, mj_b + ob);
          st_async4(mj_a + o + mj_st, pc.x, pc.y, pc.z, pc.w, mj_b + ob + mj_st);
        }
        const bool el = elect();
        if (el) mbar_expect(bar + 8 * (B_RS + (s & 1)), 2048);
        mbar_wait(bar + 8 * (B_MJ + ((s + 1) & 1)), (s >> 1) & 1, lim);
        if (D_M) delay_until(clk(), D_M);
        TS(25);
        if (el) {
          mbar_expect(mb, 7168);
          bulk_mc(mdst, msrc, 448, mb);
          mbar_expect(bar + 8 * (B_MJ + (s & 1)), 1024);
          if (s + 3 < NSEG) mbar_expect(bar + 8 * (B_X + ((s + 3) & 3)), XB);
          if (XP == 0) load_x(s + 3);
        }
        stg16r(gm0 + s3c * XC_REG, 0xffff);
        stg16r(gm0 + s3c * XC_REG + XC_TWIN, 0xffff);
        mbar_wait(glast, s & 1, lim);
      }
    } else if (warp < 11) {
      const int mt = warp - 9, q = lane & 3;
#pragma unroll 1
      for (int t = mt * 32 + lane; t < 448; t += 64) {
        const uint4 v = *reinterpret_cast<const uint4*>(mem0 + (t & 7) * DM + (t >> 3) * 8);
        sts_u4(sb + O_MIMG + t * 16, v.x, v.y, v.z, v.w);
      }
      asm volatile("fence.proxy.async.shared::cta;" ::: "memory");
      if (mt == 1 && lane == 0) sts32v(sb + O_NEAR + 4, near_copy(xch(16) + 2 * XC_REG - (blockIdx.x % 7) * 128));
      __syncwarp();
      cluster_wait();
      cluster_arrive();
      cluster_wait();
#pragma unroll 1
      for (int s = 0; s < NSEG; s++) {
        mbar_wait(bar + 8 * (B_T + (s & 1)), (s >> 1) & 1, lim);
        if (s < NSEG - 1) mbar_wait(bar + 8 * (B_G + 7), s & 1, lim);
        const uint32_t t0 = clk();
        if (mt == 0 && elect()) {
          asm volatile("cp.reduce.async.bulk.global.shared::cta.bulk_group.add.f32 [%0], [%1], 5632;" :: "l"(&g_sacc[s & 7][h][0]), "r"(sb + O_ST + (s & 1) * 5632) : "memory");
          asm volatile("cp.async.bulk.commit_group;" ::: "memory");
          asm volatile("cp.async.bulk.wait_group.read 0;" ::: "memory");
        }
        __syncwarp();
        delay_until(t0, D_T);
        if (mt) TS(28);
        const float4* sp = reinterpret_cast<const float4*>(&g_sacc[s & 7][h][mt * 512 + lane * 4]);
        float u[7][4];
        bool stale;
        do {
          stale = false;
#pragma unroll
          for (int c = 0; c < 7; c++) {
            u[c][0] = u[c][1] = u[c][2] = 0.f; u[c][3] = 7.f;
            if (c < 4 || mt)
              asm volatile("ld.relaxed.gpu.global.v4.f32 {%0,%1,%2,%3}, [%4];" : "=f"(u[c][0]), "=f"(u[c][1]), "=f"(u[c][2]), "=f"(u[c][3]) : "l"(sp + c * 32) : "memory");
          }
#pragma unroll
          for (int c = 0; c < 7; c++) stale |= u[c][3] != 7.f;
        } while (__any_sync(0xffffffffu, stale) && --lim > 0);
        if (mt) TS(29);
        uint32_t pk[2][5];
        float v[2][10];
#pragma unroll
        for (int e = 0; e < 10; e++) {
          const int i = 4 * (e >> 1) + (e & 1);
          v[0][e] = u[i / 3][i % 3];
          v[1][e] = u[(i + 2) / 3][(i + 2) % 3];
        }
#pragma unroll
        for (int rg = 0; rg < 2; rg++) {
          const int row = 16 * mt + 8 * rg + (lane >> 2);
#pragma unroll
          for (int e = 2; e < 10; e++)
            if (8 * ((e >> 1) - 1) + 2 * q + (e & 1) > row) v[rg][e] = MASKV;
          float mx = v[rg][0];
#pragma unroll
          for (int e = 1; e < 10; e++) mx = fmaxf(mx, v[rg][e]);
          mx = qmax(mx);
          const float nb = -mx * SC2;
          float l = 0.f;
#pragma unroll
          for (int e = 0; e < 10; e++) { v[rg][e] = ex2(fmaf(v[rg][e], SC2, nb)); l += v[rg][e]; }
          const float inv = rcp(qsum(l));
#pragma unroll
          for (int n = 0; n < 5; n++) pk[rg][n] = pack2(v[rg][2 * n] * inv, v[rg][2 * n + 1] * inv);
        }
        const uint32_t pb = sb + O_P + (s & 1) * 2560 + mt * 1280;
        sts_u4(pb + lane * 16, pk[0][1], pk[1][1], pk[0][3], pk[1][3]);
        sts_u4(pb + 512 + lane * 16, pk[0][2], pk[1][2], pk[0][4], pk[1][4]);
        sts_u2(pb + 1024 + lane * 8, pk[0][0], pk[1][0]);
        __syncwarp();
        if (lane == 0) mbar_arrive(bar + 8 * (B_P + (s & 1)));
        if (mt == 1) TS(13);
        if (j + 7 * mt < 11) asm volatile("st.relaxed.gpu.global.v4.f32 [%0], {%1,%1,%1,%1};" :: "l"(&g_sacc[(s + 4) & 7][h][(j + 7 * mt) * 128 + lane * 4]), "f"(0.f) : "memory");
      }
    } else {
      const int t1 = lane >> 4, l16 = lane & 15;
      const int col = j * 64 + ((lane >> 2) & 3) * 16 + (lane & 3) * 2;
      const uint32_t epoch = ldg1r(&g_ticket[0]) / 112 + 1;
      if (lane == 0) {
        sts32v(sb + O_NEAR, near_copy(xch(h)));
      }
      __syncwarp();
      cluster_wait();
      cluster_arrive();
      cluster_wait();
      const int trow = 16 * (h >> 3) + (h & 7) + 8 * t1;
      const uint32_t xg = sb + trow * 128 + (((l16 >> 1) ^ (trow & 7)) << 4) + (l16 & 1) * 8;
      auto gate = [&](int sg) {
        mbar_wait(bar + 8 * (B_X + (sg & 3)), (sg >> 2) & 1, lim);
        float z = 0.f;
#pragma unroll 1
        for (int k = 0; k < 7; k++) {
          const uint2 xv = lds_u2(xg + (sg & 3) * XB + k * 4096);
          const uint2 gw = *reinterpret_cast<const uint2*>(gate_w + (k * 16 + l16) * 4);
          z = fmaf(bf_lo(xv.x), bf_lo(gw.x), z); z = fmaf(bf_hi(xv.x), bf_hi(gw.x), z);
          z = fmaf(bf_lo(xv.y), bf_lo(gw.y), z); z = fmaf(bf_hi(xv.y), bf_hi(gw.y), z);
        }
#pragma unroll
        for (int o = 1; o < 16; o <<= 1) z += __shfl_xor_sync(0xffffffffu, z, o);
        return rcp(1.f + ex2(-1.4426950408889634f * z));
      };
      float4 pa4 = make_float4(0.f, 0.f, 0.f, 0.f);
      bool pend = false;
      auto finish = [&](int sg) {
        if (ldg1r(&g_bflag[sg >> 1][j >> 2][0]) == epoch) {
          const int o = (sg * 32 + trow) * DM + col;
          uint32_t b0, b1, b2, b3;
          ldg2r(b0, b1, g_b + o); ldg2r(b2, b3, g_b + o + 8);
          uint32_t* op = reinterpret_cast<uint32_t*>(out + o);
          op[0] = pack2(pa4.x + __uint_as_float(b0), pa4.y + __uint_as_float(b1));
          op[4] = pack2(pa4.z + __uint_as_float(b2), pa4.w + __uint_as_float(b3));
        }
      };
      float g1 = gate(0), g2 = gate(1);
#pragma unroll 1
      for (int st = 0; st < NSEG + 2; st++) {
        if (st < NSEG - 1) {
          const int s = st;
          if (s) mbar_wait(bar + 8 * (B_M + (s & 1)), ((s - 1) >> 1) & 1, lim);
          delay_until(clk(), s ? D_X : 1500);
          const float4* xp = reinterpret_cast<const float4*>(&g_xacc[s & 3][h][lane * 4]);
          float v[4][4];
          bool stale;
          do {
#pragma unroll
            for (int n = 0; n < 4; n++)
              asm volatile("ld.relaxed.gpu.global.v4.f32 {%0,%1,%2,%3}, [%4];" : "=f"(v[n][0]), "=f"(v[n][1]), "=f"(v[n][2]), "=f"(v[n][3]) : "l"(xp + n * 32) : "memory");
            stale = __any_sync(0xffffffffu, (v[0][2] + v[0][3] != 7.f) | (v[1][2] + v[1][3] != 7.f) | (v[2][2] + v[2][3] != 7.f) | (v[3][2] + v[3][3] != 7.f));
          } while (stale && --lim > 0);
          const float mx = qmax(fmaxf(fmaxf(fmaxf(v[0][0], v[0][1]), fmaxf(v[1][0], v[1][1])), fmaxf(fmaxf(v[2][0], v[2][1]), fmaxf(v[3][0], v[3][1]))));
          const float nb = -mx * SC2;
          float lx = 0.f;
          uint32_t pa[4];
#pragma unroll
          for (int n = 0; n < 4; n++) {
            const float p0 = ex2(fmaf(v[n][0], SC2, nb)), p1 = ex2(fmaf(v[n][1], SC2, nb));
            lx += p0 + p1;
            pa[n] = pack2(p0, p1);
          }
          sts_u4(sb + O_SX + lane * 16, pa[0], pa[1], pa[2], pa[3]);
          sts_f2(sb + O_SX + 512 + lane * 8, mx, lx);
          bar_arrive(N_W1, 160);
          TS(22);
        }
        if (lane < 19 && j * 19 + lane < 128 && st != NSEG - 1)
          asm volatile("st.relaxed.gpu.global.v4.f32 [%0], {%1,%1,%1,%1};" :: "l"(&g_xacc[(st + 2 - (st >= NSEG) * 5) & 3][h][(j * 19 + lane) * 4]), "f"(0.f) : "memory");
        if (st < 2) continue;
        const int s = st - 2;
        const int tok = s * 32 + trow;
        const bool have_b = ldg1r(&g_bflag[s >> 1][j >> 2][0]) == epoch;
        if (pend) { if (s >= NSEG - 3) __threadfence(); finish(s - 1); }
        const float* bp = &g_b[tok * DM + col];
        uint32_t b0 = 0, b1 = 0, b2 = 0, b3 = 0;
        if (have_b) { ldg2r(b0, b1, bp); ldg2r(b2, b3, bp + 8); }
        const bool last = s == NSEG - 1;
        mbar_wait(bar + 8 * (last ? B_OL : B_O + (s & 1)), last ? 0 : (s >> 1) & 1, lim);
        const float g = g1;
        g1 = g2;
        if (s + 2 < NSEG) g2 = gate(s + 2);
        const uint32_t ob = sb + O_ORS + (last ? 2 : s & 1) * 4096 + t1 * 2048 + l16 * 16;
        float e[8] = {0.f, 0.f, 0.f, 0.f, 0.f, 0.f, 0.f, 0.f};
#pragma unroll 2
        for (int k = 0; k < 8; k++) {
          const uint4 c = lds_u4(ob + k * 256);
          e[0] += bf_lo(c.x); e[1] += bf_hi(c.x); e[2] += bf_lo(c.y); e[3] += bf_hi(c.y);
          e[4] += bf_lo(c.z); e[5] += bf_hi(c.z); e[6] += bf_lo(c.w); e[7] += bf_hi(c.w);
        }
        float4 a;
        a.x = g * ((t1 ? e[4] : e[0]) + __shfl_xor_sync(0xffffffffu, t1 ? e[0] : e[4], 16));
        a.y = g * ((t1 ? e[5] : e[1]) + __shfl_xor_sync(0xffffffffu, t1 ? e[1] : e[5], 16));
        a.z = g * ((t1 ? e[6] : e[2]) + __shfl_xor_sync(0xffffffffu, t1 ? e[2] : e[6], 16));
        a.w = g * ((t1 ? e[7] : e[3]) + __shfl_xor_sync(0xffffffffu, t1 ? e[3] : e[7], 16));
        __syncwarp();
        if (lane == 0 && s < NSEG - 3) mbar_expect(bar + 8 * (B_O + (s & 1)), 4096);
        if (lane == 0) sts32v(sb + O_C3, s + 1);
        float* sp = &g_stash[tok * DM + col];
        stg2r(sp, tagf(a.x, epoch & 3), tagf(a.y, epoch & 3));
        stg2r(sp + 8, tagf(a.z, epoch & 3), tagf(a.w, epoch & 3));
        if (have_b) {
          uint32_t* op = reinterpret_cast<uint32_t*>(out + tok * DM + col);
          op[0] = pack2(a.x + __uint_as_float(b0), a.y + __uint_as_float(b1));
          op[4] = pack2(a.z + __uint_as_float(b2), a.w + __uint_as_float(b3));
        }
        pend = !have_b;
        pa4 = a;
        TS(14);
      }
      if (pend) { __threadfence(); finish(NSEG - 1); }
      if (lane == 0) atomicAdd(&g_ticket[0], 1);
    }
    if (lim <= 0) g_err = 1;
    __syncwarp();
    cluster_arrive();
    cluster_wait();
  }
}

constexpr uint32_t F_STAGE = 49152, F_BAR = 4 * F_STAGE, F_G = F_BAR + 128, F_M = F_G + 512, F_SMEM = F_M + 1024 + 1024;

template <int N>
DEVI void ffn_tile(float (&d)[N / 2], uint32_t sb, int wg, int nk, int& it, int& dead, int lane) {
#pragma unroll 1
  for (int k = 0; k < nk; k++, it++) {
    const int st = it & 3;
    mbar_wait(sb + F_BAR + 8 * st, (it >> 2) & 1, dead);
    const uint64_t da = desc128(sb + st * F_STAGE + wg * 8192, 1), db = desc128(sb + st * F_STAGE + 16384, 512);
    wg_fence();
#pragma unroll
    for (int kk = 0; kk < 4; kk++) {
      if constexpr (N == 256) wgmma_n256_kn(d, da + kk * 2, db + kk * 128, (k | kk) != 0);
      else                    wgmma_n192_kn(d, da + kk * 2, db + kk * 128, (k | kk) != 0);
    }
    wg_commit();
    if (k) { wg_wait<1>(); if (lane == 0) mbar_arrive(sb + F_BAR + 32 + 8 * ((it - 1) & 3)); }
  }
  wg_wait<0>();
  if (lane == 0) mbar_arrive(sb + F_BAR + 32 + 8 * ((it - 1) & 3));
  reg_fence(d);
}

template <int NJ>
DEVI void ffn_finish(float (&d)[NJ * 32], float g0, float g1, uint32_t sb, int r0, int row, int j0, uint32_t epoch,
                     __nv_bfloat16* __restrict__ out, int tid) {
  const int wg = tid >> 7, t = tid & 127, off = (r0 + row) * DM + j0 * 64 + 2 * (tid & 3);
#pragma unroll
  for (int n = 0; n < NJ * 8; n++) {
    d[4 * n] *= g0; d[4 * n + 1] *= g0; d[4 * n + 2] *= g1; d[4 * n + 3] *= g1;
    *reinterpret_cast<float2*>(g_b + off + n * 8) = make_float2(d[4 * n], d[4 * n + 1]);
    *reinterpret_cast<float2*>(g_b + off + 8 * DM + n * 8) = make_float2(d[4 * n + 2], d[4 * n + 3]);
  }
  asm volatile("fence.release.gpu;" ::: "memory");
  bar_sync(2 + wg, 128);
  if (t == 0) {
    asm volatile("st.relaxed.gpu.global.u32 [%0], %1;" :: "l"(&g_bflag[(r0 >> 6) + wg][j0 >> 2][0]), "r"(epoch) : "memory");
    __threadfence();
  }
  bar_sync(2 + wg, 128);
#pragma unroll
  for (int n0 = 0; n0 < NJ * 8; n0 += 8) {
    uint32_t a[8][4];
#pragma unroll
    for (int n = 0; n < 8; n++) { ldg2r(a[n][0], a[n][1], g_stash + off + (n0 + n) * 8); ldg2r(a[n][2], a[n][3], g_stash + off + 8 * DM + (n0 + n) * 8); }
#pragma unroll
    for (int n = 0; n < 8; n++)
#pragma unroll
      for (int half = 0; half < 2; half++)
        if (((a[n][2 * half] ^ epoch) & 3) == 0)
          *reinterpret_cast<uint32_t*>(out + off + half * 8 * DM + (n0 + n) * 8) =
              pack2(__uint_as_float(a[n][2 * half]) + d[4 * (n0 + n) + 2 * half], __uint_as_float(a[n][2 * half + 1]) + d[4 * (n0 + n) + 2 * half + 1]);
  }
}

__global__ void __launch_bounds__(384, 1)
ffn_kernel(const __grid_constant__ CUtensorMap tmX, const __grid_constant__ CUtensorMap tmW1,
           const __grid_constant__ CUtensorMap tmH, const __grid_constant__ CUtensorMap tmW2,
           const __nv_bfloat16* __restrict__ x, const __nv_bfloat16* __restrict__ gate_w, __nv_bfloat16* __restrict__ out) {
  extern __shared__ uint8_t smem_raw[];
  const uint32_t sb = (smem_u32(smem_raw) + 1023) & ~1023u;
  const uint32_t hbar = sb + F_BAR + 64;
  int dead = SPIN_LIMIT;
  const int tid = threadIdx.x, lane = tid & 31, warp = __shfl_sync(0xffffffffu, tid >> 5, 0), r0 = blockIdx.x * 128;
  if (tid == 0) {
    for (int i = 0; i < 4; i++) { mbar_init(sb + F_BAR + 8 * i, 1); mbar_init(sb + F_BAR + 32 + 8 * i, 8); }
    mbar_init(hbar, 256);
    asm volatile("fence.mbarrier_init.release.cluster;" ::: "memory");
    asm volatile("fence.proxy.async.shared::cta;" ::: "memory");
  }
  __syncthreads();
  if (warp >= 8) {
    asm volatile("setmaxnreg.dec.sync.aligned.u32 56;");
    if (tid == 256) {
      int it = 0;
#pragma unroll 1
      for (int t = 0; t < 9; t++) {
        const int nk = t < 7 ? 7 : 28, nb = t < 8 ? 4 : 3;
        if (t == 7) mbar_wait1(hbar, 0, dead);
#pragma unroll 1
        for (int k = 0; k < nk; k++, it++) {
          const int st = it & 3;
          const uint32_t fb = sb + F_BAR + 8 * st, a = sb + st * F_STAGE;
          if (it >= 4) mbar_wait1(fb + 32, ((it >> 2) - 1) & 1, dead);
          mbar_expect(fb, 16384 + nb * 8192);
          tma2d(a, t < 7 ? &tmX : &tmH, k * 64, r0, fb);
          for (int b = 0; b < nb; b++) tma2d(a + 16384 + b * 8192, t < 7 ? &tmW1 : &tmW2, (t < 7 ? t : t - 7) * 256 + b * 64, k * 64, fb);
        }
      }
    } else if (warp > 8) {
      const int l16 = lane & 15;
      for (int r = (warp - 9) * 2 + (lane >> 4); r < 132; r += 6) {
        const int rr = r < 128 ? r : 127;
        float z = 0.f;
#pragma unroll
        for (int k = 0; k < 7; k++) {
          const uint2 xv = *reinterpret_cast<const uint2*>(x + (r0 + rr) * DM + (k * 16 + l16) * 4);
          const uint2 gv = *reinterpret_cast<const uint2*>(gate_w + (k * 16 + l16) * 4);
          z = fmaf(bf_lo(xv.x), bf_lo(gv.x), z); z = fmaf(bf_hi(xv.x), bf_hi(gv.x), z);
          z = fmaf(bf_lo(xv.y), bf_lo(gv.y), z); z = fmaf(bf_hi(xv.y), bf_hi(gv.y), z);
        }
#pragma unroll
        for (int o = 1; o < 16; o <<= 1) z += __shfl_xor_sync(0xffffffffu, z, o);
        if (l16 == 0) sts32v(sb + F_G + rr * 4, __float_as_uint(1.f - rcp(1.f + ex2(-1.4426950408889634f * z))));
      }
      __syncwarp();
      bar_arrive(1, 352);
    }
  } else {
    asm volatile("setmaxnreg.inc.sync.aligned.u32 224;");
    const int wg = warp >> 2, row = wg * 64 + (warp & 3) * 16 + (lane >> 2), q = lane & 3;
    const uint32_t epoch = (ldg1r(&g_ticket[1]) >> 4) + 1;
    int it = 0;
#pragma unroll 1
    for (int t = 0; t < 7; t++) {
      float d[128];
      ffn_tile<256>(d, sb, wg, 7, it, dead, lane);
      __nv_bfloat16* hp = g_h + (size_t)(r0 + row) * DFF + t * 256 + 2 * q;
#pragma unroll
      for (int n = 0; n < 32; n++) {
        *reinterpret_cast<uint32_t*>(hp + n * 8) = pack2(fmaxf(d[4 * n], 0.f), fmaxf(d[4 * n + 1], 0.f));
        *reinterpret_cast<uint32_t*>(hp + 8 * DFF + n * 8) = pack2(fmaxf(d[4 * n + 2], 0.f), fmaxf(d[4 * n + 3], 0.f));
      }
    }
    __threadfence();
    asm volatile("fence.proxy.async;" ::: "memory");
    mbar_arrive(hbar);
    bar_sync(1, 352);
    const float g0 = lds_f(sb + F_G + row * 4), g1 = lds_f(sb + F_G + row * 4 + 32);
    {
      float d[128];
      ffn_tile<256>(d, sb, wg, 28, it, dead, lane);
      ffn_finish<4>(d, g0, g1, sb, r0, row, 0, epoch, out, tid);
    }
    {
      float d[96];
      ffn_tile<192>(d, sb, wg, 28, it, dead, lane);
      ffn_finish<3>(d, g0, g1, sb, r0, row, 4, epoch, out, tid);
    }
    bar_sync(1, 256);
    if (tid == 0) atomicAdd(&g_ticket[1], 1);
    if (dead <= 0) g_err = 1;
  }
}

typedef CUresult (*EncodeFn)(CUtensorMap*, CUtensorMapDataType, cuuint32_t, void*, const cuuint64_t*, const cuuint64_t*,
                             const cuuint32_t*, const cuuint32_t*, CUtensorMapInterleave, CUtensorMapSwizzle,
                             CUtensorMapL2promotion, CUtensorMapFloatOOBfill);

void make_map(EncodeFn fn, CUtensorMap* m, const void* p, uint64_t rows, uint64_t cols, uint32_t box_rows) {
  const cuuint64_t dims[2] = {cols, rows}, strides[1] = {cols * 2};
  const cuuint32_t box[2] = {64, box_rows}, es[2] = {1, 1};
  fn(m, CU_TENSOR_MAP_DATA_TYPE_BFLOAT16, 2, const_cast<void*>(p), dims, strides, box, es, CU_TENSOR_MAP_INTERLEAVE_NONE,
     CU_TENSOR_MAP_SWIZZLE_128B, CU_TENSOR_MAP_L2_PROMOTION_L2_256B, CU_TENSOR_MAP_FLOAT_OOB_FILL_NONE);
}

}

extern "C" void kernel_launch(void* const* d_in, const int* in_sizes, int n_in, void* d_out, int out_size) {
  (void)in_sizes; (void)n_in; (void)out_size;
  const __nv_bfloat16* x = (const __nv_bfloat16*)d_in[0];
  const __nv_bfloat16* mem0 = (const __nv_bfloat16*)d_in[1];
  const __nv_bfloat16* gate_w = (const __nv_bfloat16*)d_in[10];
  static EncodeFn fn = nullptr;
  static void* hptr = nullptr;
  if (!fn) {
    cudaDriverEntryPointQueryResult qr;
    cudaGetDriverEntryPoint("cuTensorMapEncodeTiled", (void**)&fn, cudaEnableDefault, &qr);
    cudaGetSymbolAddress(&hptr, g_h);
    cudaFuncSetAttribute(rmt_kernel, cudaFuncAttributeMaxDynamicSharedMemorySize, T_SMEM);
    cudaFuncSetAttribute(rmt_kernel, cudaFuncAttributeNonPortableClusterSizeAllowed, 1);
    cudaFuncSetAttribute(ffn_kernel, cudaFuncAttributeMaxDynamicSharedMemorySize, F_SMEM);
  }
  CUtensorMap mWq, mWk, mWv, mWo, mX, mXf, mW1, mH, mW2;
  make_map(fn, &mWq, d_in[2], DM, NH * DH, 64);
  make_map(fn, &mWk, d_in[3], DM, NH * DH, 224);
  make_map(fn, &mWv, d_in[4], DM, NH * DH, 224);
  make_map(fn, &mWo, d_in[5], NH * DH, DM, 256);
  make_map(fn, &mX, x, SEQ, DM, 32);
  make_map(fn, &mXf, x, SEQ, DM, 128);
  make_map(fn, &mW1, d_in[8], DM, DFF, 64);
  make_map(fn, &mH, hptr, SEQ, DFF, 128);
  make_map(fn, &mW2, d_in[9], DFF, DM, 64);

  cudaLaunchConfig_t cfg = {};
  cudaLaunchAttribute at[1];
  cfg.gridDim = dim3(112); cfg.blockDim = dim3(384); cfg.dynamicSmemBytes = T_SMEM; cfg.stream = cudaStreamPerThread;
  at[0].id = cudaLaunchAttributeClusterDimension;
  at[0].val.clusterDim.x = 16; at[0].val.clusterDim.y = 1; at[0].val.clusterDim.z = 1;
  cfg.attrs = at; cfg.numAttrs = 1;
  cudaLaunchKernelEx(&cfg, rmt_kernel, mWq, mWk, mWv, mWo, mX, x, mem0, gate_w, (__nv_bfloat16*)d_out);

  cfg.gridDim = dim3(16); cfg.dynamicSmemBytes = F_SMEM;
  at[0].id = cudaLaunchAttributeProgrammaticStreamSerialization;
  at[0].val.programmaticStreamSerializationAllowed = 1;
  cudaLaunchKernelEx(&cfg, ffn_kernel, mXf, mW1, mH, mW2, x, gate_w, (__nv_bfloat16*)d_out);
}
```

```cpp
#include <cuda_runtime.h>
#include <cuda_bf16.h>
#include <cuda.h>
#include <stdint.h>

namespace {

#define DEVI __device__ __forceinline__

constexpr int SEQ = 2048, DM = 448, NH = 16, DH = 256, NSEG = 64, DFF = 1792;
constexpr float SC2 = 1.4426950408889634f / 16.0f;
constexpr float MASKV = -1.6e10f;
constexpr int SPIN_LIMIT = 1 << 22;

#define D_M 550
#define D_X 300
#define D_T 700
#define D_SS 150
#define O_SEND 1
#define XP 2
#define D_SQ 30
#define D_XS 220
#define XD0 0
#define XEV 1
#define D_S 100

__device__ __align__(1024) uint8_t g_xch_raw[18 * 65536];
DEVI uint8_t* xch(int blk) { return reinterpret_cast<uint8_t*>((reinterpret_cast<uintptr_t>(g_xch_raw) + 65535) & ~(uintptr_t)65535) + blk * 65536; }
constexpr uint32_t XC_R0 = 4096, XC_REG = 16384, XC_TWIN = 8192;
__device__ __align__(1024) float g_xacc[4][NH][512];
__device__ __align__(1024) float g_sacc[8][NH][1408];
__device__ __align__(1024) float g_stash[SEQ * DM];
__device__ __align__(1024) float g_b[SEQ * DM];
__device__ __align__(1024) __nv_bfloat16 g_h[SEQ * DFF];
__device__ __align__(1024) uint32_t g_bflag[32][2][8];
__device__ uint32_t g_ticket[2];
__device__ int g_err;
#define TS(i)
#define PTS(i)

DEVI uint32_t smem_u32(const void* p) { return (uint32_t)__cvta_generic_to_shared(p); }
DEVI uint32_t clk() { uint32_t c; asm volatile("mov.u32 %0, %%clock;" : "=r"(c) :: "memory"); return c; }
DEVI void mbar_init(uint32_t bar, uint32_t cnt) { asm volatile("mbarrier.init.shared::cta.b64 [%0], %1;" :: "r"(bar), "r"(cnt) : "memory"); }
DEVI void mbar_expect(uint32_t bar, uint32_t bytes) { asm volatile("mbarrier.arrive.expect_tx.shared::cta.b64 _, [%0], %1;" :: "r"(bar), "r"(bytes) : "memory"); }
DEVI void mbar_arrive(uint32_t bar) { asm volatile("mbarrier.arrive.shared::cta.b64 _, [%0];" :: "r"(bar) : "memory"); }
DEVI uint32_t lds32v(uint32_t a) { uint32_t v; asm volatile("ld.volatile.shared::cta.u32 %0, [%1];" : "=r"(v) : "r"(a) : "memory"); return v; }
DEVI void sts32v(uint32_t a, uint32_t v) { asm volatile("st.volatile.shared::cta.u32 [%0], %1;" :: "r"(a), "r"(v) : "memory"); }
DEVI void mbar_wait(uint32_t bar, uint32_t par, int& lim) {
  asm volatile("{\n.reg .pred p, q;\nWAIT_LOOP:\n"
               "mbarrier.try_wait.parity.shared::cta.b64 p, [%1], %2;\n"
               "sub.s32 %0, %0, 1;\nsetp.gt.and.s32 q, %0, 0, !p;\n@q bra.uni WAIT_LOOP;\n}"
               : "+r"(lim) : "r"(bar), "r"(par) : "memory");
}
DEVI void mbar_wait1(uint32_t bar, uint32_t par, int& lim) {
  asm volatile("{\n.reg .pred p, q;\nWAIT_LOOP:\n"
               "mbarrier.try_wait.parity.shared::cta.b64 p, [%1], %2;\n"
               "sub.s32 %0, %0, 1;\nsetp.gt.and.s32 q, %0, 0, !p;\n@q bra WAIT_LOOP;\n}"
               : "+r"(lim) : "r"(bar), "r"(par) : "memory");
}
DEVI bool elect() { uint32_t p; asm volatile("{\n.reg .pred p;\nelect.sync _|p, 0xffffffff;\nselp.u32 %0, 1, 0, p;\n}" : "=r"(p)); return p; }
DEVI bool bar_or(int id, int n, bool v) {
  uint32_t r;
  asm volatile("{\n.reg .pred p, q;\nsetp.ne.u32 q, %3, 0;\nbar.red.or.pred p, %1, %2, q;\nselp.u32 %0, 1, 0, p;\n}"
               : "=r"(r) : "r"(id), "r"(n), "r"((uint32_t)v) : "memory");
  return r;
}
DEVI void delay_until(uint32_t t0, uint32_t d) {
  asm volatile("{\n.reg .pred p;\n.reg .u32 t, u;\n.reg .u64 c;\nDELAY_LOOP:\nmov.u64 c, %%clock64;\nmov.b64 {t, u}, c;\nsub.u32 t, t, %0;\nsetp.lt.u32 p, t, %1;\n@p bra.uni DELAY_LOOP;\n}"
               :: "r"(t0), "r"(d) : "memory");
}
DEVI float rcp(float x) { float y; asm("rcp.approx.ftz.f32 %0, %1;" : "=f"(y) : "f"(x)); return y; }
template <class T> DEVI void pin(T& v) { asm volatile("" : "+r"(v)); }
template <class T> DEVI void pinp(T*& v) { asm volatile("" : "+l"(v)); }
DEVI void bar_sync(int id, int n) { asm volatile("bar.sync %0, %1;" :: "r"(id), "r"(n) : "memory"); }
DEVI void bar_arrive(int id, int n) { asm volatile("bar.arrive %0, %1;" :: "r"(id), "r"(n) : "memory"); }
DEVI void cluster_arrive_relaxed() { asm volatile("barrier.cluster.arrive.relaxed.aligned;" ::: "memory"); }
DEVI void cluster_arrive() { asm volatile("barrier.cluster.arrive.release.aligned;" ::: "memory"); }
DEVI void cluster_wait() { asm volatile("barrier.cluster.wait.acquire.aligned;" ::: "memory"); }
DEVI uint32_t mapa(uint32_t a, uint32_t r) { uint32_t o; asm("mapa.shared::cluster.u32 %0, %1, %2;" : "=r"(o) : "r"(a), "r"(r)); return o; }
DEVI uint32_t pack2(float lo, float hi) { uint32_t r; asm("cvt.rn.bf16x2.f32 %0, %1, %2;" : "=r"(r) : "f"(hi), "f"(lo)); return r; }
DEVI float ex2(float x) { float y; asm("ex2.approx.ftz.f32 %0, %1;" : "=f"(y) : "f"(x)); return y; }
DEVI float bf_lo(uint32_t v) { return __uint_as_float(v << 16); }
DEVI float bf_hi(uint32_t v) { return __uint_as_float(v & 0xffff0000u); }
DEVI void ldsm4(uint32_t (&r)[4], uint32_t a) {
  asm volatile("ldmatrix.sync.aligned.m8n8.x4.shared.b16 {%0,%1,%2,%3}, [%4];" : "=r"(r[0]), "=r"(r[1]), "=r"(r[2]), "=r"(r[3]) : "r"(a) : "memory");
}
DEVI void stsm4t(uint32_t a, uint32_t r0, uint32_t r1, uint32_t r2, uint32_t r3) {
  asm volatile("stmatrix.sync.aligned.m8n8.x4.trans.shared.b16 [%0], {%1,%2,%3,%4};" :: "r"(a), "r"(r0), "r"(r1), "r"(r2), "r"(r3) : "memory");
}
DEVI void stsm2t(uint32_t a, uint32_t r0, uint32_t r1) {
  asm volatile("stmatrix.sync.aligned.m8n8.x2.trans.shared.b16 [%0], {%1,%2};" :: "r"(a), "r"(r0), "r"(r1) : "memory");
}
DEVI void mma16(float (&c)[4], uint32_t a0, uint32_t a1, uint32_t a2, uint32_t a3, uint32_t b0, uint32_t b1) {
  asm("mma.sync.aligned.m16n8k16.row.col.f32.bf16.bf16.f32 {%0,%1,%2,%3},{%4,%5,%6,%7},{%8,%9},{%0,%1,%2,%3};"
      : "+f"(c[0]), "+f"(c[1]), "+f"(c[2]), "+f"(c[3]) : "r"(a0), "r"(a1), "r"(a2), "r"(a3), "r"(b0), "r"(b1));
}
DEVI void mma8(float (&c)[4], uint32_t a0, uint32_t a1, uint32_t b0) {
  asm("mma.sync.aligned.m16n8k8.row.col.f32.bf16.bf16.f32 {%0,%1,%2,%3},{%4,%5},{%6},{%0,%1,%2,%3};"
      : "+f"(c[0]), "+f"(c[1]), "+f"(c[2]), "+f"(c[3]) : "r"(a0), "r"(a1), "r"(b0));
}
DEVI void mma16v(float (&c)[4], uint32_t a0, uint32_t a1, uint32_t a2, uint32_t a3, uint32_t b0, uint32_t b1) {
  asm volatile("mma.sync.aligned.m16n8k16.row.col.f32.bf16.bf16.f32 {%0,%1,%2,%3},{%4,%5,%6,%7},{%8,%9},{%0,%1,%2,%3};"
      : "+f"(c[0]), "+f"(c[1]), "+f"(c[2]), "+f"(c[3]) : "r"(a0), "r"(a1), "r"(a2), "r"(a3), "r"(b0), "r"(b1));
}
DEVI void mma8v(float (&c)[4], uint32_t a0, uint32_t a1, uint32_t b0) {
  asm volatile("mma.sync.aligned.m16n8k8.row.col.f32.bf16.bf16.f32 {%0,%1,%2,%3},{%4,%5},{%6},{%0,%1,%2,%3};"
      : "+f"(c[0]), "+f"(c[1]), "+f"(c[2]), "+f"(c[3]) : "r"(a0), "r"(a1), "r"(b0));
}
DEVI float2 mma_rows8(const uint32_t (&a0)[4], const uint32_t (&a1)[4], const uint32_t (&b0)[4], const uint32_t (&b1)[4]) {
  float e0[4] = {0.f, 0.f, 0.f, 0.f}, e1[4] = {0.f, 0.f, 0.f, 0.f}, e2[4] = {0.f, 0.f, 0.f, 0.f}, e3[4] = {0.f, 0.f, 0.f, 0.f};
  mma16v(e0, a0[0], a0[1], a0[2], a0[3], b0[0], b0[1]);
  mma16v(e1, a0[0], a0[1], a0[2], a0[3], b0[2], b0[3]);
  mma16v(e2, a1[0], a1[1], a1[2], a1[3], b1[0], b1[1]);
  mma16v(e3, a1[0], a1[1], a1[2], a1[3], b1[2], b1[3]);
  return make_float2((e0[0] + e1[2]) + (e2[0] + e3[2]), (e0[1] + e1[3]) + (e2[1] + e3[3]));
}
DEVI void wg_fence() { asm volatile("wgmma.fence.sync.aligned;" ::: "memory"); }
DEVI void wg_commit() { asm volatile("wgmma.commit_group.sync.aligned;" ::: "memory"); }
template <int N> DEVI void wg_wait() { asm volatile("wgmma.wait_group.sync.aligned %0;" :: "n"(N) : "memory"); }
template <int N> DEVI void reg_fence(float (&d)[N]) {
#pragma unroll
  for (int i = 0; i < N; i++) asm volatile("" : "+f"(d[i]) :: "memory");
}
DEVI uint64_t desc128(uint32_t addr, uint32_t lbo16) {
  return (uint64_t)((addr >> 4) & 0x3fff) | ((uint64_t)lbo16 << 16) | (64ull << 32) | (1ull << 62);
}
DEVI void tma2d(uint32_t dst, const CUtensorMap* tm, int c0, int c1, uint32_t bar) {
  asm volatile("cp.async.bulk.tensor.2d.shared::cluster.global.mbarrier::complete_tx::bytes [%0], [%1, {%2, %3}], [%4];"
               :: "r"(dst), "l"(tm), "r"(c0), "r"(c1), "r"(bar) : "memory");
}
DEVI void tma2d_mc(uint32_t dst, const CUtensorMap* tm, int c0, int c1, uint32_t bar) {
  asm volatile("cp.async.bulk.tensor.2d.shared::cluster.global.mbarrier::complete_tx::bytes.multicast::cluster [%0], [%1, {%2, %3}], [%4], %5;"
               :: "r"(dst), "l"(tm), "r"(c0), "r"(c1), "r"(bar), "h"((uint16_t)0xffff) : "memory");
}
DEVI void bulk_ld(uint32_t dst, const void* src, uint32_t bytes, uint32_t bar) {
  asm volatile("cp.async.bulk.shared::cluster.global.mbarrier::complete_tx::bytes [%0], [%1], %2, [%3];"
               :: "r"(dst), "l"(src), "r"(bytes), "r"(bar) : "memory");
}
DEVI void bulk_mc(uint32_t dst, const void* src, uint32_t bytes, uint32_t bar) {
  asm volatile("cp.async.bulk.shared::cluster.global.mbarrier::complete_tx::bytes.multicast::cluster [%0], [%1], %2, [%3], %4;"
               :: "r"(dst), "l"(src), "r"(bytes), "r"(bar), "h"((uint16_t)0xffff) : "memory");
}
DEVI void st_async4(uint32_t a, float x, float y, float z, float w, uint32_t bar) {
  asm volatile("st.async.weak.shared::cluster.mbarrier::complete_tx::bytes.v4.f32 [%0], {%1,%2,%3,%4}, [%5];"
               :: "r"(a), "f"(x), "f"(y), "f"(z), "f"(w), "r"(bar) : "memory");
}
DEVI void st_async4u(uint32_t a, uint32_t x, uint32_t y, uint32_t z, uint32_t w, uint32_t bar) {
  asm volatile("st.async.weak.shared::cluster.mbarrier::complete_tx::bytes.v4.b32 [%0], {%1,%2,%3,%4}, [%5];"
               :: "r"(a), "r"(x), "r"(y), "r"(z), "r"(w), "r"(bar) : "memory");
}
DEVI uint32_t ldg1r(const void* p) { uint32_t v; asm volatile("ld.relaxed.gpu.global.u32 %0, [%1];" : "=r"(v) : "l"(p) : "memory"); return v; }
DEVI uint32_t near_copy(uint8_t* blk) {
  uint32_t best[2] = {~0u, ~0u}, v = 0;
#pragma unroll 1
  for (int i = 0; i < 6; i++) {
    const uint8_t* p = blk + XC_R0 + 7936 + (i & 1) * XC_TWIN + (v & 4);
    const uint32_t t0 = clk();
    asm volatile("atom.relaxed.gpu.global.and.b32 %0, [%1], 0;" : "=r"(v) : "l"(p) : "memory");
    uint32_t t1;
    asm volatile("{\n.reg .pred p;\nPROBE_WAIT:\nsetp.eq.u32 p, %1, 0x5a5a5a5a;\n@p nanosleep.u32 32;\nmov.u32 %0, %%clock;\n}" : "=r"(t1) : "r"(v) : "memory");
    const uint32_t d = t1 - t0;
    if (i & 1) best[1] = min(best[1], d); else best[0] = min(best[0], d);
  }
  return best[1] < best[0] ? XC_TWIN : 0;
}
DEVI void tma2d_prefetch(const CUtensorMap* tm, int c0, int c1) {
  asm volatile("cp.async.bulk.prefetch.tensor.2d.L2.global [%0, {%1, %2}];" :: "l"(tm), "r"(c0), "r"(c1) : "memory");
}
DEVI void ldg2r(uint32_t& x, uint32_t& y, const void* p) { asm volatile("ld.relaxed.gpu.global.v2.u32 {%0,%1}, [%2];" : "=r"(x), "=r"(y) : "l"(p) : "memory"); }
DEVI void stg2r(void* p, uint32_t x, uint32_t y) { asm volatile("st.relaxed.gpu.global.v2.u32 [%0], {%1,%2};" :: "l"(p), "r"(x), "r"(y) : "memory"); }
DEVI void stg16r(void* p, uint16_t v) { asm volatile("st.relaxed.gpu.global.u16 [%0], %1;" :: "l"(p), "h"(v) : "memory"); }
DEVI float lds_f(uint32_t a) { float v; asm volatile("ld.shared.f32 %0, [%1];" : "=f"(v) : "r"(a) : "memory"); return v; }
DEVI float2 lds_f2(uint32_t a) { float2 v; asm volatile("ld.shared.v2.f32 {%0,%1}, [%2];" : "=f"(v.x), "=f"(v.y) : "r"(a) : "memory"); return v; }
DEVI float4 lds_f4(uint32_t a) { float4 v; asm volatile("ld.shared.v4.f32 {%0,%1,%2,%3}, [%4];" : "=f"(v.x), "=f"(v.y), "=f"(v.z), "=f"(v.w) : "r"(a) : "memory"); return v; }
DEVI uint2 lds_u2(uint32_t a) { uint2 v; asm volatile("ld.shared.v2.u32 {%0,%1}, [%2];" : "=r"(v.x), "=r"(v.y) : "r"(a) : "memory"); return v; }
DEVI uint4 lds_u4(uint32_t a) { uint4 v; asm volatile("ld.shared.v4.u32 {%0,%1,%2,%3}, [%4];" : "=r"(v.x), "=r"(v.y), "=r"(v.z), "=r"(v.w) : "r"(a) : "memory"); return v; }
DEVI void sts_f2(uint32_t a, float x, float y) { asm volatile("st.shared.v2.f32 [%0], {%1,%2};" :: "r"(a), "f"(x), "f"(y) : "memory"); }
DEVI void sts_f4(uint32_t a, float x, float y, float z, float w) { asm volatile("st.shared.v4.f32 [%0], {%1,%2,%3,%4};" :: "r"(a), "f"(x), "f"(y), "f"(z), "f"(w) : "memory"); }
DEVI void sts_u2(uint32_t a, uint32_t x, uint32_t y) { asm volatile("st.shared.v2.u32 [%0], {%1,%2};" :: "r"(a), "r"(x), "r"(y) : "memory"); }
DEVI void sts_u4(uint32_t a, uint32_t x, uint32_t y, uint32_t z, uint32_t w) { asm volatile("st.shared.v4.u32 [%0], {%1,%2,%3,%4};" :: "r"(a), "r"(x), "r"(y), "r"(z), "r"(w) : "memory"); }
DEVI uint32_t tagf(float v, uint32_t tag) { return (__float_as_uint(v) & ~3u) | tag; }
DEVI float qmax(float v) { v = fmaxf(v, __shfl_xor_sync(0xffffffffu, v, 1)); return fmaxf(v, __shfl_xor_sync(0xffffffffu, v, 2)); }
DEVI float qsum(float v) { v += __shfl_xor_sync(0xffffffffu, v, 1); return v + __shfl_xor_sync(0xffffffffu, v, 2); }

__device__ __forceinline__ void wgmma_n224_kk(float (&d)[112], uint64_t da, uint64_t db, int sc) {
  asm volatile("{\n.reg .pred p;\nsetp.ne.b32 p, %114, 0;\n"
    "wgmma.mma_async.sync.aligned.m64n224k16.f32.bf16.bf16 {%0,%1,%2,%3,%4,%5,%6,%7,%8,%9,%10,%11,%12,%13,%14,%15,%16,%17,%18,%19,%20,%21,%22,%23,%24,%25,%26,%27,%28,%29,%30,%31,%32,%33,%34,%35,%36,%37,%38,%39,%40,%41,%42,%43,%44,%45,%46,%47,%48,%49,%50,%51,%52,%53,%54,%55,%56,%57,%58,%59,%60,%61,%62,%63,%64,%65,%66,%67,%68,%69,%70,%71,%72,%73,%74,%75,%76,%77,%78,%79,%80,%81,%82,%83,%84,%85,%86,%87,%88,%89,%90,%91,%92,%93,%94,%95,%96,%97,%98,%99,%100,%101,%102,%103,%104,%105,%106,%107,%108,%109,%110,%111}, %112, %113, p, 1, 1, 0, 0;\n}"
    : "+f"(d[0]),"+f"(d[1]),"+f"(d[2]),"+f"(d[3]),"+f"(d[4]),"+f"(d[5]),"+f"(d[6]),"+f"(d[7]),"+f"(d[8]),"+f"(d[9]),"+f"(d[10]),"+f"(d[11]),"+f"(d[12]),"+f"(d[13]),"+f"(d[14]),"+f"(d[15]),"+f"(d[16]),"+f"(d[17]),"+f"(d[18]),"+f"(d[19]),"+f"(d[20]),"+f"(d[21]),"+f"(d[22]),"+f"(d[23]),"+f"(d[24]),"+f"(d[25]),"+f"(d[26]),"+f"(d[27]),"+f"(d[28]),"+f"(d[29]),"+f"(d[30]),"+f"(d[31]),"+f"(d[32]),"+f"(d[33]),"+f"(d[34]),"+f"(d[35]),"+f"(d[36]),"+f"(d[37]),"+f"(d[38]),"+f"(d[39]),"+f"(d[40]),"+f"(d[41]),"+f"(d[42]),"+f"(d[43]),"+f"(d[44]),"+f"(d[45]),"+f"(d[46]),"+f"(d[47]),"+f"(d[48]),"+f"(d[49]),"+f"(d[50]),"+f"(d[51]),"+f"(d[52]),"+f"(d[53]),"+f"(d[54]),"+f"(d[55]),"+f"(d[56]),"+f"(d[57]),"+f"(d[58]),"+f"(d[59]),"+f"(d[60]),"+f"(d[61]),"+f"(d[62]),"+f"(d[63]),"+f"(d[64]),"+f"(d[65]),"+f"(d[66]),"+f"(d[67]),"+f"(d[68]),"+f"(d[69]),"+f"(d[70]),"+f"(d[71]),"+f"(d[72]),"+f"(d[73]),"+f"(d[74]),"+f"(d[75]),"+f"(d[76]),"+f"(d[77]),"+f"(d[78]),"+f"(d[79]),"+f"(d[80]),"+f"(d[81]),"+f"(d[82]),"+f"(d[83]),"+f"(d[84]),"+f"(d[85]),"+f"(d[86]),"+f"(d[87]),"+f"(d[88]),"+f"(d[89]),"+f"(d[90]),"+f"(d[91]),"+f"(d[92]),"+f"(d[93]),"+f"(d[94]),"+f"(d[95]),"+f"(d[96]),"+f"(d[97]),"+f"(d[98]),"+f"(d[99]),"+f"(d[100]),"+f"(d[101]),"+f"(d[102]),"+f"(d[103]),"+f"(d[104]),"+f"(d[105]),"+f"(d[106]),"+f"(d[107]),"+f"(d[108]),"+f"(d[109]),"+f"(d[110]),"+f"(d[111])
    : "l"(da),"l"(db),"r"(sc));
}
__device__ __forceinline__ void wgmma_n224_mk(float (&d)[112], uint64_t da, uint64_t db, int sc) {
  asm volatile("{\n.reg .pred p;\nsetp.ne.b32 p, %114, 0;\n"
    "wgmma.mma_async.sync.aligned.m64n224k16.f32.bf16.bf16 {%0,%1,%2,%3,%4,%5,%6,%7,%8,%9,%10,%11,%12,%13,%14,%15,%16,%17,%18,%19,%20,%21,%22,%23,%24,%25,%26,%27,%28,%29,%30,%31,%32,%33,%34,%35,%36,%37,%38,%39,%40,%41,%42,%43,%44,%45,%46,%47,%48,%49,%50,%51,%52,%53,%54,%55,%56,%57,%58,%59,%60,%61,%62,%63,%64,%65,%66,%67,%68,%69,%70,%71,%72,%73,%74,%75,%76,%77,%78,%79,%80,%81,%82,%83,%84,%85,%86,%87,%88,%89,%90,%91,%92,%93,%94,%95,%96,%97,%98,%99,%100,%101,%102,%103,%104,%105,%106,%107,%108,%109,%110,%111}, %112, %113, p, 1, 1, 1, 0;\n}"
    : "+f"(d[0]),"+f"(d[1]),"+f"(d[2]),"+f"(d[3]),"+f"(d[4]),"+f"(d[5]),"+f"(d[6]),"+f"(d[7]),"+f"(d[8]),"+f"(d[9]),"+f"(d[10]),"+f"(d[11]),"+f"(d[12]),"+f"(d[13]),"+f"(d[14]),"+f"(d[15]),"+f"(d[16]),"+f"(d[17]),"+f"(d[18]),"+f"(d[19]),"+f"(d[20]),"+f"(d[21]),"+f"(d[22]),"+f"(d[23]),"+f"(d[24]),"+f"(d[25]),"+f"(d[26]),"+f"(d[27]),"+f"(d[28]),"+f"(d[29]),"+f"(d[30]),"+f"(d[31]),"+f"(d[32]),"+f"(d[33]),"+f"(d[34]),"+f"(d[35]),"+f"(d[36]),"+f"(d[37]),"+f"(d[38]),"+f"(d[39]),"+f"(d[40]),"+f"(d[41]),"+f"(d[42]),"+f"(d[43]),"+f"(d[44]),"+f"(d[45]),"+f"(d[46]),"+f"(d[47]),"+f"(d[48]),"+f"(d[49]),"+f"(d[50]),"+f"(d[51]),"+f"(d[52]),"+f"(d[53]),"+f"(d[54]),"+f"(d[55]),"+f"(d[56]),"+f"(d[57]),"+f"(d[58]),"+f"(d[59]),"+f"(d[60]),"+f"(d[61]),"+f"(d[62]),"+f"(d[63]),"+f"(d[64]),"+f"(d[65]),"+f"(d[66]),"+f"(d[67]),"+f"(d[68]),"+f"(d[69]),"+f"(d[70]),"+f"(d[71]),"+f"(d[72]),"+f"(d[73]),"+f"(d[74]),"+f"(d[75]),"+f"(d[76]),"+f"(d[77]),"+f"(d[78]),"+f"(d[79]),"+f"(d[80]),"+f"(d[81]),"+f"(d[82]),"+f"(d[83]),"+f"(d[84]),"+f"(d[85]),"+f"(d[86]),"+f"(d[87]),"+f"(d[88]),"+f"(d[89]),"+f"(d[90]),"+f"(d[91]),"+f"(d[92]),"+f"(d[93]),"+f"(d[94]),"+f"(d[95]),"+f"(d[96]),"+f"(d[97]),"+f"(d[98]),"+f"(d[99]),"+f"(d[100]),"+f"(d[101]),"+f"(d[102]),"+f"(d[103]),"+f"(d[104]),"+f"(d[105]),"+f"(d[106]),"+f"(d[107]),"+f"(d[108]),"+f"(d[109]),"+f"(d[110]),"+f"(d[111])
    : "l"(da),"l"(db),"r"(sc));
}
__device__ __forceinline__ void wgmma_n32_rs(float (&d)[16], const uint32_t (&a)[4], uint64_t db, int sc) {
  asm volatile("{\n.reg .pred p;\nsetp.ne.b32 p, %21, 0;\n"
    "wgmma.mma_async.sync.aligned.m64n32k16.f32.bf16.bf16 {%0,%1,%2,%3,%4,%5,%6,%7,%8,%9,%10,%11,%12,%13,%14,%15}, {%16,%17,%18,%19}, %20, p, 1, 1, 0;\n}"
    : "+f"(d[0]),"+f"(d[1]),"+f"(d[2]),"+f"(d[3]),"+f"(d[4]),"+f"(d[5]),"+f"(d[6]),"+f"(d[7]),"+f"(d[8]),"+f"(d[9]),"+f"(d[10]),"+f"(d[11]),"+f"(d[12]),"+f"(d[13]),"+f"(d[14]),"+f"(d[15])
    : "r"(a[0]),"r"(a[1]),"r"(a[2]),"r"(a[3]),"l"(db),"r"(sc));
}
__device__ __forceinline__ void wgmma_n8_rs(float (&d)[4], const uint32_t (&a)[4], uint64_t db, int sc) {
  asm volatile("{\n.reg .pred p;\nsetp.ne.b32 p, %9, 0;\n"
    "wgmma.mma_async.sync.aligned.m64n8k16.f32.bf16.bf16 {%0,%1,%2,%3}, {%4,%5,%6,%7}, %8, p, 1, 1, 0;\n}"
    : "+f"(d[0]),"+f"(d[1]),"+f"(d[2]),"+f"(d[3])
    : "r"(a[0]),"r"(a[1]),"r"(a[2]),"r"(a[3]),"l"(db),"r"(sc));
}
__device__ __forceinline__ void wgmma_n256_kn(float (&d)[128], uint64_t da, uint64_t db, int sc) {
  asm volatile("{\n.reg .pred p;\nsetp.ne.b32 p, %130, 0;\n"
    "wgmma.mma_async.sync.aligned.m64n256k16.f32.bf16.bf16 {%0,%1,%2,%3,%4,%5,%6,%7,%8,%9,%10,%11,%12,%13,%14,%15,%16,%17,%18,%19,%20,%21,%22,%23,%24,%25,%26,%27,%28,%29,%30,%31,%32,%33,%34,%35,%36,%37,%38,%39,%40,%41,%42,%43,%44,%45,%46,%47,%48,%49,%50,%51,%52,%53,%54,%55,%56,%57,%58,%59,%60,%61,%62,%63,%64,%65,%66,%67,%68,%69,%70,%71,%72,%73,%74,%75,%76,%77,%78,%79,%80,%81,%82,%83,%84,%85,%86,%87,%88,%89,%90,%91,%92,%93,%94,%95,%96,%97,%98,%99,%100,%101,%102,%103,%104,%105,%106,%107,%108,%109,%110,%111,%112,%113,%114,%115,%116,%117,%118,%119,%120,%121,%122,%123,%124,%125,%126,%127}, %128, %129, p, 1, 1, 0, 1;\n}"
    : "+f"(d[0]),"+f"(d[1]),"+f"(d[2]),"+f"(d[3]),"+f"(d[4]),"+f"(d[5]),"+f"(d[6]),"+f"(d[7]),"+f"(d[8]),"+f"(d[9]),"+f"(d[10]),"+f"(d[11]),"+f"(d[12]),"+f"(d[13]),"+f"(d[14]),"+f"(d[15]),"+f"(d[16]),"+f"(d[17]),"+f"(d[18]),"+f"(d[19]),"+f"(d[20]),"+f"(d[21]),"+f"(d[22]),"+f"(d[23]),"+f"(d[24]),"+f"(d[25]),"+f"(d[26]),"+f"(d[27]),"+f"(d[28]),"+f"(d[29]),"+f"(d[30]),"+f"(d[31]),"+f"(d[32]),"+f"(d[33]),"+f"(d[34]),"+f"(d[35]),"+f"(d[36]),"+f"(d[37]),"+f"(d[38]),"+f"(d[39]),"+f"(d[40]),"+f"(d[41]),"+f"(d[42]),"+f"(d[43]),"+f"(d[44]),"+f"(d[45]),"+f"(d[46]),"+f"(d[47]),"+f"(d[48]),"+f"(d[49]),"+f"(d[50]),"+f"(d[51]),"+f"(d[52]),"+f"(d[53]),"+f"(d[54]),"+f"(d[55]),"+f"(d[56]),"+f"(d[57]),"+f"(d[58]),"+f"(d[59]),"+f"(d[60]),"+f"(d[61]),"+f"(d[62]),"+f"(d[63]),"+f"(d[64]),"+f"(d[65]),"+f"(d[66]),"+f"(d[67]),"+f"(d[68]),"+f"(d[69]),"+f"(d[70]),"+f"(d[71]),"+f"(d[72]),"+f"(d[73]),"+f"(d[74]),"+f"(d[75]),"+f"(d[76]),"+f"(d[77]),"+f"(d[78]),"+f"(d[79]),"+f"(d[80]),"+f"(d[81]),"+f"(d[82]),"+f"(d[83]),"+f"(d[84]),"+f"(d[85]),"+f"(d[86]),"+f"(d[87]),"+f"(d[88]),"+f"(d[89]),"+f"(d[90]),"+f"(d[91]),"+f"(d[92]),"+f"(d[93]),"+f"(d[94]),"+f"(d[95]),"+f"(d[96]),"+f"(d[97]),"+f"(d[98]),"+f"(d[99]),"+f"(d[100]),"+f"(d[101]),"+f"(d[102]),"+f"(d[103]),"+f"(d[104]),"+f"(d[105]),"+f"(d[106]),"+f"(d[107]),"+f"(d[108]),"+f"(d[109]),"+f"(d[110]),"+f"(d[111]),"+f"(d[112]),"+f"(d[113]),"+f"(d[114]),"+f"(d[115]),"+f"(d[116]),"+f"(d[117]),"+f"(d[118]),"+f"(d[119]),"+f"(d[120]),"+f"(d[121]),"+f"(d[122]),"+f"(d[123]),"+f"(d[124]),"+f"(d[125]),"+f"(d[126]),"+f"(d[127])
    : "l"(da),"l"(db),"r"(sc));
}
__device__ __forceinline__ void wgmma_n192_kn(float (&d)[96], uint64_t da, uint64_t db, int sc) {
  asm volatile("{\n.reg .pred p;\nsetp.ne.b32 p, %98, 0;\n"
    "wgmma.mma_async.sync.aligned.m64n192k16.f32.bf16.bf16 {%0,%1,%2,%3,%4,%5,%6,%7,%8,%9,%10,%11,%12,%13,%14,%15,%16,%17,%18,%19,%20,%21,%22,%23,%24,%25,%26,%27,%28,%29,%30,%31,%32,%33,%34,%35,%36,%37,%38,%39,%40,%41,%42,%43,%44,%45,%46,%47,%48,%49,%50,%51,%52,%53,%54,%55,%56,%57,%58,%59,%60,%61,%62,%63,%64,%65,%66,%67,%68,%69,%70,%71,%72,%73,%74,%75,%76,%77,%78,%79,%80,%81,%82,%83,%84,%85,%86,%87,%88,%89,%90,%91,%92,%93,%94,%95}, %96, %97, p, 1, 1, 0, 1;\n}"
    : "+f"(d[0]),"+f"(d[1]),"+f"(d[2]),"+f"(d[3]),"+f"(d[4]),"+f"(d[5]),"+f"(d[6]),"+f"(d[7]),"+f"(d[8]),"+f"(d[9]),"+f"(d[10]),"+f"(d[11]),"+f"(d[12]),"+f"(d[13]),"+f"(d[14]),"+f"(d[15]),"+f"(d[16]),"+f"(d[17]),"+f"(d[18]),"+f"(d[19]),"+f"(d[20]),"+f"(d[21]),"+f"(d[22]),"+f"(d[23]),"+f"(d[24]),"+f"(d[25]),"+f"(d[26]),"+f"(d[27]),"+f"(d[28]),"+f"(d[29]),"+f"(d[30]),"+f"(d[31]),"+f"(d[32]),"+f"(d[33]),"+f"(d[34]),"+f"(d[35]),"+f"(d[36]),"+f"(d[37]),"+f"(d[38]),"+f"(d[39]),"+f"(d[40]),"+f"(d[41]),"+f"(d[42]),"+f"(d[43]),"+f"(d[44]),"+f"(d[45]),"+f"(d[46]),"+f"(d[47]),"+f"(d[48]),"+f"(d[49]),"+f"(d[50]),"+f"(d[51]),"+f"(d[52]),"+f"(d[53]),"+f"(d[54]),"+f"(d[55]),"+f"(d[56]),"+f"(d[57]),"+f"(d[58]),"+f"(d[59]),"+f"(d[60]),"+f"(d[61]),"+f"(d[62]),"+f"(d[63]),"+f"(d[64]),"+f"(d[65]),"+f"(d[66]),"+f"(d[67]),"+f"(d[68]),"+f"(d[69]),"+f"(d[70]),"+f"(d[71]),"+f"(d[72]),"+f"(d[73]),"+f"(d[74]),"+f"(d[75]),"+f"(d[76]),"+f"(d[77]),"+f"(d[78]),"+f"(d[79]),"+f"(d[80]),"+f"(d[81]),"+f"(d[82]),"+f"(d[83]),"+f"(d[84]),"+f"(d[85]),"+f"(d[86]),"+f"(d[87]),"+f"(d[88]),"+f"(d[89]),"+f"(d[90]),"+f"(d[91]),"+f"(d[92]),"+f"(d[93]),"+f"(d[94]),"+f"(d[95])
    : "l"(da),"l"(db),"r"(sc));
}

constexpr uint32_t XB = 28672;
constexpr uint32_t O_WQ = 5 * XB;
constexpr uint32_t O_WO = O_WQ + 32768;
constexpr uint32_t O_MIMG = O_WO + 32768;
constexpr uint32_t O_BAR = O_MIMG + 2 * 7168;
constexpr uint32_t O_TS = O_BAR + 384;
constexpr uint32_t T_SMEM = O_TS + 4096 + 128 + 1024;
constexpr uint32_t O_Z = 4 * XB;
constexpr uint32_t O_RS = O_Z + 2 * 5120;
constexpr uint32_t O_ORS = O_RS + 2 * 2048;
constexpr uint32_t O_P = O_ORS + 4 * 4096;
constexpr uint32_t O_SX = O_P + 2 * 2560;
constexpr uint32_t O_MJ = O_SX + 1536;
constexpr uint32_t O_ST = O_MJ + 2048;
constexpr uint32_t O_PC = O_ST + 2 * 5632;
constexpr uint32_t O_YB = O_PC + 128;
constexpr uint32_t O_GX = O_YB + 2 * 5120;
constexpr uint32_t O_GY = O_GX + 2 * 1792;
enum { B_X = 0, B_M = 4, B_RS = 6, B_O = 8, B_ZX = 10, B_P = 12, B_PF = 14, B_PE = 18, B_WQ = 22, B_WO = 23, B_T = 24, B_MJ = 26, B_OL = 28, B_G = 30, B_M2 = 31, B_YM = 33, B_GY = 34, B_N = 35 };
constexpr uint32_t O_NEAR = O_BAR + 8 * B_N, O_DONE = O_NEAR + 8, O_C3 = O_DONE + 4;
enum { N_ZM = 1, N_MOK = 2, N_W1 = 3, N_INIT = 4, N_ZX = 5, N_REDO = 6, N_YX = 7, N_SS = 8, N_ST = 9 };

DEVI void gemm_m(const uint32_t (&w)[28][4], uint32_t img_lane, float (&c)[4]) {
  float acc[4][4];
#pragma unroll
  for (int i = 0; i < 4; i++) { acc[i][0] = acc[i][1] = acc[i][2] = acc[i][3] = 0.f; }
  uint32_t r[14][4];
#pragma unroll
  for (int u = 0; u < 14; u++) ldsm4(r[u], img_lane + u * 512);
#pragma unroll
  for (int u = 0; u < 14; u++) {
    mma16v(acc[(2 * u) & 3], w[2 * u][0], w[2 * u][1], w[2 * u][2], w[2 * u][3], r[u][0], r[u][1]);
    mma16v(acc[(2 * u + 1) & 3], w[2 * u + 1][0], w[2 * u + 1][1], w[2 * u + 1][2], w[2 * u + 1][3], r[u][2], r[u][3]);
  }
#pragma unroll
  for (int i = 0; i < 4; i++) c[i] = (acc[0][i] + acc[1][i]) + (acc[2][i] + acc[3][i]);
}

DEVI void gemm_x_issue(const uint32_t (&w)[28][4], uint32_t xbuf, float (&d)[16]) {
  const uint64_t b0 = desc128(xbuf, 1);
  wg_fence();
#pragma unroll
  for (int k = 0; k < 28; k++) wgmma_n32_rs(d, w[k], b0 + (uint64_t)((k >> 2) * 256 + (k & 3) * 2), k != 0);
  wg_commit();
}
DEVI void gemm_x(const uint32_t (&w)[28][4], uint32_t xbuf, float (&d)[16]) {
  gemm_x_issue(w, xbuf, d);
  wg_wait<0>();
  reg_fence(d);
}

template <int WHICH>
DEVI void build_weights(uint32_t (&w)[28][4], uint32_t sb, int& dead, int lane) {
  const uint32_t bar = sb + O_BAR;
  mbar_wait(bar + 8 * (WHICH ? B_WO : B_WQ), 0, dead);
  if ((threadIdx.x & 127) == 0) PTS(4 + WHICH);
#pragma unroll
  for (int half = 0; half < 2; half++) {
    float d[112];
#pragma unroll 1
    for (int fk = 0; fk < 4; fk++) {
      const int c = 2 * (4 * half + fk) + WHICH, st = c & 3;
      mbar_wait(bar + 8 * (B_PF + st), (c >> 2) & 1, dead);
      if ((threadIdx.x & 127) == 0) PTS(8 + c);
      const uint64_t db = desc128(sb + (st + 1) * XB, 1);
      wg_fence();
#pragma unroll
      for (int kk = 0; kk < 4; kk++) {
        if (WHICH == 0) wgmma_n224_kk(d, desc128(sb + O_WQ + fk * 8192 + kk * 32, 1), db + kk * 2, (fk | kk) != 0);
        else            wgmma_n224_mk(d, desc128(sb + O_WO + (fk * 4 + kk) * 2048, 1), db + kk * 2, (fk | kk) != 0);
      }
      wg_commit();
      wg_wait<0>();
      if (lane == 0) mbar_arrive(bar + 8 * (B_PE + st));
    }
    reg_fence(d);
#pragma unroll
    for (int kk = 0; kk < 14; kk++) {
      w[14 * half + kk][0] = pack2(d[8 * kk + 0], d[8 * kk + 1]);
      w[14 * half + kk][1] = pack2(d[8 * kk + 2], d[8 * kk + 3]);
      w[14 * half + kk][2] = pack2(d[8 * kk + 4], d[8 * kk + 5]);
      w[14 * half + kk][3] = pack2(d[8 * kk + 6], d[8 * kk + 7]);
    }
  }
}

DEVI bool stale7(const uint32_t (&v)[14], uint32_t tag) {
  const uint32_t o = ((v[0] | v[1] | v[2]) | (v[3] | v[4] | v[5]) | (v[6] | v[7] | v[8])) | ((v[9] | v[10] | v[11]) | (v[12] | v[13]));
  const uint32_t a = ((v[0] & v[1] & v[2]) & (v[3] & v[4] & v[5]) & (v[6] & v[7] & v[8])) & ((v[9] & v[10] & v[11]) & (v[12] & v[13]));
  return (((o ^ tag) | (a ^ tag)) & 3u) != 0;
}
DEVI float2 add7(const uint32_t (&v)[14]) {
  float2 r;
  r.x = ((__uint_as_float(v[0]) + __uint_as_float(v[2])) + (__uint_as_float(v[4]) + __uint_as_float(v[6]))) +
        ((__uint_as_float(v[8]) + __uint_as_float(v[10])) + __uint_as_float(v[12]));
  r.y = ((__uint_as_float(v[1]) + __uint_as_float(v[3])) + (__uint_as_float(v[5]) + __uint_as_float(v[7]))) +
        ((__uint_as_float(v[9]) + __uint_as_float(v[11])) + __uint_as_float(v[13]));
  return r;
}

__global__ void __launch_bounds__(384, 1)
rmt_kernel(const __grid_constant__ CUtensorMap tmWq, const __grid_constant__ CUtensorMap tmWk,
           const __grid_constant__ CUtensorMap tmWv, const __grid_constant__ CUtensorMap tmWo,
           const __grid_constant__ CUtensorMap tmX, const __nv_bfloat16* __restrict__ x,
           const __nv_bfloat16* __restrict__ mem0, const __nv_bfloat16* __restrict__ gate_w, __nv_bfloat16* __restrict__ out) {
  extern __shared__ uint8_t smem_raw[];
  const uint32_t sb = (smem_u32(smem_raw) + 1023) & ~1023u;
  const uint32_t bar = sb + O_BAR;
  int lim = SPIN_LIMIT;
  int tid;
  uint32_t h, j;
  asm volatile("mov.u32 %0, %%tid.x;" : "=r"(tid));
  asm volatile("mov.u32 %0, %%cluster_ctarank;" : "=r"(h));
  asm volatile("mov.u32 %0, %%clusterid.x;" : "=r"(j));
  tid = __shfl_sync(0xffffffffu, tid, tid & 31);
  const int lane = tid & 31, warp = __shfl_sync(0xffffffffu, tid >> 5, 0);
  if (warp == 0) PTS(0);

  if (warp == 8) {
    if (elect()) {
#pragma unroll
      for (int i = 0; i < 4; i++) mbar_init(bar + 8 * (B_PF + i), 1);
      mbar_init(bar + 8 * B_WQ, 1);
      mbar_init(bar + 8 * B_WO, 1);
      asm volatile("fence.mbarrier_init.release.cluster;" ::: "memory");
      PTS(1);
      mbar_expect(bar + 8 * B_PF, XB);
      tma2d(sb + XB, &tmWk, h * DH, 0, bar + 8 * B_PF);
      PTS(27);
      mbar_expect(bar + 8 * B_WQ, 32768);
#pragma unroll
      for (int k = 0; k < 4; k++) tma2d(sb + O_WQ + k * 8192, &tmWq, h * DH + k * 64, j * 64, bar + 8 * B_WQ);
      PTS(28);
      mbar_expect(bar + 8 * B_WO, 32768);
      tma2d(sb + O_WO, &tmWo, j * 64, h * DH, bar + 8 * B_WO);
      PTS(29);
#pragma unroll
      for (int c = 1; c < 4; c++) {
        mbar_expect(bar + 8 * (B_PF + c), XB);
        tma2d(sb + (c + 1) * XB, (c & 1) ? &tmWv : &tmWk, h * DH + (c >> 1) * 64, 0, bar + 8 * (B_PF + c));
      }
      PTS(30);
      int c = 4 + j;
      tma2d_prefetch((c & 1) ? &tmWv : &tmWk, h * DH + ((c >> 1) & 3) * 64, (c >> 3) * 224);
      c += 7;
      if (c < 16) tma2d_prefetch((c & 1) ? &tmWv : &tmWk, h * DH + ((c >> 1) & 3) * 64, 224);
    }
  } else if (warp == 9) {
    if (elect()) {
#pragma unroll
      for (int i = 0; i < B_N; i++)
        if (i < B_PF || (i >= B_PE && i < B_WQ) || i >= B_T) mbar_init(bar + 8 * i, i == B_M2 + 1 ? 16 : i >= B_MJ ? 1 : i >= B_T ? 3 : i >= B_PE ? 4 : i >= B_P ? 2 : i >= B_ZX ? 4 : 1);
      sts32v(sb + O_DONE, 0);
      sts32v(sb + O_C3, 0);
      sts32v(sb + O_DONE + 8, 0);
      mbar_expect(bar + 8 * B_X, XB);
      mbar_expect(bar + 8 * B_OL, 4096);
      mbar_expect(bar + 8 * (B_OL + 1), 4096);
#pragma unroll
      for (int i = 0; i < 2; i++) { mbar_expect(bar + 8 * (B_RS + i), 2048); mbar_expect(bar + 8 * (B_O + i), 4096); }
      asm volatile("fence.mbarrier_init.release.cluster;" ::: "memory");
    }
  }
  asm volatile("griddepcontrol.launch_dependents;");
  if (warp == 8) PTS(2);
  __syncthreads();
  cluster_arrive_relaxed();
  if (warp == 0) PTS(3);

  if (warp < 4) {
    asm volatile("setmaxnreg.inc.sync.aligned.u32 216;");
    uint32_t w[28][4];
    build_weights<0>(w, sb, lim, lane);
    if (warp == 0) PTS(6);
    cluster_wait();
    cluster_arrive_relaxed();
    uint32_t zst = sb + O_Z + ((2 * warp + ((lane >> 3) & 1)) * 40 + 8 * (lane >> 4) + (lane & 7)) * 16;
    const int mt = warp & 1, n0 = (warp >> 1) * 3;
    const int ch = lane >> 3, chp = (ch >> 1) | ((ch & 1) << 1);
    uint32_t zld = sb + O_Z + ((warp == 2 ? chp : ch) * 40 + (lane & 7)) * 16 + (warp == 2 ? 0 : n0 * 128);
    const int xrow = 16 * mt + (lane & 15);
    uint32_t xq = sb + j * 4096 + xrow * 128 + (((lane >> 4) ^ (xrow & 7)) << 4);
    uint32_t mimg = sb + O_MIMG + lane * 16, sta = sb + O_ST + (warp == 3 ? 4096 : mt * 2048) + lane * 16;
    uint8_t* p_smm = xch(h) + (XC_R0 + 2 * XC_REG + j * 256 + lane * 8);
    pin(zst); pin(zld); pin(xq); pin(mimg); pin(sta); pinp(p_smm);
    {
      float d[16];
      mbar_wait(bar + 8 * B_X, 0, lim);
      gemm_x(w, sb, d);
      if (warp == 0) PTS(7);
      cluster_wait();
      if (warp == 0) PTS(24);
      stsm4t(zst + 8 * 16, pack2(d[0], d[1]), pack2(d[2], d[3]), pack2(d[4], d[5]), pack2(d[6], d[7]));
      stsm4t(zst + 24 * 16, pack2(d[8], d[9]), pack2(d[10], d[11]), pack2(d[12], d[13]), pack2(d[14], d[15]));
      __syncwarp();
      if (lane == 0) mbar_arrive(bar + 8 * B_ZX);
    }
    const uint32_t o_a = mapa(sb + O_ORS + h * 256 + warp * 64 + (lane & 3) * 16, lane >> 2);
    const uint32_t o_b = mapa(bar + 8 * B_O, lane >> 2);
    const uint32_t o_st = mapa(sb, 8) - mapa(sb, 0);
    uint32_t oh[8];
    auto token_pv = [&](int sp) {
      const uint32_t p16 = mimg + (O_P - O_MIMG) + (sp & 1) * 2560, p8 = p16 + 1024 - lane * 8, yb = sb + O_YB + (sp & 1) * 5120 + tid * 16;
      const uint4 y0 = lds_u4(yb), y1 = lds_u4(yb + 2048);
      const uint2 ymp = lds_u2(yb + 4096 - tid * 8);
      mbar_wait(bar + 8 * (B_P + (sp & 1)), (sp >> 1) & 1, lim);
      const uint2 m0 = lds_u2(p8), m1 = lds_u2(p8 + 1280);
      const uint4 p0 = lds_u4(p16), p1 = lds_u4(p16 + 512), p2 = lds_u4(p16 + 1280), p3 = lds_u4(p16 + 1280 + 512);
      float o0[4] = {0.f, 0.f, 0.f, 0.f}, o1[4] = {0.f, 0.f, 0.f, 0.f}, o2[4] = {0.f, 0.f, 0.f, 0.f}, o3[4] = {0.f, 0.f, 0.f, 0.f};
      mma8(o0, m0.x, m0.y, ymp.x);
      mma8(o1, m0.x, m0.y, ymp.y);
      mma8(o2, m1.x, m1.y, ymp.x);
      mma8(o3, m1.x, m1.y, ymp.y);
      mma16(o0, p0.x, p0.y, p0.z, p0.w, y0.x, y0.y);
      mma16(o1, p0.x, p0.y, p0.z, p0.w, y0.z, y0.w);
      mma16(o2, p2.x, p2.y, p2.z, p2.w, y0.x, y0.y);
      mma16(o3, p2.x, p2.y, p2.z, p2.w, y0.z, y0.w);
      mma16(o0, p1.x, p1.y, p1.z, p1.w, y1.x, y1.y);
      mma16(o1, p1.x, p1.y, p1.z, p1.w, y1.z, y1.w);
      mma16(o2, p3.x, p3.y, p3.z, p3.w, y1.x, y1.y);
      mma16(o3, p3.x, p3.y, p3.z, p3.w, y1.z, y1.w);
      oh[0] = pack2(o0[0], o0[1]); oh[1] = pack2(o1[0], o1[1]); oh[2] = pack2(o0[2], o0[3]); oh[3] = pack2(o1[2], o1[3]);
      oh[4] = pack2(o2[0], o2[1]); oh[5] = pack2(o3[0], o3[1]); oh[6] = pack2(o2[2], o2[3]); oh[7] = pack2(o3[2], o3[3]);
    };
    auto token_send = [&](int sp) {
      const bool last = sp >= NSEG - 2;
      const uint32_t oa = o_a + ((last ? 2 : 0) + (sp & 1)) * 4096, ob = o_b + ((last ? B_OL - B_O : 0) + (sp & 1)) * 8;
      st_async4u(oa, oh[0], oh[1], oh[2], oh[3], ob);
      st_async4u(oa + o_st, oh[4], oh[5], oh[6], oh[7], ob + o_st);
    };
#pragma unroll 1
    for (int s = 0; s < NSEG; s++) {
      const bool rec = s < NSEG - 1;
      uint32_t img = mimg + (s & 1) * 7168, zs = zst + (s & 1) * 5120, zl = zld + (s & 1) * 5120;
      uint32_t tag = ((s >> 1) + 1) & 3;
      uint8_t* smm = p_smm + (s & 1) * 1792;
      pin(img); pin(zs); pin(zl); pin(tag); pinp(smm);
      uint32_t a[4][4];
      if (s) mbar_wait(bar + 8 * (B_M + (s & 1)), ((s - 1) >> 1) & 1, lim);
      if (warp == 2) TS(0);
      float c[4];
      do {
        gemm_m(w, img, c);
        stsm2t(zs, pack2(c[0], c[1]), pack2(c[2], c[3]));
        if (warp == 2) { ldsm4(a[0], img + j * 1024); ldsm4(a[1], img + j * 1024 + 512); }
        if (warp == 1) TS(24);
      } while (__builtin_expect(bar_or(N_ZM, 160, false), 0));
      uint32_t b0[4], b1[4];
      if (warp == 2) {
        TS(1);
        ldsm4(b0, zl);
        ldsm4(b1, zl + 4 * 640);
        const float2 e = mma_rows8(a[0], a[1], b0, b1);
        if (rec) { stg2r(smm, tagf(e.x, tag), tagf(e.y, tag)); stg2r(smm + XC_TWIN, tagf(e.x, tag), tagf(e.y, tag)); }
        if (lane == 0) mbar_arrive(bar + 8 * B_YM);
        TS(2);
      }
      bar_sync(N_SS, 128);
      if (s >= 2) token_send(s - 2);
      bar_sync(N_REDO, 256);
      if (warp != 2) {
        const uint32_t st = sta + (s & 1) * 5632, aq = xq + (s & 3) * XB;
        uint32_t b2[4], b3[4], b4[4], b5[4];
        ldsm4(a[0], aq); ldsm4(b0, zl); ldsm4(b2, zl + 128); ldsm4(b4, zl + 256); ldsm4(a[1], aq ^ 32);
        ldsm4(a[2], aq ^ 64); ldsm4(b1, zl + 2560); ldsm4(b3, zl + 2560 + 128); ldsm4(b5, zl + 2560 + 256); ldsm4(a[3], aq ^ 96);
        float e0[4] = {0.f, 0.f, 0.f, 0.f}, e1[4] = {0.f, 0.f, 0.f, 0.f}, e2[4] = {0.f, 0.f, 0.f, 0.f};
        mma16(e0, a[0][0], a[0][1], a[0][2], a[0][3], b0[0], b0[1]);
        mma16(e1, a[0][0], a[0][1], a[0][2], a[0][3], b2[0], b2[1]);
        mma16(e2, a[0][0], a[0][1], a[0][2], a[0][3], b4[0], b4[1]);
        mma16(e0, a[1][0], a[1][1], a[1][2], a[1][3], b0[2], b0[3]);
        mma16(e1, a[1][0], a[1][1], a[1][2], a[1][3], b2[2], b2[3]);
        mma16(e2, a[1][0], a[1][1], a[1][2], a[1][3], b4[2], b4[3]);
        mma16(e0, a[2][0], a[2][1], a[2][2], a[2][3], b1[0], b1[1]);
        mma16(e1, a[2][0], a[2][1], a[2][2], a[2][3], b3[0], b3[1]);
        mma16(e2, a[2][0], a[2][1], a[2][2], a[2][3], b5[0], b5[1]);
        mma16(e0, a[3][0], a[3][1], a[3][2], a[3][3], b1[2], b1[3]);
        mma16(e1, a[3][0], a[3][1], a[3][2], a[3][3], b3[2], b3[3]);
        mma16(e2, a[3][0], a[3][1], a[3][2], a[3][3], b5[2], b5[3]);
        sts_f4(st, e0[0], e0[1], e0[2], 1.f);
        sts_f4(st + 512, e0[3], e1[0], e1[1], 1.f);
        sts_f4(st + 1024, e1[2], e1[3], n0 ? 0.f : e2[0], 1.f);
        if (n0 == 0) sts_f4(st + 1536, e2[1], e2[2], e2[3], 1.f);
        if (warp == 1) TS(19);
        asm volatile("fence.proxy.async.shared::cta;" ::: "memory");
        __syncwarp();
        if (lane == 0) mbar_arrive(bar + 8 * (B_T + (s & 1)));
      }
      if (s) token_pv(s - 1);
      if (warp == 1) TS(5);
      if (rec) {
        float d[16];
        if (warp == 1) TS(16);
        mbar_wait(bar + 8 * (B_X + ((s + 1) & 3)), ((s + 1) >> 2) & 1, lim);
        bar_sync(N_ZX, 256);
        if (warp == 1) TS(17);
        gemm_x_issue(w, sb + ((s + 1) & 3) * XB, d);
        wg_wait<0>();
        reg_fence(d);
        if (warp == 1) TS(18);
        const uint32_t zn = zst + ((s + 1) & 1) * 5120;
        stsm4t(zn + 8 * 16, pack2(d[0], d[1]), pack2(d[2], d[3]), pack2(d[4], d[5]), pack2(d[6], d[7]));
        stsm4t(zn + 24 * 16, pack2(d[8], d[9]), pack2(d[10], d[11]), pack2(d[12], d[13]), pack2(d[14], d[15]));
        __syncwarp();
        if (lane == 0) mbar_arrive(bar + 8 * (B_ZX + ((s + 1) & 1)));
        if (warp == 2) TS(3);
      }
    }
    token_send(NSEG - 2);
    bar_sync(N_ST, 256);
    token_pv(NSEG - 1);
    token_send(NSEG - 1);
    if (lim <= 0) g_err = 1;
    __syncwarp();
    if (warp == 0) PTS(25);
    cluster_arrive();
    cluster_wait();
  } else if (warp < 8) {
    asm volatile("setmaxnreg.inc.sync.aligned.u32 216;");
    const int wq = warp - 4;
    uint32_t w[28][4];
    build_weights<1>(w, sb, lim, lane);
    cluster_wait();
    cluster_arrive_relaxed();
    uint32_t yx[8], ym[2];
    {
      float d[16];
      mbar_wait(bar + 8 * B_X, 0, lim);
      gemm_x(w, sb, d);
#pragma unroll
      for (int i = 0; i < 8; i++) yx[i] = pack2(d[2 * i], d[2 * i + 1]);
      cluster_wait();
    }
    const int ri = lane >> 2, q = lane & 3;
    uint32_t zld = sb + O_Z + (((lane >> 4) | ((lane >> 2) & 2)) * 40 + 8 + 8 * wq + (lane & 7)) * 16;
    uint32_t rs_a = mapa(sb + O_RS + h * 128 + ((ri & 1) * 4 + q) * 16, 4 * wq + (ri >> 1));
    uint32_t rs_b = mapa(bar + 8 * B_RS, 4 * wq + (ri >> 1));
    uint32_t mimg = sb + O_MIMG + lane * 16, l8 = sb + lane * 8;
    float* p_smx = &g_xacc[0][h][wq * 128 + lane * 4];
    for (int k = wq; k < 22; k += 4) sts_u2(sb + O_GX + k * 256 + lane * 8, 0, 0);
    asm volatile("fence.proxy.async.shared::cta;" ::: "memory");
    bar_sync(N_INIT, 160);
    const uint32_t yb = sb + O_YB + (tid & 127) * 16;
    sts_u4(yb, yx[0], yx[4], yx[1], yx[5]);
    sts_u4(yb + 2048, yx[2], yx[6], yx[3], yx[7]);
    pin(zld); pin(rs_a); pin(rs_b); pin(mimg); pin(l8); pinp(p_smx);

    uint32_t zb0[4], zb1[4];
    mbar_wait(bar + 8 * B_ZX, 0, lim);
    ldsm4(zb0, zld);
    ldsm4(zb1, zld + 4 * 640);

#pragma unroll 1
    for (int s = 0; s < NSEG; s++) {
      const bool rec = s < NSEG - 1;
      uint32_t img = mimg + (s & 1) * 7168, tag = ((s >> 1) + 1) & 3;
      uint32_t ra = rs_a + (s & 1) * 2048, rb = rs_b + (s & 1) * 8;
      float* smx = p_smx + (s & 3) * (NH * 512);
      pin(img); pin(tag); pin(ra); pin(rb); pinp(smx);
      if (rec) {
        while (__all_sync(0xffffffffu, (int)lds32v(sb + O_C3) < s - 2) && --lim > 0) {}
        if (s) mbar_wait(bar + 8 * (B_M + (s & 1)), ((s - 1) >> 1) & 1, lim);
        uint32_t a0[4], a1[4];
        ldsm4(a0, img + j * 1024);
        ldsm4(a1, img + j * 1024 + 512);
        const uint32_t mxw = __vimax3_u32(__vimax3_u32(a0[0], a0[1], a0[2]), __vimax3_u32(a0[3], a1[0], a1[1]), max(a1[2], a1[3]));
        if (__builtin_expect(s && __any_sync(0xffffffffu, mxw == 0xffffffffu), 0)) {
          mbar_wait(bar + 8 * B_YM, s & 1, lim);
          ldsm4(a0, img + j * 1024);
          ldsm4(a1, img + j * 1024 + 512);
        }
        const float2 e = mma_rows8(a0, a1, zb0, zb1);
        asm volatile("red.relaxed.gpu.global.add.v4.f32 [%0], {%1,%2,%3,%4};" :: "l"(smx), "f"(e.x), "f"(e.y), "f"((float)(s + 1)), "f"(0.f) : "memory");
        if (wq == 0) TS(15);
      }
      if (wq == 0) TS(20);
      mbar_wait(bar + 8 * B_YM, s & 1, lim);
      float c[4];
      {
        const uint64_t dm = (uint64_t)(((sb + O_MIMG + (s & 1) * 7168) >> 4) & 0x3fff) | (8ull << 16) | (8ull << 32);
        wg_fence();
#pragma unroll
        for (int k = 0; k < 28; k++) wgmma_n8_rs(c, w[k], dm + k * 16, k != 0);
        wg_commit();
        bar_arrive(N_REDO, 256);
        if (wq == 0) TS(21);
      }
      float v[4][4], mxl = 0.f;
      if (rec) {
        const float full = 7.f * (s + 1);
        do {
#pragma unroll
          for (int n = 0; n < 4; n++)
            asm volatile("ld.volatile.shared.v4.f32 {%0,%1,%2,%3}, [%4];" : "=f"(v[n][0]), "=f"(v[n][1]), "=f"(v[n][2]), "=f"(v[n][3]) : "r"(mimg + (O_GY - O_MIMG) + n * 512) : "memory");
        } while (__any_sync(0xffffffffu, (v[0][2] + v[0][3] != full) | (v[1][2] + v[1][3] != full) | (v[2][2] + v[2][3] != full) | (v[3][2] + v[3][3] != full)) && --lim > 0);
        sts32v(sb + O_DONE + 8, s + 1);
        mxl = fmaxf(fmaxf(fmaxf(v[0][0], v[0][1]), fmaxf(v[1][0], v[1][1])), fmaxf(fmaxf(v[2][0], v[2][1]), fmaxf(v[3][0], v[3][1])));
        if (wq == 0) TS(22);
      }
      wg_wait<0>();
      reg_fence(c);
      ym[0] = pack2(c[0], c[1]);
      ym[1] = pack2(c[2], c[3]);
      if (rec) {
        uint32_t vm[14];
        const uint32_t gx = l8 + O_GX + (s & 1) * 1792;
        do {
#pragma unroll
          for (int k = 0; k < 7; k++) asm volatile("ld.volatile.shared.v2.u32 {%0,%1}, [%2];" : "=r"(vm[2 * k]), "=r"(vm[2 * k + 1]) : "r"(gx + k * 256) : "memory");
        } while (__any_sync(0xffffffffu, stale7(vm, tag)) && --lim > 0);
        const float2 sm = add7(vm);
        if (wq == 0) TS(8);
        const float mx = qmax(fmaxf(mxl, fmaxf(sm.x, sm.y)));
        const float nb = -mx * SC2;
        uint32_t pa[4];
        float l = 0.f;
#pragma unroll
        for (int n = 0; n < 4; n++) {
          const float p0 = ex2(fmaf(v[n][0], SC2, nb)), p1 = ex2(fmaf(v[n][1], SC2, nb));
          l += p0 + p1;
          pa[n] = pack2(p0, p1);
        }
        float o0[4] = {0.f, 0.f, 0.f, 0.f}, o1[4] = {0.f, 0.f, 0.f, 0.f}, u0[4] = {0.f, 0.f, 0.f, 0.f}, u1[4] = {0.f, 0.f, 0.f, 0.f};
        mma16v(o0, pa[0], pa[1], pa[2], pa[3], yx[0], yx[4]);
        mma16v(o1, pa[0], pa[1], pa[2], pa[3], yx[1], yx[5]);
        mma16v(u0, pa[0], pa[1], pa[2], pa[3], yx[2], yx[6]);
        mma16v(u1, pa[0], pa[1], pa[2], pa[3], yx[3], yx[7]);
        const float p0 = ex2(fmaf(sm.x, SC2, nb)), p1 = ex2(fmaf(sm.y, SC2, nb));
        const uint32_t pp = pack2(p0, p1);
        mma8v(o0, pp, pp, ym[0]);
        mma8v(o1, pp, pp, ym[1]);
        const float inv = rcp(qsum(l + (p0 + p1)));
        st_async4(ra, (o0[0] + u0[2]) * inv, (o0[1] + u0[3]) * inv, (o1[0] + u1[2]) * inv, (o1[1] + u1[3]) * inv, rb);
        sts32v(sb + O_DONE, s + 1);
      }
      sts_u2(yb + 4096 - (tid & 127) * 8 + (s & 1) * 5120, ym[0], ym[1]);
      if (!rec) bar_arrive(N_ST, 256);
      if (rec) {
        bar_arrive(N_ZX, 256);
        if (wq == 0) TS(9);
      }
      if (rec) {
        float d[16];
        mbar_wait(bar + 8 * (B_X + ((s + 1) & 3)), ((s + 1) >> 2) & 1, lim);
        gemm_x(w, sb + ((s + 1) & 3) * XB, d);
#pragma unroll
        for (int i = 0; i < 8; i++) yx[i] = pack2(d[2 * i], d[2 * i + 1]);
        sts_u4(yb + ((s + 1) & 1) * 5120, yx[0], yx[4], yx[1], yx[5]);
        sts_u4(yb + ((s + 1) & 1) * 5120 + 2048, yx[2], yx[6], yx[3], yx[7]);
        mbar_wait(bar + 8 * (B_ZX + ((s + 1) & 1)), ((s + 1) >> 1) & 1, lim);
        ldsm4(zb0, zld + ((s + 1) & 1) * 5120);
        ldsm4(zb1, zld + ((s + 1) & 1) * 5120 + 4 * 640);
        if (wq == 0) TS(10);
      }
    }
    if (lim <= 0) g_err = 1;
    __syncwarp();
    cluster_arrive();
    cluster_wait();
  } else {
    asm volatile("setmaxnreg.dec.sync.aligned.u32 72;");
    if (warp == 8) {
      const int u = lane >> 2, comp = lane & 3;
      uint8_t* gm0 = xch(16) + (XC_R0 + (8 * j + 2 * (h >> 2) + (comp >> 1)) * 128 + (2 * (h & 3) + (u >> 2)) * 16 + ((u & 3) * 2 + (comp & 1)) * 2);
#pragma unroll
      for (int k = 0; k < 6; k++) stg16r(gm0 + k * XC_TWIN, 0xffff);
      cluster_wait();
      if (lane == 0) {
        int lim1 = SPIN_LIMIT;
        if (h < 7) tma2d_mc(sb + h * 4096, &tmX, h * 64, 0, bar + 8 * B_X);
#pragma unroll 1
        for (int c = 4; c < 16; c++) {
          const int st = c & 3;
          mbar_wait1(bar + 8 * (B_PE + st), ((c >> 2) - 1) & 1, lim1);
          mbar_expect(bar + 8 * (B_PF + st), XB);
          tma2d(sb + (st + 1) * XB, (c & 1) ? &tmWv : &tmWk, h * DH + ((c >> 1) & 3) * 64, (c >> 3) * 224, bar + 8 * (B_PF + st));
        }
      }
      __syncwarp();
      cluster_arrive();
      cluster_wait();
      if (lane == 0) {
        for (int k = 1; k < 3; k++) {
          mbar_expect(bar + 8 * (B_X + k), XB);
          if (h < 7) tma2d_mc(sb + k * XB + h * 4096, &tmX, h * 64, k * 32, bar + 8 * (B_X + k));
        }
      }
      uint32_t chk = sb + O_MIMG + lane * 32 + (lane >> 2) * 4, rs0 = sb + O_RS + lane * 4;
      const uint8_t* gnear = xch(16) + (XC_R0 + __shfl_sync(0xffffffffu, lds32v(sb + O_NEAR + 4), 0));
      pin(chk); pin(rs0); pinp(gm0);
      const uint32_t m2r = mapa(bar + 8 * (B_M2 + 1), lane & 15);
      auto cl_sync_arrive = [&](uint32_t a) { if (lane < 16) asm volatile("mbarrier.arrive.relaxed.cluster.shared::cluster.b64 _, [%0];" :: "r"(a) : "memory"); __syncwarp(); };
      const uint8_t* p_gsrc = xch(h) + (XC_R0 + 2 * XC_REG + __shfl_sync(0xffffffffu, lds32v(sb + O_NEAR), 0));
      bar_sync(N_INIT, 160);
      uint32_t m2p = 0;
      int s3 = 0;
#pragma unroll 1
      for (int s = 0; s < NSEG; s++) {
        uint32_t ck = chk + (s & 1) * 7168;
        pin(ck);
        bool redo = false;
        if (s) {
          mbar_wait(bar + 8 * (B_M + (s & 1)), ((s - 1) >> 1) & 1, lim);
          while (true) {
            uint32_t v[7];
#pragma unroll
            for (int k = 0; k < 7; k++) v[k] = lds32v(ck + k * 1024);
            const uint32_t mx = __vimax3_u32(__vimax3_u32(v[0], v[1], v[2]), __vimax3_u32(v[3], v[4], v[5]), v[6]);
            if (__builtin_expect(!__any_sync(0xffffffffu, mx == 0xffffffffu) || lim <= 0, 1)) break;
            redo = true;
            cl_sync_arrive(m2r);
            if (elect()) mbar_expect(bar + 8 * B_M2, 7168);
            mbar_wait(bar + 8 * (B_M2 + 1), m2p, lim);
            if (elect()) bulk_mc(sb + O_MIMG + (s & 1) * 7168 + h * 448, gnear + s3 * XC_REG + h * 448, 448, bar + 8 * B_M2);
            mbar_wait(bar + 8 * B_M2, m2p, lim);
            m2p ^= 1;
          }
        }
        TS(23);
        if (bar_or(N_ZM, 160, redo)) bar_or(N_ZM, 160, false);
        if (s == NSEG - 1) break;
        {
          const uint32_t tz = clk();
          const uint8_t* gsrc = p_gsrc + (s & 1) * 1792;
          const bool el = elect();
          uint32_t td = D_S;
          bool xd = false;
          do {
            delay_until(tz, td);
            if (el) {
              asm volatile("mbarrier.expect_tx.relaxed.cta.shared::cta.b64 [%0], %1;" :: "r"(bar + 8 * B_G), "r"(xd ? 1792 : 3840) : "memory");
              bulk_ld(sb + O_GX + (s & 1) * 1792, gsrc, 1792, bar + 8 * B_G);
              if (!xd) bulk_ld(sb + O_GY, &g_xacc[s & 3][h][0], 2048, bar + 8 * B_G);
            }
            td += D_SS;
            xd = __all_sync(0xffffffffu, (int)lds32v(sb + O_DONE + 8) > s);
          } while (__all_sync(0xffffffffu, (int)lds32v(sb + O_DONE) <= s) && --lim > 0);
        }
        const int s3n = s3 == 2 ? 0 : s3 + 1;
        uint32_t rb = rs0 + (s & 1) * 2048;
        uint8_t* gm = gm0 + s3n * XC_REG;
        const uint32_t mdst = sb + O_MIMG + ((s + 1) & 1) * 7168 + h * 448, mb = bar + 8 * (B_M + ((s + 1) & 1));
        const uint8_t* msrc = gnear + s3n * XC_REG + h * 448;
        s3 = s3n;
        pin(rb); pinp(gm);
        mbar_wait(bar + 8 * (B_RS + (s & 1)), (s >> 1) & 1, lim);
        TS(11);
        float v[16];
#pragma unroll
        for (int k = 0; k < 16; k++) v[k] = lds_f(rb + k * 128);
        const float sum = (((v[0] + v[1]) + (v[2] + v[3])) + ((v[4] + v[5]) + (v[6] + v[7]))) +
                          (((v[8] + v[9]) + (v[10] + v[11])) + ((v[12] + v[13]) + (v[14] + v[15])));
        stg16r(gm, (uint16_t)(pack2(sum, 0.f) & 0xffff));
        stg16r(gm + XC_TWIN, (uint16_t)(pack2(sum, 0.f) & 0xffff));
        const uint32_t tm = clk();
        TS(12);
        const bool el = elect();
        if (el) mbar_expect(bar + 8 * (B_RS + (s & 1)), 2048);
        delay_until(tm, D_M);
        TS(25);
        if (el) bulk_mc(mdst, msrc, 448, mb);
      }
      if (elect()) mbar_arrive(bar + 8 * B_G);
      mbar_wait(bar + 8 * B_G, 0, lim);
    } else if (warp < 11) {
      const int mt = warp - 9, q = lane & 3;
#pragma unroll 1
      for (int t = mt * 32 + lane; t < 448; t += 64) {
        const uint4 v = *reinterpret_cast<const uint4*>(mem0 + (t & 7) * DM + (t >> 3) * 8);
        sts_u4(sb + O_MIMG + t * 16, v.x, v.y, v.z, v.w);
      }
      asm volatile("fence.proxy.async.shared::cta;" ::: "memory");
      if (mt == 1 && lane == 0) sts32v(sb + O_NEAR + 4, near_copy(xch(16) + 2 * XC_REG - (blockIdx.x % 7) * 128));
      __syncwarp();
      cluster_wait();
      cluster_arrive();
      cluster_wait();
      uint8_t* gm0 = xch(16) + (XC_R0 + (8 * j + 2 * (h >> 2) + (q >> 1)) * 128 + (2 * (h & 3) + (lane >> 4)) * 16 + (((lane >> 2) & 3) * 2 + (q & 1)) * 2);
      int s3p = 2;
#pragma unroll 1
      for (int s = 0; s < NSEG; s++) {
        mbar_wait(bar + 8 * (B_T + (s & 1)), (s >> 1) & 1, lim);
        if (s < NSEG - 1) while (__all_sync(0xffffffffu, (int)lds32v(sb + O_DONE) <= s) && --lim > 0) delay_until(clk(), 64);
        if (mt == 1 && s < NSEG - 1) {
          if (elect()) {
            mbar_expect(bar + 8 * (B_M + ((s + 1) & 1)), 7168);
            if (s >= 1 && s + 2 < NSEG) {
              mbar_expect(bar + 8 * (B_X + ((s + 2) & 3)), XB);
              if (h < 7) tma2d_mc(sb + ((s + 2) & 3) * XB + h * 4096, &tmX, h * 64, (s + 2) * 32, bar + 8 * (B_X + ((s + 2) & 3)));
            }
          }
          stg16r(gm0 + s3p * XC_REG, 0xffff);
          stg16r(gm0 + s3p * XC_REG + XC_TWIN, 0xffff);
          s3p = s3p == 2 ? 0 : s3p + 1;
        }
        const uint32_t t0 = clk();
        if (mt == 0 && elect()) {
          asm volatile("cp.reduce.async.bulk.global.shared::cta.bulk_group.add.f32 [%0], [%1], 5632;" :: "l"(&g_sacc[s & 7][h][0]), "r"(sb + O_ST + (s & 1) * 5632) : "memory");
          asm volatile("cp.async.bulk.commit_group;" ::: "memory");
          asm volatile("cp.async.bulk.wait_group.read 0;" ::: "memory");
        }
        __syncwarp();
        delay_until(t0, D_T);
        if (mt) TS(28);
        const float4* sp = reinterpret_cast<const float4*>(&g_sacc[s & 7][h][mt * 512 + lane * 4]);
        float u[7][4];
        bool stale;
        do {
          stale = false;
#pragma unroll
          for (int c = 0; c < 7; c++) {
            u[c][0] = u[c][1] = u[c][2] = 0.f; u[c][3] = 7.f;
            if (c < 4 || mt)
              asm volatile("ld.relaxed.gpu.global.v4.f32 {%0,%1,%2,%3}, [%4];" : "=f"(u[c][0]), "=f"(u[c][1]), "=f"(u[c][2]), "=f"(u[c][3]) : "l"(sp + c * 32) : "memory");
          }
#pragma unroll
          for (int c = 0; c < 7; c++) stale |= u[c][3] != 7.f;
        } while (__any_sync(0xffffffffu, stale) && --lim > 0);
        if (mt) TS(29);
        uint32_t pk[2][5];
        float v[2][10];
#pragma unroll
        for (int e = 0; e < 10; e++) {
          const int i = 4 * (e >> 1) + (e & 1);
          v[0][e] = u[i / 3][i % 3];
          v[1][e] = u[(i + 2) / 3][(i + 2) % 3];
        }
#pragma unroll
        for (int rg = 0; rg < 2; rg++) {
          const int row = 16 * mt + 8 * rg + (lane >> 2);
#pragma unroll
          for (int e = 2; e < 10; e++)
            if (8 * ((e >> 1) - 1) + 2 * q + (e & 1) > row) v[rg][e] = MASKV;
          float mx = v[rg][0];
#pragma unroll
          for (int e = 1; e < 10; e++) mx = fmaxf(mx, v[rg][e]);
          mx = qmax(mx);
          const float nb = -mx * SC2;
          float l = 0.f;
#pragma unroll
          for (int e = 0; e < 10; e++) { v[rg][e] = ex2(fmaf(v[rg][e], SC2, nb)); l += v[rg][e]; }
          const float inv = rcp(qsum(l));
#pragma unroll
          for (int n = 0; n < 5; n++) pk[rg][n] = pack2(v[rg][2 * n] * inv, v[rg][2 * n + 1] * inv);
        }
        const uint32_t pb = sb + O_P + (s & 1) * 2560 + mt * 1280;
        sts_u4(pb + lane * 16, pk[0][1], pk[1][1], pk[0][3], pk[1][3]);
        sts_u4(pb + 512 + lane * 16, pk[0][2], pk[1][2], pk[0][4], pk[1][4]);
        sts_u2(pb + 1024 + lane * 8, pk[0][0], pk[1][0]);
        __syncwarp();
        if (lane == 0) mbar_arrive(bar + 8 * (B_P + (s & 1)));
        if (mt == 1) TS(13);
        if (j + 7 * mt < 11) asm volatile("st.relaxed.gpu.global.v4.f32 [%0], {%1,%1,%1,%1};" :: "l"(&g_sacc[(s + 4) & 7][h][(j + 7 * mt) * 128 + lane * 4]), "f"(0.f) : "memory");
      }
    } else {
      const int t1 = lane >> 4, l16 = lane & 15;
      const int col = j * 64 + ((lane >> 2) & 3) * 16 + (lane & 3) * 2;
      const uint32_t epoch = ldg1r(&g_ticket[0]) / 112 + 1;
      if (lane == 0) {
        sts32v(sb + O_NEAR, near_copy(xch(h)));
      }
      __syncwarp();
      cluster_wait();
      cluster_arrive();
      cluster_wait();
      const int trow = 16 * (h >> 3) + (h & 7) + 8 * t1;
      const uint32_t xg = sb + trow * 128 + (((l16 >> 1) ^ (trow & 7)) << 4) + (l16 & 1) * 8;
      auto gate = [&](int sg) {
        mbar_wait(bar + 8 * (B_X + (sg & 3)), (sg >> 2) & 1, lim);
        float z = 0.f;
#pragma unroll 1
        for (int k = 0; k < 7; k++) {
          const uint2 xv = lds_u2(xg + (sg & 3) * XB + k * 4096);
          const uint2 gw = *reinterpret_cast<const uint2*>(gate_w + (k * 16 + l16) * 4);
          z = fmaf(bf_lo(xv.x), bf_lo(gw.x), z); z = fmaf(bf_hi(xv.x), bf_hi(gw.x), z);
          z = fmaf(bf_lo(xv.y), bf_lo(gw.y), z); z = fmaf(bf_hi(xv.y), bf_hi(gw.y), z);
        }
#pragma unroll
        for (int o = 1; o < 16; o <<= 1) z += __shfl_xor_sync(0xffffffffu, z, o);
        return rcp(1.f + ex2(-1.4426950408889634f * z));
      };
      float4 pa4 = make_float4(0.f, 0.f, 0.f, 0.f);
      bool pend = false;
      auto finish = [&](int sg) {
        if (ldg1r(&g_bflag[sg >> 1][j >> 2][0]) == epoch) {
          const int o = (sg * 32 + trow) * DM + col;
          uint32_t b0, b1, b2, b3;
          ldg2r(b0, b1, g_b + o); ldg2r(b2, b3, g_b + o + 8);
          uint32_t* op = reinterpret_cast<uint32_t*>(out + o);
          op[0] = pack2(pa4.x + __uint_as_float(b0), pa4.y + __uint_as_float(b1));
          op[4] = pack2(pa4.z + __uint_as_float(b2), pa4.w + __uint_as_float(b3));
        }
      };
      float g1 = gate(0), g2 = gate(1);
#pragma unroll 1
      for (int s = 0; s < NSEG; s++) {
        const int tok = s * 32 + trow;
        const bool have_b = ldg1r(&g_bflag[s >> 1][j >> 2][0]) == epoch;
        const float* bp = &g_b[tok * DM + col];
        uint32_t b0 = 0, b1 = 0, b2 = 0, b3 = 0;
        if (have_b) { ldg2r(b0, b1, bp); ldg2r(b2, b3, bp + 8); }
        const bool last = s >= NSEG - 2;
        mbar_wait(bar + 8 * ((last ? B_OL : B_O) + (s & 1)), last ? 0 : (s >> 1) & 1, lim);
        if (pend) { if (s >= NSEG - 2) __threadfence(); finish(s - 1); }
        if (lane < 19 && j * 19 + lane < 128)
          asm volatile("st.relaxed.gpu.global.v4.f32 [%0], {%1,%1,%1,%1};" :: "l"(&g_xacc[s & 3][h][(j * 19 + lane) * 4]), "f"(0.f) : "memory");
        const float g = g1;
        g1 = g2;
        if (s + 2 < NSEG) g2 = gate(s + 2);
        const uint32_t ob = sb + O_ORS + ((last ? 2 : 0) + (s & 1)) * 4096 + t1 * 2048 + l16 * 16;
        float e[8] = {0.f, 0.f, 0.f, 0.f, 0.f, 0.f, 0.f, 0.f};
#pragma unroll 2
        for (int k = 0; k < 8; k++) {
          const uint4 c = lds_u4(ob + k * 256);
          e[0] += bf_lo(c.x); e[1] += bf_hi(c.x); e[2] += bf_lo(c.y); e[3] += bf_hi(c.y);
          e[4] += bf_lo(c.z); e[5] += bf_hi(c.z); e[6] += bf_lo(c.w); e[7] += bf_hi(c.w);
        }
        float4 a;
        a.x = g * ((t1 ? e[4] : e[0]) + __shfl_xor_sync(0xffffffffu, t1 ? e[0] : e[4], 16));
        a.y = g * ((t1 ? e[5] : e[1]) + __shfl_xor_sync(0xffffffffu, t1 ? e[1] : e[5], 16));
        a.z = g * ((t1 ? e[6] : e[2]) + __shfl_xor_sync(0xffffffffu, t1 ? e[2] : e[6], 16));
        a.w = g * ((t1 ? e[7] : e[3]) + __shfl_xor_sync(0xffffffffu, t1 ? e[3] : e[7], 16));
        __syncwarp();
        if (lane == 0 && s < NSEG - 4) mbar_expect(bar + 8 * (B_O + (s & 1)), 4096);
        if (lane == 0) sts32v(sb + O_C3, s + 1);
        float* sp = &g_stash[tok * DM + col];
        stg2r(sp, tagf(a.x, epoch & 3), tagf(a.y, epoch & 3));
        stg2r(sp + 8, tagf(a.z, epoch & 3), tagf(a.w, epoch & 3));
        if (have_b) {
          uint32_t* op = reinterpret_cast<uint32_t*>(out + tok * DM + col);
          op[0] = pack2(a.x + __uint_as_float(b0), a.y + __uint_as_float(b1));
          op[4] = pack2(a.z + __uint_as_float(b2), a.w + __uint_as_float(b3));
        }
        pend = !have_b;
        pa4 = a;
        TS(14);
      }
      if (pend) { __threadfence(); finish(NSEG - 1); }
      if (lane == 0) atomicAdd(&g_ticket[0], 1);
    }
    if (lim <= 0) g_err = 1;
    __syncwarp();
    cluster_arrive();
    cluster_wait();
  }
}

constexpr uint32_t F_STAGE = 49152, F_BAR = 4 * F_STAGE, F_G = F_BAR + 128, F_M = F_G + 512, F_SMEM = F_M + 1024 + 1024;

template <int N>
DEVI void ffn_tile(float (&d)[N / 2], uint32_t sb, int wg, int nk, int& it, int& dead, int lane) {
#pragma unroll 1
  for (int k = 0; k < nk; k++, it++) {
    const int st = it & 3;
    mbar_wait(sb + F_BAR + 8 * st, (it >> 2) & 1, dead);
    const uint64_t da = desc128(sb + st * F_STAGE + wg * 8192, 1), db = desc128(sb + st * F_STAGE + 16384, 512);
    wg_fence();
#pragma unroll
    for (int kk = 0; kk < 4; kk++) {
      if constexpr (N == 256) wgmma_n256_kn(d, da + kk * 2, db + kk * 128, (k | kk) != 0);
      else                    wgmma_n192_kn(d, da + kk * 2, db + kk * 128, (k | kk) != 0);
    }
    wg_commit();
    if (k) { wg_wait<1>(); if (lane == 0) mbar_arrive(sb + F_BAR + 32 + 8 * ((it - 1) & 3)); }
  }
  wg_wait<0>();
  if (lane == 0) mbar_arrive(sb + F_BAR + 32 + 8 * ((it - 1) & 3));
  reg_fence(d);
}

template <int NJ>
DEVI void ffn_finish(float (&d)[NJ * 32], float g0, float g1, uint32_t sb, int r0, int row, int j0, uint32_t epoch,
                     __nv_bfloat16* __restrict__ out, int tid) {
  const int wg = tid >> 7, t = tid & 127, off = (r0 + row) * DM + j0 * 64 + 2 * (tid & 3);
#pragma unroll
  for (int n = 0; n < NJ * 8; n++) {
    d[4 * n] *= g0; d[4 * n + 1] *= g0; d[4 * n + 2] *= g1; d[4 * n + 3] *= g1;
    *reinterpret_cast<float2*>(g_b + off + n * 8) = make_float2(d[4 * n], d[4 * n + 1]);
    *reinterpret_cast<float2*>(g_b + off + 8 * DM + n * 8) = make_float2(d[4 * n + 2], d[4 * n + 3]);
  }
  asm volatile("fence.release.gpu;" ::: "memory");
  bar_sync(2 + wg, 128);
  if (t == 0) {
    asm volatile("st.relaxed.gpu.global.u32 [%0], %1;" :: "l"(&g_bflag[(r0 >> 6) + wg][j0 >> 2][0]), "r"(epoch) : "memory");
    __threadfence();
  }
  bar_sync(2 + wg, 128);
#pragma unroll
  for (int n0 = 0; n0 < NJ * 8; n0 += 8) {
    uint32_t a[8][4];
#pragma unroll
    for (int n = 0; n < 8; n++) { ldg2r(a[n][0], a[n][1], g_stash + off + (n0 + n) * 8); ldg2r(a[n][2], a[n][3], g_stash + off + 8 * DM + (n0 + n) * 8); }
#pragma unroll
    for (int n = 0; n < 8; n++)
#pragma unroll
      for (int half = 0; half < 2; half++)
        if (((a[n][2 * half] ^ epoch) & 3) == 0)
          *reinterpret_cast<uint32_t*>(out + off + half * 8 * DM + (n0 + n) * 8) =
              pack2(__uint_as_float(a[n][2 * half]) + d[4 * (n0 + n) + 2 * half], __uint_as_float(a[n][2 * half + 1]) + d[4 * (n0 + n) + 2 * half + 1]);
  }
}

__global__ void __launch_bounds__(384, 1)
ffn_kernel(const __grid_constant__ CUtensorMap tmX, const __grid_constant__ CUtensorMap tmW1,
           const __grid_constant__ CUtensorMap tmH, const __grid_constant__ CUtensorMap tmW2,
           const __nv_bfloat16* __restrict__ x, const __nv_bfloat16* __restrict__ gate_w, __nv_bfloat16* __restrict__ out) {
  extern __shared__ uint8_t smem_raw[];
  const uint32_t sb = (smem_u32(smem_raw) + 1023) & ~1023u;
  const uint32_t hbar = sb + F_BAR + 64;
  int dead = SPIN_LIMIT;
  const int tid = threadIdx.x, lane = tid & 31, warp = __shfl_sync(0xffffffffu, tid >> 5, 0), r0 = blockIdx.x * 128;
  if (tid == 0) {
    for (int i = 0; i < 4; i++) { mbar_init(sb + F_BAR + 8 * i, 1); mbar_init(sb + F_BAR + 32 + 8 * i, 8); }
    mbar_init(hbar, 256);
    asm volatile("fence.mbarrier_init.release.cluster;" ::: "memory");
    asm volatile("fence.proxy.async.shared::cta;" ::: "memory");
  }
  __syncthreads();
  if (warp >= 8) {
    asm volatile("setmaxnreg.dec.sync.aligned.u32 56;");
    if (tid == 256) {
      int it = 0;
#pragma unroll 1
      for (int t = 0; t < 9; t++) {
        const int nk = t < 7 ? 7 : 28, nb = t < 8 ? 4 : 3;
        if (t == 7) mbar_wait1(hbar, 0, dead);
#pragma unroll 1
        for (int k = 0; k < nk; k++, it++) {
          const int st = it & 3;
          const uint32_t fb = sb + F_BAR + 8 * st, a = sb + st * F_STAGE;
          if (it >= 4) mbar_wait1(fb + 32, ((it >> 2) - 1) & 1, dead);
          mbar_expect(fb, 16384 + nb * 8192);
          tma2d(a, t < 7 ? &tmX : &tmH, k * 64, r0, fb);
          for (int b = 0; b < nb; b++) tma2d(a + 16384 + b * 8192, t < 7 ? &tmW1 : &tmW2, (t < 7 ? t : t - 7) * 256 + b * 64, k * 64, fb);
        }
      }
    } else if (warp > 8) {
      const int l16 = lane & 15;
      for (int r = (warp - 9) * 2 + (lane >> 4); r < 132; r += 6) {
        const int rr = r < 128 ? r : 127;
        float z = 0.f;
#pragma unroll
        for (int k = 0; k < 7; k++) {
          const uint2 xv = *reinterpret_cast<const uint2*>(x + (r0 + rr) * DM + (k * 16 + l16) * 4);
          const uint2 gv = *reinterpret_cast<const uint2*>(gate_w + (k * 16 + l16) * 4);
          z = fmaf(bf_lo(xv.x), bf_lo(gv.x), z); z = fmaf(bf_hi(xv.x), bf_hi(gv.x), z);
          z = fmaf(bf_lo(xv.y), bf_lo(gv.y), z); z = fmaf(bf_hi(xv.y), bf_hi(gv.y), z);
        }
#pragma unroll
        for (int o = 1; o < 16; o <<= 1) z += __shfl_xor_sync(0xffffffffu, z, o);
        if (l16 == 0) sts32v(sb + F_G + rr * 4, __float_as_uint(1.f - rcp(1.f + ex2(-1.4426950408889634f * z))));
      }
      __syncwarp();
      bar_arrive(1, 352);
    }
  } else {
    asm volatile("setmaxnreg.inc.sync.aligned.u32 224;");
    const int wg = warp >> 2, row = wg * 64 + (warp & 3) * 16 + (lane >> 2), q = lane & 3;
    const uint32_t epoch = (ldg1r(&g_ticket[1]) >> 4) + 1;
    int it = 0;
#pragma unroll 1
    for (int t = 0; t < 7; t++) {
      float d[128];
      ffn_tile<256>(d, sb, wg, 7, it, dead, lane);
      __nv_bfloat16* hp = g_h + (size_t)(r0 + row) * DFF + t * 256 + 2 * q;
#pragma unroll
      for (int n = 0; n < 32; n++) {
        *reinterpret_cast<uint32_t*>(hp + n * 8) = pack2(fmaxf(d[4 * n], 0.f), fmaxf(d[4 * n + 1], 0.f));
        *reinterpret_cast<uint32_t*>(hp + 8 * DFF + n * 8) = pack2(fmaxf(d[4 * n + 2], 0.f), fmaxf(d[4 * n + 3], 0.f));
      }
    }
    __threadfence();
    asm volatile("fence.proxy.async;" ::: "memory");
    mbar_arrive(hbar);
    bar_sync(1, 352);
    const float g0 = lds_f(sb + F_G + row * 4), g1 = lds_f(sb + F_G + row * 4 + 32);
    {
      float d[128];
      ffn_tile<256>(d, sb, wg, 28, it, dead, lane);
      ffn_finish<4>(d, g0, g1, sb, r0, row, 0, epoch, out, tid);
    }
    {
      float d[96];
      ffn_tile<192>(d, sb, wg, 28, it, dead, lane);
      ffn_finish<3>(d, g0, g1, sb, r0, row, 4, epoch, out, tid);
    }
    bar_sync(1, 256);
    if (tid == 0) atomicAdd(&g_ticket[1], 1);
    if (dead <= 0) g_err = 1;
  }
}

typedef CUresult (*EncodeFn)(CUtensorMap*, CUtensorMapDataType, cuuint32_t, void*, const cuuint64_t*, const cuuint64_t*,
                             const cuuint32_t*, const cuuint32_t*, CUtensorMapInterleave, CUtensorMapSwizzle,
                             CUtensorMapL2promotion, CUtensorMapFloatOOBfill);

void make_map(EncodeFn fn, CUtensorMap* m, const void* p, uint64_t rows, uint64_t cols, uint32_t box_rows) {
  const cuuint64_t dims[2] = {cols, rows}, strides[1] = {cols * 2};
  const cuuint32_t box[2] = {64, box_rows}, es[2] = {1, 1};
  fn(m, CU_TENSOR_MAP_DATA_TYPE_BFLOAT16, 2, const_cast<void*>(p), dims, strides, box, es, CU_TENSOR_MAP_INTERLEAVE_NONE,
     CU_TENSOR_MAP_SWIZZLE_128B, CU_TENSOR_MAP_L2_PROMOTION_L2_256B, CU_TENSOR_MAP_FLOAT_OOB_FILL_NONE);
}

}

extern "C" void kernel_launch(void* const* d_in, const int* in_sizes, int n_in, void* d_out, int out_size) {
  (void)in_sizes; (void)n_in; (void)out_size;
  const __nv_bfloat16* x = (const __nv_bfloat16*)d_in[0];
  const __nv_bfloat16* mem0 = (const __nv_bfloat16*)d_in[1];
  const __nv_bfloat16* gate_w = (const __nv_bfloat16*)d_in[10];
  static EncodeFn fn = nullptr;
  static void* hptr = nullptr;
  if (!fn) {
    cudaDriverEntryPointQueryResult qr;
    cudaGetDriverEntryPoint("cuTensorMapEncodeTiled", (void**)&fn, cudaEnableDefault, &qr);
    cudaGetSymbolAddress(&hptr, g_h);
    cudaFuncSetAttribute(rmt_kernel, cudaFuncAttributeMaxDynamicSharedMemorySize, T_SMEM);
    cudaFuncSetAttribute(rmt_kernel, cudaFuncAttributeNonPortableClusterSizeAllowed, 1);
    cudaFuncSetAttribute(ffn_kernel, cudaFuncAttributeMaxDynamicSharedMemorySize, F_SMEM);
  }
  CUtensorMap mWq, mWk, mWv, mWo, mX, mXf, mW1, mH, mW2;
  make_map(fn, &mWq, d_in[2], DM, NH * DH, 64);
  make_map(fn, &mWk, d_in[3], DM, NH * DH, 224);
  make_map(fn, &mWv, d_in[4], DM, NH * DH, 224);
  make_map(fn, &mWo, d_in[5], NH * DH, DM, 256);
  make_map(fn, &mX, x, SEQ, DM, 32);
  make_map(fn, &mXf, x, SEQ, DM, 128);
  make_map(fn, &mW1, d_in[8], DM, DFF, 64);
  make_map(fn, &mH, hptr, SEQ, DFF, 128);
  make_map(fn, &mW2, d_in[9], DFF, DM, 64);

  cudaLaunchConfig_t cfg = {};
  cudaLaunchAttribute at[1];
  cfg.gridDim = dim3(112); cfg.blockDim = dim3(384); cfg.dynamicSmemBytes = T_SMEM; cfg.stream = cudaStreamPerThread;
  at[0].id = cudaLaunchAttributeClusterDimension;
  at[0].val.clusterDim.x = 16; at[0].val.clusterDim.y = 1; at[0].val.clusterDim.z = 1;
  cfg.attrs = at; cfg.numAttrs = 1;
  cudaLaunchKernelEx(&cfg, rmt_kernel, mWq, mWk, mWv, mWo, mX, x, mem0, gate_w, (__nv_bfloat16*)d_out);

  cfg.gridDim = dim3(16); cfg.dynamicSmemBytes = F_SMEM;
  at[0].id = cudaLaunchAttributeProgrammaticStreamSerialization;
  at[0].val.programmaticStreamSerializationAllowed = 1;
  cudaLaunchKernelEx(&cfg, ffn_kernel, mXf, mW1, mH, mW2, x, gate_w, (__nv_bfloat16*)d_out);
}
```

```cpp
#include <cuda_runtime.h>
#include <cuda_bf16.h>
#include <cuda.h>
#include <stdint.h>

namespace {

#define DEVI __device__ __forceinline__

constexpr int SEQ = 2048, DM = 448, NH = 16, DH = 256, NSEG = 64, DFF = 1792;
constexpr float SC2 = 1.4426950408889634f / 16.0f;
constexpr float MASKV = -1.6e10f;
constexpr int SPIN_LIMIT = 1 << 22;

#define D_M 500
#define D_X 300
#define D_T 700
#define D_SS 150
#define O_SEND 1
#define XP 2
#define D_SQ 30
#define D_XS 220
#define SD0 1
#define XEV 1
#define PFM 1
#define D_TL 450
#define D_S 30

__device__ __align__(1024) uint8_t g_xch_raw[18 * 65536];
DEVI uint8_t* xch(int blk) { return reinterpret_cast<uint8_t*>((reinterpret_cast<uintptr_t>(g_xch_raw) + 65535) & ~(uintptr_t)65535) + blk * 65536; }
constexpr uint32_t XC_R0 = 4096, XC_REG = 16384, XC_TWIN = 8192;
__device__ __align__(1024) float g_xacc[4][NH][512];
__device__ __align__(1024) float g_sacc[8][NH][1408];
__device__ __align__(1024) float g_stash[SEQ * DM];
__device__ __align__(1024) float g_b[SEQ * DM];
__device__ __align__(1024) __nv_bfloat16 g_h[SEQ * DFF];
__device__ __align__(1024) uint32_t g_bflag[32][2][8];
__device__ uint32_t g_ticket[2];
__device__ int g_err;
#define TS(i)
#define PTS(i)

DEVI uint32_t smem_u32(const void* p) { return (uint32_t)__cvta_generic_to_shared(p); }
DEVI uint32_t clk() { uint32_t c; asm volatile("mov.u32 %0, %%clock;" : "=r"(c) :: "memory"); return c; }
DEVI void mbar_init(uint32_t bar, uint32_t cnt) { asm volatile("mbarrier.init.shared::cta.b64 [%0], %1;" :: "r"(bar), "r"(cnt) : "memory"); }
DEVI void mbar_expect(uint32_t bar, uint32_t bytes) { asm volatile("mbarrier.arrive.expect_tx.shared::cta.b64 _, [%0], %1;" :: "r"(bar), "r"(bytes) : "memory"); }
DEVI void mbar_arrive(uint32_t bar) { asm volatile("mbarrier.arrive.shared::cta.b64 _, [%0];" :: "r"(bar) : "memory"); }
DEVI uint32_t lds32v(uint32_t a) { uint32_t v; asm volatile("ld.volatile.shared::cta.u32 %0, [%1];" : "=r"(v) : "r"(a) : "memory"); return v; }
DEVI void sts32v(uint32_t a, uint32_t v) { asm volatile("st.volatile.shared::cta.u32 [%0], %1;" :: "r"(a), "r"(v) : "memory"); }
DEVI void mbar_wait(uint32_t bar, uint32_t par, int& lim) {
  asm volatile("{\n.reg .pred p, q;\nWAIT_LOOP:\n"
               "mbarrier.try_wait.parity.shared::cta.b64 p, [%1], %2;\n"
               "sub.s32 %0, %0, 1;\nsetp.gt.and.s32 q, %0, 0, !p;\n@q bra.uni WAIT_LOOP;\n}"
               : "+r"(lim) : "r"(bar), "r"(par) : "memory");
}
DEVI void mbar_wait1(uint32_t bar, uint32_t par, int& lim) {
  asm volatile("{\n.reg .pred p, q;\nWAIT_LOOP:\n"
               "mbarrier.try_wait.parity.shared::cta.b64 p, [%1], %2;\n"
               "sub.s32 %0, %0, 1;\nsetp.gt.and.s32 q, %0, 0, !p;\n@q bra WAIT_LOOP;\n}"
               : "+r"(lim) : "r"(bar), "r"(par) : "memory");
}
DEVI bool elect() { uint32_t p; asm volatile("{\n.reg .pred p;\nelect.sync _|p, 0xffffffff;\nselp.u32 %0, 1, 0, p;\n}" : "=r"(p)); return p; }
DEVI bool bar_or(int id, int n, bool v) {
  uint32_t r;
  asm volatile("{\n.reg .pred p, q;\nsetp.ne.u32 q, %3, 0;\nbar.red.or.pred p, %1, %2, q;\nselp.u32 %0, 1, 0, p;\n}"
               : "=r"(r) : "r"(id), "r"(n), "r"((uint32_t)v) : "memory");
  return r;
}
DEVI void delay_until(uint32_t t0, uint32_t d) {
  asm volatile("{\n.reg .pred p;\n.reg .u32 t, u;\n.reg .u64 c;\nDELAY_LOOP:\nmov.u64 c, %%clock64;\nmov.b64 {t, u}, c;\nsub.u32 t, t, %0;\nsetp.lt.u32 p, t, %1;\n@p bra.uni DELAY_LOOP;\n}"
               :: "r"(t0), "r"(d) : "memory");
}
DEVI float rcp(float x) { float y; asm("rcp.approx.ftz.f32 %0, %1;" : "=f"(y) : "f"(x)); return y; }
template <class T> DEVI void pin(T& v) { asm volatile("" : "+r"(v)); }
template <class T> DEVI void pinp(T*& v) { asm volatile("" : "+l"(v)); }
DEVI void bar_sync(int id, int n) { asm volatile("bar.sync %0, %1;" :: "r"(id), "r"(n) : "memory"); }
DEVI void bar_arrive(int id, int n) { asm volatile("bar.arrive %0, %1;" :: "r"(id), "r"(n) : "memory"); }
DEVI void cluster_arrive_relaxed() { asm volatile("barrier.cluster.arrive.relaxed.aligned;" ::: "memory"); }
DEVI void cluster_arrive() { asm volatile("barrier.cluster.arrive.release.aligned;" ::: "memory"); }
DEVI void cluster_wait() { asm volatile("barrier.cluster.wait.acquire.aligned;" ::: "memory"); }
DEVI uint32_t mapa(uint32_t a, uint32_t r) { uint32_t o; asm("mapa.shared::cluster.u32 %0, %1, %2;" : "=r"(o) : "r"(a), "r"(r)); return o; }
DEVI uint32_t pack2(float lo, float hi) { uint32_t r; asm("cvt.rn.bf16x2.f32 %0, %1, %2;" : "=r"(r) : "f"(hi), "f"(lo)); return r; }
DEVI float ex2(float x) { float y; asm("ex2.approx.ftz.f32 %0, %1;" : "=f"(y) : "f"(x)); return y; }
DEVI float bf_lo(uint32_t v) { return __uint_as_float(v << 16); }
DEVI float bf_hi(uint32_t v) { return __uint_as_float(v & 0xffff0000u); }
DEVI void ldsm4(uint32_t (&r)[4], uint32_t a) {
  asm volatile("ldmatrix.sync.aligned.m8n8.x4.shared.b16 {%0,%1,%2,%3}, [%4];" : "=r"(r[0]), "=r"(r[1]), "=r"(r[2]), "=r"(r[3]) : "r"(a) : "memory");
}
DEVI void stsm4t(uint32_t a, uint32_t r0, uint32_t r1, uint32_t r2, uint32_t r3) {
  asm volatile("stmatrix.sync.aligned.m8n8.x4.trans.shared.b16 [%0], {%1,%2,%3,%4};" :: "r"(a), "r"(r0), "r"(r1), "r"(r2), "r"(r3) : "memory");
}
DEVI void stsm2t(uint32_t a, uint32_t r0, uint32_t r1) {
  asm volatile("stmatrix.sync.aligned.m8n8.x2.trans.shared.b16 [%0], {%1,%2};" :: "r"(a), "r"(r0), "r"(r1) : "memory");
}
DEVI void mma16(float (&c)[4], uint32_t a0, uint32_t a1, uint32_t a2, uint32_t a3, uint32_t b0, uint32_t b1) {
  asm("mma.sync.aligned.m16n8k16.row.col.f32.bf16.bf16.f32 {%0,%1,%2,%3},{%4,%5,%6,%7},{%8,%9},{%0,%1,%2,%3};"
      : "+f"(c[0]), "+f"(c[1]), "+f"(c[2]), "+f"(c[3]) : "r"(a0), "r"(a1), "r"(a2), "r"(a3), "r"(b0), "r"(b1));
}
DEVI void mma8(float (&c)[4], uint32_t a0, uint32_t a1, uint32_t b0) {
  asm("mma.sync.aligned.m16n8k8.row.col.f32.bf16.bf16.f32 {%0,%1,%2,%3},{%4,%5},{%6},{%0,%1,%2,%3};"
      : "+f"(c[0]), "+f"(c[1]), "+f"(c[2]), "+f"(c[3]) : "r"(a0), "r"(a1), "r"(b0));
}
DEVI void mma16v(float (&c)[4], uint32_t a0, uint32_t a1, uint32_t a2, uint32_t a3, uint32_t b0, uint32_t b1) {
  asm volatile("mma.sync.aligned.m16n8k16.row.col.f32.bf16.bf16.f32 {%0,%1,%2,%3},{%4,%5,%6,%7},{%8,%9},{%0,%1,%2,%3};"
      : "+f"(c[0]), "+f"(c[1]), "+f"(c[2]), "+f"(c[3]) : "r"(a0), "r"(a1), "r"(a2), "r"(a3), "r"(b0), "r"(b1));
}
DEVI void mma8v(float (&c)[4], uint32_t a0, uint32_t a1, uint32_t b0) {
  asm volatile("mma.sync.aligned.m16n8k8.row.col.f32.bf16.bf16.f32 {%0,%1,%2,%3},{%4,%5},{%6},{%0,%1,%2,%3};"
      : "+f"(c[0]), "+f"(c[1]), "+f"(c[2]), "+f"(c[3]) : "r"(a0), "r"(a1), "r"(b0));
}
DEVI float2 mma_rows8(const uint32_t (&a0)[4], const uint32_t (&a1)[4], const uint32_t (&b0)[4], const uint32_t (&b1)[4]) {
  float e0[4] = {0.f, 0.f, 0.f, 0.f}, e1[4] = {0.f, 0.f, 0.f, 0.f}, e2[4] = {0.f, 0.f, 0.f, 0.f}, e3[4] = {0.f, 0.f, 0.f, 0.f};
  mma16v(e0, a0[0], a0[1], a0[2], a0[3], b0[0], b0[1]);
  mma16v(e1, a0[0], a0[1], a0[2], a0[3], b0[2], b0[3]);
  mma16v(e2, a1[0], a1[1], a1[2], a1[3], b1[0], b1[1]);
  mma16v(e3, a1[0], a1[1], a1[2], a1[3], b1[2], b1[3]);
  return make_float2((e0[0] + e1[2]) + (e2[0] + e3[2]), (e0[1] + e1[3]) + (e2[1] + e3[3]));
}
DEVI void wg_fence() { asm volatile("wgmma.fence.sync.aligned;" ::: "memory"); }
DEVI void wg_commit() { asm volatile("wgmma.commit_group.sync.aligned;" ::: "memory"); }
template <int N> DEVI void wg_wait() { asm volatile("wgmma.wait_group.sync.aligned %0;" :: "n"(N) : "memory"); }
template <int N> DEVI void reg_fence(float (&d)[N]) {
#pragma unroll
  for (int i = 0; i < N; i++) asm volatile("" : "+f"(d[i]) :: "memory");
}
DEVI uint64_t desc128(uint32_t addr, uint32_t lbo16) {
  return (uint64_t)((addr >> 4) & 0x3fff) | ((uint64_t)lbo16 << 16) | (64ull << 32) | (1ull << 62);
}
DEVI void tma2d(uint32_t dst, const CUtensorMap* tm, int c0, int c1, uint32_t bar) {
  asm volatile("cp.async.bulk.tensor.2d.shared::cluster.global.mbarrier::complete_tx::bytes [%0], [%1, {%2, %3}], [%4];"
               :: "r"(dst), "l"(tm), "r"(c0), "r"(c1), "r"(bar) : "memory");
}
DEVI void tma2d_mc(uint32_t dst, const CUtensorMap* tm, int c0, int c1, uint32_t bar) {
  asm volatile("cp.async.bulk.tensor.2d.shared::cluster.global.mbarrier::complete_tx::bytes.multicast::cluster [%0], [%1, {%2, %3}], [%4], %5;"
               :: "r"(dst), "l"(tm), "r"(c0), "r"(c1), "r"(bar), "h"((uint16_t)0xffff) : "memory");
}
DEVI void bulk_ld(uint32_t dst, const void* src, uint32_t bytes, uint32_t bar) {
  asm volatile("cp.async.bulk.shared::cluster.global.mbarrier::complete_tx::bytes [%0], [%1], %2, [%3];"
               :: "r"(dst), "l"(src), "r"(bytes), "r"(bar) : "memory");
}
DEVI void bulk_mc(uint32_t dst, const void* src, uint32_t bytes, uint32_t bar) {
  asm volatile("cp.async.bulk.shared::cluster.global.mbarrier::complete_tx::bytes.multicast::cluster [%0], [%1], %2, [%3], %4;"
               :: "r"(dst), "l"(src), "r"(bytes), "r"(bar), "h"((uint16_t)0xffff) : "memory");
}
DEVI void st_async4(uint32_t a, float x, float y, float z, float w, uint32_t bar) {
  asm volatile("st.async.weak.shared::cluster.mbarrier::complete_tx::bytes.v4.f32 [%0], {%1,%2,%3,%4}, [%5];"
               :: "r"(a), "f"(x), "f"(y), "f"(z), "f"(w), "r"(bar) : "memory");
}
DEVI void st_async4u(uint32_t a, uint32_t x, uint32_t y, uint32_t z, uint32_t w, uint32_t bar) {
  asm volatile("st.async.weak.shared::cluster.mbarrier::complete_tx::bytes.v4.b32 [%0], {%1,%2,%3,%4}, [%5];"
               :: "r"(a), "r"(x), "r"(y), "r"(z), "r"(w), "r"(bar) : "memory");
}
DEVI uint32_t ldg1r(const void* p) { uint32_t v; asm volatile("ld.relaxed.gpu.global.u32 %0, [%1];" : "=r"(v) : "l"(p) : "memory"); return v; }
DEVI uint32_t near_copy(uint8_t* blk) {
  uint32_t best[2] = {~0u, ~0u}, v = 0;
#pragma unroll 1
  for (int i = 0; i < 6; i++) {
    const uint8_t* p = blk + XC_R0 + 7936 + (i & 1) * XC_TWIN + (v & 4);
    const uint32_t t0 = clk();
    asm volatile("atom.relaxed.gpu.global.and.b32 %0, [%1], 0;" : "=r"(v) : "l"(p) : "memory");
    uint32_t t1;
    asm volatile("{\n.reg .pred p;\nPROBE_WAIT:\nsetp.eq.u32 p, %1, 0x5a5a5a5a;\n@p nanosleep.u32 32;\nmov.u32 %0, %%clock;\n}" : "=r"(t1) : "r"(v) : "memory");
    const uint32_t d = t1 - t0;
    if (i & 1) best[1] = min(best[1], d); else best[0] = min(best[0], d);
  }
  return best[1] < best[0] ? XC_TWIN : 0;
}
DEVI void tma2d_prefetch(const CUtensorMap* tm, int c0, int c1) {
  asm volatile("cp.async.bulk.prefetch.tensor.2d.L2.global [%0, {%1, %2}];" :: "l"(tm), "r"(c0), "r"(c1) : "memory");
}
DEVI void ldg2r(uint32_t& x, uint32_t& y, const void* p) { asm volatile("ld.relaxed.gpu.global.v2.u32 {%0,%1}, [%2];" : "=r"(x), "=r"(y) : "l"(p) : "memory"); }
DEVI void stg2r(void* p, uint32_t x, uint32_t y) { asm volatile("st.relaxed.gpu.global.v2.u32 [%0], {%1,%2};" :: "l"(p), "r"(x), "r"(y) : "memory"); }
DEVI void stg16r(void* p, uint16_t v) { asm volatile("st.relaxed.gpu.global.u16 [%0], %1;" :: "l"(p), "h"(v) : "memory"); }
DEVI float lds_f(uint32_t a) { float v; asm volatile("ld.shared.f32 %0, [%1];" : "=f"(v) : "r"(a) : "memory"); return v; }
DEVI float2 lds_f2(uint32_t a) { float2 v; asm volatile("ld.shared.v2.f32 {%0,%1}, [%2];" : "=f"(v.x), "=f"(v.y) : "r"(a) : "memory"); return v; }
DEVI float4 lds_f4(uint32_t a) { float4 v; asm volatile("ld.shared.v4.f32 {%0,%1,%2,%3}, [%4];" : "=f"(v.x), "=f"(v.y), "=f"(v.z), "=f"(v.w) : "r"(a) : "memory"); return v; }
DEVI uint2 lds_u2(uint32_t a) { uint2 v; asm volatile("ld.shared.v2.u32 {%0,%1}, [%2];" : "=r"(v.x), "=r"(v.y) : "r"(a) : "memory"); return v; }
DEVI uint4 lds_u4(uint32_t a) { uint4 v; asm volatile("ld.shared.v4.u32 {%0,%1,%2,%3}, [%4];" : "=r"(v.x), "=r"(v.y), "=r"(v.z), "=r"(v.w) : "r"(a) : "memory"); return v; }
DEVI void sts_f2(uint32_t a, float x, float y) { asm volatile("st.shared.v2.f32 [%0], {%1,%2};" :: "r"(a), "f"(x), "f"(y) : "memory"); }
DEVI void sts_f4(uint32_t a, float x, float y, float z, float w) { asm volatile("st.shared.v4.f32 [%0], {%1,%2,%3,%4};" :: "r"(a), "f"(x), "f"(y), "f"(z), "f"(w) : "memory"); }
DEVI void sts_u2(uint32_t a, uint32_t x, uint32_t y) { asm volatile("st.shared.v2.u32 [%0], {%1,%2};" :: "r"(a), "r"(x), "r"(y) : "memory"); }
DEVI void sts_u4(uint32_t a, uint32_t x, uint32_t y, uint32_t z, uint32_t w) { asm volatile("st.shared.v4.u32 [%0], {%1,%2,%3,%4};" :: "r"(a), "r"(x), "r"(y), "r"(z), "r"(w) : "memory"); }
DEVI uint32_t tagf(float v, uint32_t tag) { return (__float_as_uint(v) & ~3u) | tag; }
DEVI float qmax(float v) { v = fmaxf(v, __shfl_xor_sync(0xffffffffu, v, 1)); return fmaxf(v, __shfl_xor_sync(0xffffffffu, v, 2)); }
DEVI float qsum(float v) { v += __shfl_xor_sync(0xffffffffu, v, 1); return v + __shfl_xor_sync(0xffffffffu, v, 2); }

__device__ __forceinline__ void wgmma_n224_kk(float (&d)[112], uint64_t da, uint64_t db, int sc) {
  asm volatile("{\n.reg .pred p;\nsetp.ne.b32 p, %114, 0;\n"
    "wgmma.mma_async.sync.aligned.m64n224k16.f32.bf16.bf16 {%0,%1,%2,%3,%4,%5,%6,%7,%8,%9,%10,%11,%12,%13,%14,%15,%16,%17,%18,%19,%20,%21,%22,%23,%24,%25,%26,%27,%28,%29,%30,%31,%32,%33,%34,%35,%36,%37,%38,%39,%40,%41,%42,%43,%44,%45,%46,%47,%48,%49,%50,%51,%52,%53,%54,%55,%56,%57,%58,%59,%60,%61,%62,%63,%64,%65,%66,%67,%68,%69,%70,%71,%72,%73,%74,%75,%76,%77,%78,%79,%80,%81,%82,%83,%84,%85,%86,%87,%88,%89,%90,%91,%92,%93,%94,%95,%96,%97,%98,%99,%100,%101,%102,%103,%104,%105,%106,%107,%108,%109,%110,%111}, %112, %113, p, 1, 1, 0, 0;\n}"
    : "+f"(d[0]),"+f"(d[1]),"+f"(d[2]),"+f"(d[3]),"+f"(d[4]),"+f"(d[5]),"+f"(d[6]),"+f"(d[7]),"+f"(d[8]),"+f"(d[9]),"+f"(d[10]),"+f"(d[11]),"+f"(d[12]),"+f"(d[13]),"+f"(d[14]),"+f"(d[15]),"+f"(d[16]),"+f"(d[17]),"+f"(d[18]),"+f"(d[19]),"+f"(d[20]),"+f"(d[21]),"+f"(d[22]),"+f"(d[23]),"+f"(d[24]),"+f"(d[25]),"+f"(d[26]),"+f"(d[27]),"+f"(d[28]),"+f"(d[29]),"+f"(d[30]),"+f"(d[31]),"+f"(d[32]),"+f"(d[33]),"+f"(d[34]),"+f"(d[35]),"+f"(d[36]),"+f"(d[37]),"+f"(d[38]),"+f"(d[39]),"+f"(d[40]),"+f"(d[41]),"+f"(d[42]),"+f"(d[43]),"+f"(d[44]),"+f"(d[45]),"+f"(d[46]),"+f"(d[47]),"+f"(d[48]),"+f"(d[49]),"+f"(d[50]),"+f"(d[51]),"+f"(d[52]),"+f"(d[53]),"+f"(d[54]),"+f"(d[55]),"+f"(d[56]),"+f"(d[57]),"+f"(d[58]),"+f"(d[59]),"+f"(d[60]),"+f"(d[61]),"+f"(d[62]),"+f"(d[63]),"+f"(d[64]),"+f"(d[65]),"+f"(d[66]),"+f"(d[67]),"+f"(d[68]),"+f"(d[69]),"+f"(d[70]),"+f"(d[71]),"+f"(d[72]),"+f"(d[73]),"+f"(d[74]),"+f"(d[75]),"+f"(d[76]),"+f"(d[77]),"+f"(d[78]),"+f"(d[79]),"+f"(d[80]),"+f"(d[81]),"+f"(d[82]),"+f"(d[83]),"+f"(d[84]),"+f"(d[85]),"+f"(d[86]),"+f"(d[87]),"+f"(d[88]),"+f"(d[89]),"+f"(d[90]),"+f"(d[91]),"+f"(d[92]),"+f"(d[93]),"+f"(d[94]),"+f"(d[95]),"+f"(d[96]),"+f"(d[97]),"+f"(d[98]),"+f"(d[99]),"+f"(d[100]),"+f"(d[101]),"+f"(d[102]),"+f"(d[103]),"+f"(d[104]),"+f"(d[105]),"+f"(d[106]),"+f"(d[107]),"+f"(d[108]),"+f"(d[109]),"+f"(d[110]),"+f"(d[111])
    : "l"(da),"l"(db),"r"(sc));
}
__device__ __forceinline__ void wgmma_n224_mk(float (&d)[112], uint64_t da, uint64_t db, int sc) {
  asm volatile("{\n.reg .pred p;\nsetp.ne.b32 p, %114, 0;\n"
    "wgmma.mma_async.sync.aligned.m64n224k16.f32.bf16.bf16 {%0,%1,%2,%3,%4,%5,%6,%7,%8,%9,%10,%11,%12,%13,%14,%15,%16,%17,%18,%19,%20,%21,%22,%23,%24,%25,%26,%27,%28,%29,%30,%31,%32,%33,%34,%35,%36,%37,%38,%39,%40,%41,%42,%43,%44,%45,%46,%47,%48,%49,%50,%51,%52,%53,%54,%55,%56,%57,%58,%59,%60,%61,%62,%63,%64,%65,%66,%67,%68,%69,%70,%71,%72,%73,%74,%75,%76,%77,%78,%79,%80,%81,%82,%83,%84,%85,%86,%87,%88,%89,%90,%91,%92,%93,%94,%95,%96,%97,%98,%99,%100,%101,%102,%103,%104,%105,%106,%107,%108,%109,%110,%111}, %112, %113, p, 1, 1, 1, 0;\n}"
    : "+f"(d[0]),"+f"(d[1]),"+f"(d[2]),"+f"(d[3]),"+f"(d[4]),"+f"(d[5]),"+f"(d[6]),"+f"(d[7]),"+f"(d[8]),"+f"(d[9]),"+f"(d[10]),"+f"(d[11]),"+f"(d[12]),"+f"(d[13]),"+f"(d[14]),"+f"(d[15]),"+f"(d[16]),"+f"(d[17]),"+f"(d[18]),"+f"(d[19]),"+f"(d[20]),"+f"(d[21]),"+f"(d[22]),"+f"(d[23]),"+f"(d[24]),"+f"(d[25]),"+f"(d[26]),"+f"(d[27]),"+f"(d[28]),"+f"(d[29]),"+f"(d[30]),"+f"(d[31]),"+f"(d[32]),"+f"(d[33]),"+f"(d[34]),"+f"(d[35]),"+f"(d[36]),"+f"(d[37]),"+f"(d[38]),"+f"(d[39]),"+f"(d[40]),"+f"(d[41]),"+f"(d[42]),"+f"(d[43]),"+f"(d[44]),"+f"(d[45]),"+f"(d[46]),"+f"(d[47]),"+f"(d[48]),"+f"(d[49]),"+f"(d[50]),"+f"(d[51]),"+f"(d[52]),"+f"(d[53]),"+f"(d[54]),"+f"(d[55]),"+f"(d[56]),"+f"(d[57]),"+f"(d[58]),"+f"(d[59]),"+f"(d[60]),"+f"(d[61]),"+f"(d[62]),"+f"(d[63]),"+f"(d[64]),"+f"(d[65]),"+f"(d[66]),"+f"(d[67]),"+f"(d[68]),"+f"(d[69]),"+f"(d[70]),"+f"(d[71]),"+f"(d[72]),"+f"(d[73]),"+f"(d[74]),"+f"(d[75]),"+f"(d[76]),"+f"(d[77]),"+f"(d[78]),"+f"(d[79]),"+f"(d[80]),"+f"(d[81]),"+f"(d[82]),"+f"(d[83]),"+f"(d[84]),"+f"(d[85]),"+f"(d[86]),"+f"(d[87]),"+f"(d[88]),"+f"(d[89]),"+f"(d[90]),"+f"(d[91]),"+f"(d[92]),"+f"(d[93]),"+f"(d[94]),"+f"(d[95]),"+f"(d[96]),"+f"(d[97]),"+f"(d[98]),"+f"(d[99]),"+f"(d[100]),"+f"(d[101]),"+f"(d[102]),"+f"(d[103]),"+f"(d[104]),"+f"(d[105]),"+f"(d[106]),"+f"(d[107]),"+f"(d[108]),"+f"(d[109]),"+f"(d[110]),"+f"(d[111])
    : "l"(da),"l"(db),"r"(sc));
}
__device__ __forceinline__ void wgmma_n32_rs(float (&d)[16], const uint32_t (&a)[4], uint64_t db, int sc) {
  asm volatile("{\n.reg .pred p;\nsetp.ne.b32 p, %21, 0;\n"
    "wgmma.mma_async.sync.aligned.m64n32k16.f32.bf16.bf16 {%0,%1,%2,%3,%4,%5,%6,%7,%8,%9,%10,%11,%12,%13,%14,%15}, {%16,%17,%18,%19}, %20, p, 1, 1, 0;\n}"
    : "+f"(d[0]),"+f"(d[1]),"+f"(d[2]),"+f"(d[3]),"+f"(d[4]),"+f"(d[5]),"+f"(d[6]),"+f"(d[7]),"+f"(d[8]),"+f"(d[9]),"+f"(d[10]),"+f"(d[11]),"+f"(d[12]),"+f"(d[13]),"+f"(d[14]),"+f"(d[15])
    : "r"(a[0]),"r"(a[1]),"r"(a[2]),"r"(a[3]),"l"(db),"r"(sc));
}
__device__ __forceinline__ void wgmma_n8_rs(float (&d)[4], const uint32_t (&a)[4], uint64_t db, int sc) {
  asm volatile("{\n.reg .pred p;\nsetp.ne.b32 p, %9, 0;\n"
    "wgmma.mma_async.sync.aligned.m64n8k16.f32.bf16.bf16 {%0,%1,%2,%3}, {%4,%5,%6,%7}, %8, p, 1, 1, 0;\n}"
    : "+f"(d[0]),"+f"(d[1]),"+f"(d[2]),"+f"(d[3])
    : "r"(a[0]),"r"(a[1]),"r"(a[2]),"r"(a[3]),"l"(db),"r"(sc));
}
__device__ __forceinline__ void wgmma_n256_kn(float (&d)[128], uint64_t da, uint64_t db, int sc) {
  asm volatile("{\n.reg .pred p;\nsetp.ne.b32 p, %130, 0;\n"
    "wgmma.mma_async.sync.aligned.m64n256k16.f32.bf16.bf16 {%0,%1,%2,%3,%4,%5,%6,%7,%8,%9,%10,%11,%12,%13,%14,%15,%16,%17,%18,%19,%20,%21,%22,%23,%24,%25,%26,%27,%28,%29,%30,%31,%32,%33,%34,%35,%36,%37,%38,%39,%40,%41,%42,%43,%44,%45,%46,%47,%48,%49,%50,%51,%52,%53,%54,%55,%56,%57,%58,%59,%60,%61,%62,%63,%64,%65,%66,%67,%68,%69,%70,%71,%72,%73,%74,%75,%76,%77,%78,%79,%80,%81,%82,%83,%84,%85,%86,%87,%88,%89,%90,%91,%92,%93,%94,%95,%96,%97,%98,%99,%100,%101,%102,%103,%104,%105,%106,%107,%108,%109,%110,%111,%112,%113,%114,%115,%116,%117,%118,%119,%120,%121,%122,%123,%124,%125,%126,%127}, %128, %129, p, 1, 1, 0, 1;\n}"
    : "+f"(d[0]),"+f"(d[1]),"+f"(d[2]),"+f"(d[3]),"+f"(d[4]),"+f"(d[5]),"+f"(d[6]),"+f"(d[7]),"+f"(d[8]),"+f"(d[9]),"+f"(d[10]),"+f"(d[11]),"+f"(d[12]),"+f"(d[13]),"+f"(d[14]),"+f"(d[15]),"+f"(d[16]),"+f"(d[17]),"+f"(d[18]),"+f"(d[19]),"+f"(d[20]),"+f"(d[21]),"+f"(d[22]),"+f"(d[23]),"+f"(d[24]),"+f"(d[25]),"+f"(d[26]),"+f"(d[27]),"+f"(d[28]),"+f"(d[29]),"+f"(d[30]),"+f"(d[31]),"+f"(d[32]),"+f"(d[33]),"+f"(d[34]),"+f"(d[35]),"+f"(d[36]),"+f"(d[37]),"+f"(d[38]),"+f"(d[39]),"+f"(d[40]),"+f"(d[41]),"+f"(d[42]),"+f"(d[43]),"+f"(d[44]),"+f"(d[45]),"+f"(d[46]),"+f"(d[47]),"+f"(d[48]),"+f"(d[49]),"+f"(d[50]),"+f"(d[51]),"+f"(d[52]),"+f"(d[53]),"+f"(d[54]),"+f"(d[55]),"+f"(d[56]),"+f"(d[57]),"+f"(d[58]),"+f"(d[59]),"+f"(d[60]),"+f"(d[61]),"+f"(d[62]),"+f"(d[63]),"+f"(d[64]),"+f"(d[65]),"+f"(d[66]),"+f"(d[67]),"+f"(d[68]),"+f"(d[69]),"+f"(d[70]),"+f"(d[71]),"+f"(d[72]),"+f"(d[73]),"+f"(d[74]),"+f"(d[75]),"+f"(d[76]),"+f"(d[77]),"+f"(d[78]),"+f"(d[79]),"+f"(d[80]),"+f"(d[81]),"+f"(d[82]),"+f"(d[83]),"+f"(d[84]),"+f"(d[85]),"+f"(d[86]),"+f"(d[87]),"+f"(d[88]),"+f"(d[89]),"+f"(d[90]),"+f"(d[91]),"+f"(d[92]),"+f"(d[93]),"+f"(d[94]),"+f"(d[95]),"+f"(d[96]),"+f"(d[97]),"+f"(d[98]),"+f"(d[99]),"+f"(d[100]),"+f"(d[101]),"+f"(d[102]),"+f"(d[103]),"+f"(d[104]),"+f"(d[105]),"+f"(d[106]),"+f"(d[107]),"+f"(d[108]),"+f"(d[109]),"+f"(d[110]),"+f"(d[111]),"+f"(d[112]),"+f"(d[113]),"+f"(d[114]),"+f"(d[115]),"+f"(d[116]),"+f"(d[117]),"+f"(d[118]),"+f"(d[119]),"+f"(d[120]),"+f"(d[121]),"+f"(d[122]),"+f"(d[123]),"+f"(d[124]),"+f"(d[125]),"+f"(d[126]),"+f"(d[127])
    : "l"(da),"l"(db),"r"(sc));
}
__device__ __forceinline__ void wgmma_n192_kn(float (&d)[96], uint64_t da, uint64_t db, int sc) {
  asm volatile("{\n.reg .pred p;\nsetp.ne.b32 p, %98, 0;\n"
    "wgmma.mma_async.sync.aligned.m64n192k16.f32.bf16.bf16 {%0,%1,%2,%3,%4,%5,%6,%7,%8,%9,%10,%11,%12,%13,%14,%15,%16,%17,%18,%19,%20,%21,%22,%23,%24,%25,%26,%27,%28,%29,%30,%31,%32,%33,%34,%35,%36,%37,%38,%39,%40,%41,%42,%43,%44,%45,%46,%47,%48,%49,%50,%51,%52,%53,%54,%55,%56,%57,%58,%59,%60,%61,%62,%63,%64,%65,%66,%67,%68,%69,%70,%71,%72,%73,%74,%75,%76,%77,%78,%79,%80,%81,%82,%83,%84,%85,%86,%87,%88,%89,%90,%91,%92,%93,%94,%95}, %96, %97, p, 1, 1, 0, 1;\n}"
    : "+f"(d[0]),"+f"(d[1]),"+f"(d[2]),"+f"(d[3]),"+f"(d[4]),"+f"(d[5]),"+f"(d[6]),"+f"(d[7]),"+f"(d[8]),"+f"(d[9]),"+f"(d[10]),"+f"(d[11]),"+f"(d[12]),"+f"(d[13]),"+f"(d[14]),"+f"(d[15]),"+f"(d[16]),"+f"(d[17]),"+f"(d[18]),"+f"(d[19]),"+f"(d[20]),"+f"(d[21]),"+f"(d[22]),"+f"(d[23]),"+f"(d[24]),"+f"(d[25]),"+f"(d[26]),"+f"(d[27]),"+f"(d[28]),"+f"(d[29]),"+f"(d[30]),"+f"(d[31]),"+f"(d[32]),"+f"(d[33]),"+f"(d[34]),"+f"(d[35]),"+f"(d[36]),"+f"(d[37]),"+f"(d[38]),"+f"(d[39]),"+f"(d[40]),"+f"(d[41]),"+f"(d[42]),"+f"(d[43]),"+f"(d[44]),"+f"(d[45]),"+f"(d[46]),"+f"(d[47]),"+f"(d[48]),"+f"(d[49]),"+f"(d[50]),"+f"(d[51]),"+f"(d[52]),"+f"(d[53]),"+f"(d[54]),"+f"(d[55]),"+f"(d[56]),"+f"(d[57]),"+f"(d[58]),"+f"(d[59]),"+f"(d[60]),"+f"(d[61]),"+f"(d[62]),"+f"(d[63]),"+f"(d[64]),"+f"(d[65]),"+f"(d[66]),"+f"(d[67]),"+f"(d[68]),"+f"(d[69]),"+f"(d[70]),"+f"(d[71]),"+f"(d[72]),"+f"(d[73]),"+f"(d[74]),"+f"(d[75]),"+f"(d[76]),"+f"(d[77]),"+f"(d[78]),"+f"(d[79]),"+f"(d[80]),"+f"(d[81]),"+f"(d[82]),"+f"(d[83]),"+f"(d[84]),"+f"(d[85]),"+f"(d[86]),"+f"(d[87]),"+f"(d[88]),"+f"(d[89]),"+f"(d[90]),"+f"(d[91]),"+f"(d[92]),"+f"(d[93]),"+f"(d[94]),"+f"(d[95])
    : "l"(da),"l"(db),"r"(sc));
}

constexpr uint32_t XB = 28672;
constexpr uint32_t O_WQ = 5 * XB;
constexpr uint32_t O_WO = O_WQ + 32768;
constexpr uint32_t O_MIMG = O_WO + 32768;
constexpr uint32_t O_BAR = O_MIMG + 2 * 7168;
constexpr uint32_t O_TS = O_BAR + 384;
constexpr uint32_t T_SMEM = O_TS + 4096 + 128 + 1024;
constexpr uint32_t O_Z = 4 * XB;
constexpr uint32_t O_RS = O_Z + 2 * 5120;
constexpr uint32_t O_ORS = O_RS + 2 * 2048;
constexpr uint32_t O_P = O_ORS + 4 * 4096;
constexpr uint32_t O_SX = O_P + 2 * 2560;
constexpr uint32_t O_MJ = O_SX + 1536;
constexpr uint32_t O_ST = O_MJ + 2048;
constexpr uint32_t O_PC = O_ST + 2 * 5632;
constexpr uint32_t O_YB = O_PC + 128;
constexpr uint32_t O_GX = O_YB + 2 * 5120;
constexpr uint32_t O_GY = O_GX + 2 * 1792;
enum { B_X = 0, B_M = 4, B_RS = 6, B_O = 8, B_ZX = 10, B_P = 12, B_PF = 14, B_PE = 18, B_WQ = 22, B_WO = 23, B_T = 24, B_MJ = 26, B_OL = 28, B_G = 30, B_M2 = 31, B_YM = 33, B_GY = 34, B_N = 35 };
constexpr uint32_t O_NEAR = O_BAR + 8 * B_N, O_DONE = O_NEAR + 8, O_C3 = O_DONE + 4;
enum { N_ZM = 1, N_MOK = 2, N_W1 = 3, N_INIT = 4, N_ZX = 5, N_REDO = 6, N_YX = 7, N_SS = 8, N_ST = 9 };

DEVI void gemm_m(const uint32_t (&w)[28][4], uint32_t img_lane, float (&c)[4]) {
  float acc[4][4];
#pragma unroll
  for (int i = 0; i < 4; i++) { acc[i][0] = acc[i][1] = acc[i][2] = acc[i][3] = 0.f; }
  uint32_t r[14][4];
#pragma unroll
  for (int u = 0; u < 14; u++) ldsm4(r[u], img_lane + u * 512);
#pragma unroll
  for (int u = 0; u < 14; u++) {
    mma16v(acc[(2 * u) & 3], w[2 * u][0], w[2 * u][1], w[2 * u][2], w[2 * u][3], r[u][0], r[u][1]);
    mma16v(acc[(2 * u + 1) & 3], w[2 * u + 1][0], w[2 * u + 1][1], w[2 * u + 1][2], w[2 * u + 1][3], r[u][2], r[u][3]);
  }
#pragma unroll
  for (int i = 0; i < 4; i++) c[i] = (acc[0][i] + acc[1][i]) + (acc[2][i] + acc[3][i]);
}

DEVI void gemm_x_issue(const uint32_t (&w)[28][4], uint32_t xbuf, float (&d)[16]) {
  const uint64_t b0 = desc128(xbuf, 1);
  wg_fence();
#pragma unroll
  for (int k = 0; k < 28; k++) wgmma_n32_rs(d, w[k], b0 + (uint64_t)((k >> 2) * 256 + (k & 3) * 2), k != 0);
  wg_commit();
}
DEVI void gemm_x(const uint32_t (&w)[28][4], uint32_t xbuf, float (&d)[16]) {
  gemm_x_issue(w, xbuf, d);
  wg_wait<0>();
  reg_fence(d);
}

template <int WHICH>
DEVI void build_weights(uint32_t (&w)[28][4], uint32_t sb, int& dead, int lane) {
  const uint32_t bar = sb + O_BAR;
  mbar_wait(bar + 8 * (WHICH ? B_WO : B_WQ), 0, dead);
  if ((threadIdx.x & 127) == 0) PTS(4 + WHICH);
#pragma unroll
  for (int half = 0; half < 2; half++) {
    float d[112];
#pragma unroll 1
    for (int fk = 0; fk < 4; fk++) {
      const int c = 2 * (4 * half + fk) + WHICH, st = c & 3;
      mbar_wait(bar + 8 * (B_PF + st), (c >> 2) & 1, dead);
      if ((threadIdx.x & 127) == 0) PTS(8 + c);
      const uint64_t db = desc128(sb + (st + 1) * XB, 1);
      wg_fence();
#pragma unroll
      for (int kk = 0; kk < 4; kk++) {
        if (WHICH == 0) wgmma_n224_kk(d, desc128(sb + O_WQ + fk * 8192 + kk * 32, 1), db + kk * 2, (fk | kk) != 0);
        else            wgmma_n224_mk(d, desc128(sb + O_WO + (fk * 4 + kk) * 2048, 1), db + kk * 2, (fk | kk) != 0);
      }
      wg_commit();
      wg_wait<0>();
      if (lane == 0) mbar_arrive(bar + 8 * (B_PE + st));
    }
    reg_fence(d);
#pragma unroll
    for (int kk = 0; kk < 14; kk++) {
      w[14 * half + kk][0] = pack2(d[8 * kk + 0], d[8 * kk + 1]);
      w[14 * half + kk][1] = pack2(d[8 * kk + 2], d[8 * kk + 3]);
      w[14 * half + kk][2] = pack2(d[8 * kk + 4], d[8 * kk + 5]);
      w[14 * half + kk][3] = pack2(d[8 * kk + 6], d[8 * kk + 7]);
    }
  }
}

DEVI bool stale7(const uint32_t (&v)[14], uint32_t tag) {
  const uint32_t o = ((v[0] | v[1] | v[2]) | (v[3] | v[4] | v[5]) | (v[6] | v[7] | v[8])) | ((v[9] | v[10] | v[11]) | (v[12] | v[13]));
  const uint32_t a = ((v[0] & v[1] & v[2]) & (v[3] & v[4] & v[5]) & (v[6] & v[7] & v[8])) & ((v[9] & v[10] & v[11]) & (v[12] & v[13]));
  return (((o ^ tag) | (a ^ tag)) & 3u) != 0;
}
DEVI float2 add7(const uint32_t (&v)[14]) {
  float2 r;
  r.x = ((__uint_as_float(v[0]) + __uint_as_float(v[2])) + (__uint_as_float(v[4]) + __uint_as_float(v[6]))) +
        ((__uint_as_float(v[8]) + __uint_as_float(v[10])) + __uint_as_float(v[12]));
  r.y = ((__uint_as_float(v[1]) + __uint_as_float(v[3])) + (__uint_as_float(v[5]) + __uint_as_float(v[7]))) +
        ((__uint_as_float(v[9]) + __uint_as_float(v[11])) + __uint_as_float(v[13]));
  return r;
}

__global__ void __launch_bounds__(384, 1)
rmt_kernel(const __grid_constant__ CUtensorMap tmWq, const __grid_constant__ CUtensorMap tmWk,
           const __grid_constant__ CUtensorMap tmWv, const __grid_constant__ CUtensorMap tmWo,
           const __grid_constant__ CUtensorMap tmX, const __nv_bfloat16* __restrict__ x,
           const __nv_bfloat16* __restrict__ mem0, const __nv_bfloat16* __restrict__ gate_w, __nv_bfloat16* __restrict__ out) {
  extern __shared__ uint8_t smem_raw[];
  const uint32_t sb = (smem_u32(smem_raw) + 1023) & ~1023u;
  const uint32_t bar = sb + O_BAR;
  int lim = SPIN_LIMIT;
  int tid;
  uint32_t h, j;
  asm volatile("mov.u32 %0, %%tid.x;" : "=r"(tid));
  asm volatile("mov.u32 %0, %%cluster_ctarank;" : "=r"(h));
  asm volatile("mov.u32 %0, %%clusterid.x;" : "=r"(j));
  tid = __shfl_sync(0xffffffffu, tid, tid & 31);
  const int lane = tid & 31, warp = __shfl_sync(0xffffffffu, tid >> 5, 0);
  if (warp == 0) PTS(0);

  if (warp == 8) {
    if (elect()) {
#pragma unroll
      for (int i = 0; i < 4; i++) mbar_init(bar + 8 * (B_PF + i), 1);
      mbar_init(bar + 8 * B_WQ, 1);
      mbar_init(bar + 8 * B_WO, 1);
      asm volatile("fence.mbarrier_init.release.cluster;" ::: "memory");
      PTS(1);
      mbar_expect(bar + 8 * B_PF, XB);
      tma2d(sb + XB, &tmWk, h * DH, 0, bar + 8 * B_PF);
      mbar_expect(bar + 8 * B_WQ, 32768);
#pragma unroll
      for (int k = 0; k < 4; k++) tma2d(sb + O_WQ + k * 8192, &tmWq, h * DH + k * 64, j * 64, bar + 8 * B_WQ);
      mbar_expect(bar + 8 * B_WO, 32768);
      tma2d(sb + O_WO, &tmWo, j * 64, h * DH, bar + 8 * B_WO);
#pragma unroll
      for (int c = 1; c < 4; c++) {
        mbar_expect(bar + 8 * (B_PF + c), XB);
        tma2d(sb + (c + 1) * XB, (c & 1) ? &tmWv : &tmWk, h * DH + (c >> 1) * 64, 0, bar + 8 * (B_PF + c));
      }
    }
  } else if (warp == 9) {
    if (elect()) {
#pragma unroll
      for (int i = 0; i < B_N; i++)
        if (i < B_PF || (i >= B_PE && i < B_WQ) || i >= B_T) mbar_init(bar + 8 * i, i == B_M2 + 1 ? 16 : i >= B_MJ ? 1 : i >= B_T ? 3 : i >= B_PE ? 4 : i >= B_P ? 2 : i >= B_ZX ? 4 : 1);
      sts32v(sb + O_DONE, 0);
      sts32v(sb + O_C3, 0);
      sts32v(sb + O_DONE + 8, 0);
      mbar_expect(bar + 8 * B_X, XB);
      mbar_expect(bar + 8 * B_OL, 4096);
      mbar_expect(bar + 8 * (B_OL + 1), 4096);
#pragma unroll
      for (int i = 0; i < 2; i++) { mbar_expect(bar + 8 * (B_RS + i), 2048); mbar_expect(bar + 8 * (B_O + i), 4096); }
      asm volatile("fence.mbarrier_init.release.cluster;" ::: "memory");
    }
  }
  asm volatile("griddepcontrol.launch_dependents;");
  if (warp == 8) PTS(2);
  __syncthreads();
  cluster_arrive_relaxed();
  if (warp == 0) PTS(3);

  if (warp < 4) {
    asm volatile("setmaxnreg.inc.sync.aligned.u32 216;");
    uint32_t w[28][4];
    build_weights<0>(w, sb, lim, lane);
    if (warp == 0) PTS(6);
    cluster_wait();
    cluster_arrive_relaxed();
    uint32_t zst = sb + O_Z + ((2 * warp + ((lane >> 3) & 1)) * 40 + 8 * (lane >> 4) + (lane & 7)) * 16;
    const int mt = warp & 1, n0 = (warp >> 1) * 3;
    const int ch = lane >> 3, chp = (ch >> 1) | ((ch & 1) << 1);
    uint32_t zld = sb + O_Z + ((warp == 2 ? chp : ch) * 40 + (lane & 7)) * 16 + (warp == 2 ? 0 : n0 * 128);
    const uint32_t zx = sb + O_Z + (chp * 40 + 8 + 8 * warp + (lane & 7)) * 16;
    float* p_smx = &g_xacc[0][h][warp * 128 + lane * 4];
    const int xrow = 16 * mt + (lane & 15);
    uint32_t xq = sb + j * 4096 + xrow * 128 + (((lane >> 4) ^ (xrow & 7)) << 4);
    uint32_t mimg = sb + O_MIMG + lane * 16, sta = sb + O_ST + (warp == 3 ? 4096 : mt * 2048) + lane * 16;
    uint8_t* p_smm = xch(h) + (XC_R0 + 2 * XC_REG + j * 256 + lane * 8);
    pin(zst); pin(zld); pin(xq); pin(mimg); pin(sta); pinp(p_smm);
    {
      float d[16];
      mbar_wait(bar + 8 * B_X, 0, lim);
      gemm_x(w, sb, d);
      if (warp == 0) PTS(7);
      cluster_wait();
      if (warp == 0) PTS(24);
      stsm4t(zst + 8 * 16, pack2(d[0], d[1]), pack2(d[2], d[3]), pack2(d[4], d[5]), pack2(d[6], d[7]));
      stsm4t(zst + 24 * 16, pack2(d[8], d[9]), pack2(d[10], d[11]), pack2(d[12], d[13]), pack2(d[14], d[15]));
    }
    const uint32_t o_a = mapa(sb + O_ORS + h * 256 + warp * 64 + (lane & 3) * 16, lane >> 2);
    const uint32_t o_b = mapa(bar + 8 * B_O, lane >> 2);
    const uint32_t o_st = mapa(sb, 8) - mapa(sb, 0);
    uint32_t oh[8];
    auto token_pv = [&](int sp) {
      const uint32_t p16 = mimg + (O_P - O_MIMG) + (sp & 1) * 2560, p8 = p16 + 1024 - lane * 8, yb = sb + O_YB + (sp & 1) * 5120 + tid * 16;
      const uint4 y0 = lds_u4(yb), y1 = lds_u4(yb + 2048);
      const uint2 ymp = lds_u2(yb + 4096 - tid * 8);
      mbar_wait(bar + 8 * (B_P + (sp & 1)), (sp >> 1) & 1, lim);
      const uint2 m0 = lds_u2(p8), m1 = lds_u2(p8 + 1280);
      const uint4 p0 = lds_u4(p16), p1 = lds_u4(p16 + 512), p2 = lds_u4(p16 + 1280), p3 = lds_u4(p16 + 1280 + 512);
      float o0[4] = {0.f, 0.f, 0.f, 0.f}, o1[4] = {0.f, 0.f, 0.f, 0.f}, o2[4] = {0.f, 0.f, 0.f, 0.f}, o3[4] = {0.f, 0.f, 0.f, 0.f};
      mma8(o0, m0.x, m0.y, ymp.x);
      mma8(o1, m0.x, m0.y, ymp.y);
      mma8(o2, m1.x, m1.y, ymp.x);
      mma8(o3, m1.x, m1.y, ymp.y);
      mma16(o0, p0.x, p0.y, p0.z, p0.w, y0.x, y0.y);
      mma16(o1, p0.x, p0.y, p0.z, p0.w, y0.z, y0.w);
      mma16(o2, p2.x, p2.y, p2.z, p2.w, y0.x, y0.y);
      mma16(o3, p2.x, p2.y, p2.z, p2.w, y0.z, y0.w);
      mma16(o0, p1.x, p1.y, p1.z, p1.w, y1.x, y1.y);
      mma16(o1, p1.x, p1.y, p1.z, p1.w, y1.z, y1.w);
      mma16(o2, p3.x, p3.y, p3.z, p3.w, y1.x, y1.y);
      mma16(o3, p3.x, p3.y, p3.z, p3.w, y1.z, y1.w);
      oh[0] = pack2(o0[0], o0[1]); oh[1] = pack2(o1[0], o1[1]); oh[2] = pack2(o0[2], o0[3]); oh[3] = pack2(o1[2], o1[3]);
      oh[4] = pack2(o2[0], o2[1]); oh[5] = pack2(o3[0], o3[1]); oh[6] = pack2(o2[2], o2[3]); oh[7] = pack2(o3[2], o3[3]);
    };
    auto token_send = [&](int sp) {
      const bool last = sp >= NSEG - 2;
      const uint32_t oa = o_a + ((last ? 2 : 0) + (sp & 1)) * 4096, ob = o_b + ((last ? B_OL - B_O : 0) + (sp & 1)) * 8;
      st_async4u(oa, oh[0], oh[1], oh[2], oh[3], ob);
      st_async4u(oa + o_st, oh[4], oh[5], oh[6], oh[7], ob + o_st);
    };
#pragma unroll 1
    for (int s = 0; s < NSEG; s++) {
      const bool rec = s < NSEG - 1;
      uint32_t img = mimg + (s & 1) * 7168, zs = zst + (s & 1) * 5120, zl = zld + (s & 1) * 5120;
      uint32_t tag = ((s >> 1) + 1) & 3;
      uint8_t* smm = p_smm + (s & 1) * 1792;
      pin(img); pin(zs); pin(zl); pin(tag); pinp(smm);
      uint32_t a[4][4];
      if (rec) {
        uint32_t zb0[4], zb1[4];
        bar_sync(N_W1, 128);
        ldsm4(zb0, zx + (s & 1) * 5120);
        ldsm4(zb1, zx + (s & 1) * 5120 + 4 * 640);
        const uint32_t mj = s ? mimg + (O_MJ - O_MIMG) + (s & 1) * 1024 : img + j * 1024;
        if (s) mbar_wait(bar + 8 * (B_MJ + (s & 1)), ((s - 1) >> 1) & 1, lim);
        ldsm4(a[0], mj);
        ldsm4(a[1], mj + 512);
        const float2 e = mma_rows8(a[0], a[1], zb0, zb1);
        asm volatile("red.relaxed.gpu.global.add.v4.f32 [%0], {%1,%2,%3,%4};" :: "l"(p_smx + (s & 3) * (NH * 512)), "f"(e.x), "f"(e.y), "f"((float)(s + 1)), "f"(0.f) : "memory");
        if (warp == 0) TS(15);
      }
      if (s) mbar_wait(bar + 8 * (B_M + (s & 1)), ((s - 1) >> 1) & 1, lim);
      if (warp == 2) TS(0);
      if (warp == 2 && s == 63) PTS(27);
      if (warp == 2 && s == 0) PTS(28);
      if (warp == 2 && s == 1) PTS(29);
      float c[4];
      do {
        gemm_m(w, img, c);
        stsm2t(zs, pack2(c[0], c[1]), pack2(c[2], c[3]));
        if (warp == 1) TS(24);
      } while (__builtin_expect(bar_or(N_ZM, 160, false), 0));
      uint32_t b0[4], b1[4];
      if (warp == 2) {
        TS(1);
        ldsm4(b0, zl);
        ldsm4(b1, zl + 4 * 640);
        const float2 e = mma_rows8(a[0], a[1], b0, b1);
        if (rec) { stg2r(smm, tagf(e.x, tag), tagf(e.y, tag)); stg2r(smm + XC_TWIN, tagf(e.x, tag), tagf(e.y, tag)); }
        if (lane == 0) mbar_arrive(bar + 8 * B_YM);
        TS(2);
      }
      bar_sync(N_SS, 128);
      if (s >= 2) token_send(s - 2);
      if (warp != 2) {
        const uint32_t st = sta + (s & 1) * 5632, aq = xq + (s & 3) * XB;
        uint32_t b2[4], b3[4], b4[4], b5[4];
        ldsm4(a[0], aq); ldsm4(b0, zl); ldsm4(b2, zl + 128); ldsm4(b4, zl + 256); ldsm4(a[1], aq ^ 32);
        ldsm4(a[2], aq ^ 64); ldsm4(b1, zl + 2560); ldsm4(b3, zl + 2560 + 128); ldsm4(b5, zl + 2560 + 256); ldsm4(a[3], aq ^ 96);
        float e0[4] = {0.f, 0.f, 0.f, 0.f}, e1[4] = {0.f, 0.f, 0.f, 0.f}, e2[4] = {0.f, 0.f, 0.f, 0.f};
        mma16(e0, a[0][0], a[0][1], a[0][2], a[0][3], b0[0], b0[1]);
        mma16(e1, a[0][0], a[0][1], a[0][2], a[0][3], b2[0], b2[1]);
        mma16(e2, a[0][0], a[0][1], a[0][2], a[0][3], b4[0], b4[1]);
        mma16(e0, a[1][0], a[1][1], a[1][2], a[1][3], b0[2], b0[3]);
        mma16(e1, a[1][0], a[1][1], a[1][2], a[1][3], b2[2], b2[3]);
        mma16(e2, a[1][0], a[1][1], a[1][2], a[1][3], b4[2], b4[3]);
        mma16(e0, a[2][0], a[2][1], a[2][2], a[2][3], b1[0], b1[1]);
        mma16(e1, a[2][0], a[2][1], a[2][2], a[2][3], b3[0], b3[1]);
        mma16(e2, a[2][0], a[2][1], a[2][2], a[2][3], b5[0], b5[1]);
        mma16(e0, a[3][0], a[3][1], a[3][2], a[3][3], b1[2], b1[3]);
        mma16(e1, a[3][0], a[3][1], a[3][2], a[3][3], b3[2], b3[3]);
        mma16(e2, a[3][0], a[3][1], a[3][2], a[3][3], b5[2], b5[3]);
        sts_f4(st, e0[0], e0[1], e0[2], 1.f);
        sts_f4(st + 512, e0[3], e1[0], e1[1], 1.f);
        sts_f4(st + 1024, e1[2], e1[3], n0 ? 0.f : e2[0], 1.f);
        if (n0 == 0) sts_f4(st + 1536, e2[1], e2[2], e2[3], 1.f);
        if (warp == 1) TS(19);
        asm volatile("fence.proxy.async.shared::cta;" ::: "memory");
        __syncwarp();
        if (lane == 0) mbar_arrive(bar + 8 * (B_T + (s & 1)));
      }
      if (s) token_pv(s - 1);
      if (warp == 1) TS(5);
      if (rec) {
        float d[16];
        if (warp == 1) TS(16);
        mbar_wait(bar + 8 * (B_X + ((s + 1) & 3)), ((s + 1) >> 2) & 1, lim);
        bar_sync(N_ZX, 256);
        if (warp == 1) TS(17);
        gemm_x_issue(w, sb + ((s + 1) & 3) * XB, d);
        wg_wait<0>();
        reg_fence(d);
        if (warp == 1) TS(18);
        const uint32_t zn = zst + ((s + 1) & 1) * 5120;
        stsm4t(zn + 8 * 16, pack2(d[0], d[1]), pack2(d[2], d[3]), pack2(d[4], d[5]), pack2(d[6], d[7]));
        stsm4t(zn + 24 * 16, pack2(d[8], d[9]), pack2(d[10], d[11]), pack2(d[12], d[13]), pack2(d[14], d[15]));
        if (warp == 2) TS(3);
      }
    }
    token_send(NSEG - 2);
    bar_sync(N_ST, 256);
    token_pv(NSEG - 1);
    token_send(NSEG - 1);
    if (lim <= 0) g_err = 1;
    __syncwarp();
    if (warp == 0) PTS(25);
    cluster_arrive_relaxed();
    cluster_wait();
  } else if (warp < 8) {
    asm volatile("setmaxnreg.inc.sync.aligned.u32 216;");
    const int wq = warp - 4;
    uint32_t w[28][4];
    build_weights<1>(w, sb, lim, lane);
    cluster_wait();
    cluster_arrive_relaxed();
    uint32_t yx[8], ym[2];
    {
      float d[16];
      mbar_wait(bar + 8 * B_X, 0, lim);
      gemm_x(w, sb, d);
#pragma unroll
      for (int i = 0; i < 8; i++) yx[i] = pack2(d[2 * i], d[2 * i + 1]);
      cluster_wait();
    }
    const int ri = lane >> 2, q = lane & 3;
    uint32_t rs_a = mapa(sb + O_RS + h * 128 + ((ri & 1) * 4 + q) * 16, 4 * wq + (ri >> 1));
    uint32_t rs_b = mapa(bar + 8 * B_RS, 4 * wq + (ri >> 1));
    uint32_t mimg = sb + O_MIMG + lane * 16, l8 = sb + lane * 8;
    for (int k = wq; k < 22; k += 4) sts_u2(sb + O_GX + k * 256 + lane * 8, 0, 0);
    asm volatile("fence.proxy.async.shared::cta;" ::: "memory");
    bar_sync(N_INIT, 160);
    const uint32_t yb = sb + O_YB + (tid & 127) * 16;
    sts_u4(yb, yx[0], yx[4], yx[1], yx[5]);
    sts_u4(yb + 2048, yx[2], yx[6], yx[3], yx[7]);
    pin(rs_a); pin(rs_b); pin(mimg); pin(l8);

#pragma unroll 1
    for (int s = 0; s < NSEG; s++) {
      const bool rec = s < NSEG - 1;
      uint32_t img = mimg + (s & 1) * 7168, tag = ((s >> 1) + 1) & 3;
      uint32_t ra = rs_a + (s & 1) * 2048, rb = rs_b + (s & 1) * 8;
      pin(img); pin(tag); pin(ra); pin(rb);
      if (rec) {
        while (__all_sync(0xffffffffu, (int)lds32v(sb + O_C3) < s - 2) && --lim > 0) {}
      }
      if (wq == 0) TS(20);
      mbar_wait(bar + 8 * B_YM, s & 1, lim);
      float c[4];
      {
        const uint64_t dm = (uint64_t)(((sb + O_MIMG + (s & 1) * 7168) >> 4) & 0x3fff) | (8ull << 16) | (8ull << 32);
        wg_fence();
#pragma unroll
        for (int k = 0; k < 28; k++) wgmma_n8_rs(c, w[k], dm + k * 16, k != 0);
        wg_commit();
        if (wq == 0) TS(21);
      }
      float v[4][4], mxl = 0.f;
      if (rec) {
        const float full = 7.f * (s + 1);
        do {
#pragma unroll
          for (int n = 0; n < 4; n++)
            asm volatile("ld.volatile.shared.v4.f32 {%0,%1,%2,%3}, [%4];" : "=f"(v[n][0]), "=f"(v[n][1]), "=f"(v[n][2]), "=f"(v[n][3]) : "r"(mimg + (O_GY - O_MIMG) + n * 512) : "memory");
        } while (__any_sync(0xffffffffu, (v[0][2] + v[0][3] != full) | (v[1][2] + v[1][3] != full) | (v[2][2] + v[2][3] != full) | (v[3][2] + v[3][3] != full)) && --lim > 0);
        sts32v(sb + O_DONE + 8, s + 1);
        mxl = fmaxf(fmaxf(fmaxf(v[0][0], v[0][1]), fmaxf(v[1][0], v[1][1])), fmaxf(fmaxf(v[2][0], v[2][1]), fmaxf(v[3][0], v[3][1])));
        if (wq == 0) TS(22);
      }
      wg_wait<0>();
      reg_fence(c);
      ym[0] = pack2(c[0], c[1]);
      ym[1] = pack2(c[2], c[3]);
      if (rec) {
        uint32_t vm[14];
        const uint32_t gx = l8 + O_GX + (s & 1) * 1792;
        do {
#pragma unroll
          for (int k = 0; k < 7; k++) asm volatile("ld.volatile.shared.v2.u32 {%0,%1}, [%2];" : "=r"(vm[2 * k]), "=r"(vm[2 * k + 1]) : "r"(gx + k * 256) : "memory");
        } while (__any_sync(0xffffffffu, stale7(vm, tag)) && --lim > 0);
        sts32v(sb + O_DONE, s + 1);
        const float2 sm = add7(vm);
        if (wq == 0) TS(8);
        const float mx = qmax(fmaxf(mxl, fmaxf(sm.x, sm.y)));
        const float nb = -mx * SC2;
        uint32_t pa[4];
        float l = 0.f;
#pragma unroll
        for (int n = 0; n < 4; n++) {
          const float p0 = ex2(fmaf(v[n][0], SC2, nb)), p1 = ex2(fmaf(v[n][1], SC2, nb));
          l += p0 + p1;
          pa[n] = pack2(p0, p1);
        }
        float o0[4] = {0.f, 0.f, 0.f, 0.f}, o1[4] = {0.f, 0.f, 0.f, 0.f}, u0[4] = {0.f, 0.f, 0.f, 0.f}, u1[4] = {0.f, 0.f, 0.f, 0.f};
        mma16v(o0, pa[0], pa[1], pa[2], pa[3], yx[0], yx[4]);
        mma16v(o1, pa[0], pa[1], pa[2], pa[3], yx[1], yx[5]);
        mma16v(u0, pa[0], pa[1], pa[2], pa[3], yx[2], yx[6]);
        mma16v(u1, pa[0], pa[1], pa[2], pa[3], yx[3], yx[7]);
        const float p0 = ex2(fmaf(sm.x, SC2, nb)), p1 = ex2(fmaf(sm.y, SC2, nb));
        const uint32_t pp = pack2(p0, p1);
        mma8v(o0, pp, pp, ym[0]);
        mma8v(o1, pp, pp, ym[1]);
        const float inv = rcp(qsum(l + (p0 + p1)));
        st_async4(ra, (o0[0] + u0[2]) * inv, (o0[1] + u0[3]) * inv, (o1[0] + u1[2]) * inv, (o1[1] + u1[3]) * inv, rb);
      }
      sts_u2(yb + 4096 - (tid & 127) * 8 + (s & 1) * 5120, ym[0], ym[1]);
      if (!rec) bar_arrive(N_ST, 256);
      if (rec) {
        bar_arrive(N_ZX, 256);
        if (wq == 0) TS(9);
      }
      if (rec) {
        float d[16];
        mbar_wait(bar + 8 * (B_X + ((s + 1) & 3)), ((s + 1) >> 2) & 1, lim);
        gemm_x(w, sb + ((s + 1) & 3) * XB, d);
#pragma unroll
        for (int i = 0; i < 8; i++) yx[i] = pack2(d[2 * i], d[2 * i + 1]);
        sts_u4(yb + ((s + 1) & 1) * 5120, yx[0], yx[4], yx[1], yx[5]);
        sts_u4(yb + ((s + 1) & 1) * 5120 + 2048, yx[2], yx[6], yx[3], yx[7]);
        if (wq == 0) TS(10);
      }
    }
    if (lim <= 0) g_err = 1;
    __syncwarp();
    cluster_arrive_relaxed();
    cluster_wait();
  } else {
    asm volatile("setmaxnreg.dec.sync.aligned.u32 72;");
    if (warp == 8) {
      const int u = lane >> 2, comp = lane & 3;
      uint8_t* gm0 = xch(16) + (XC_R0 + (8 * j + 2 * (h >> 2) + (comp >> 1)) * 128 + (2 * (h & 3) + (u >> 2)) * 16 + ((u & 3) * 2 + (comp & 1)) * 2);
#pragma unroll
      for (int k = 0; k < 6; k++) stg16r(gm0 + k * XC_TWIN, 0xffff);
      cluster_wait();
      if (lane == 0) {
        int lim1 = SPIN_LIMIT;
        if (h < 7) tma2d_mc(sb + h * 4096, &tmX, h * 64, 0, bar + 8 * B_X);
#pragma unroll 1
        for (int c = 4; c < 16; c++) {
          const int st = c & 3;
          mbar_wait1(bar + 8 * (B_PE + st), ((c >> 2) - 1) & 1, lim1);
          mbar_expect(bar + 8 * (B_PF + st), XB);
          tma2d(sb + (st + 1) * XB, (c & 1) ? &tmWv : &tmWk, h * DH + ((c >> 1) & 3) * 64, (c >> 3) * 224, bar + 8 * (B_PF + st));
        }
      }
      __syncwarp();
      cluster_arrive();
      cluster_wait();
      if (lane == 0) {
        for (int k = 1; k < 3; k++) {
          mbar_expect(bar + 8 * (B_X + k), XB);
          if (h < 7) tma2d_mc(sb + k * XB + h * 4096, &tmX, h * 64, k * 32, bar + 8 * (B_X + k));
        }
      }
      uint32_t chk = sb + O_MIMG + lane * 32 + (lane >> 2) * 4, rs0 = sb + O_RS + lane * 4;
      const uint8_t* gnear = xch(16) + (XC_R0 + __shfl_sync(0xffffffffu, lds32v(sb + O_NEAR + 4), 0));
      const uint32_t pc_st = sb + O_PC + ((comp >> 1) * 2 + (u >> 2)) * 16 + ((u & 3) * 2 + (comp & 1)) * 2;
      const uint32_t mj_a = mapa(sb + O_MJ + (2 * (h >> 2) + ((lane >> 1) & 1)) * 128 + (2 * (h & 3) + (lane & 1)) * 16, lane >> 2);
      const uint32_t mj_b = mapa(bar + 8 * B_MJ, lane >> 2), mj_st = mapa(sb, 8) - mapa(sb, 0);
      pin(chk); pin(rs0); pinp(gm0);
      const uint32_t m2r = mapa(bar + 8 * (B_M2 + 1), lane & 15);
      auto cl_sync_arrive = [&](uint32_t a) { if (lane < 16) asm volatile("mbarrier.arrive.relaxed.cluster.shared::cluster.b64 _, [%0];" :: "r"(a) : "memory"); __syncwarp(); };
      const uint8_t* p_gsrc = xch(h) + (XC_R0 + 2 * XC_REG + __shfl_sync(0xffffffffu, lds32v(sb + O_NEAR), 0));
      bar_sync(N_INIT, 160);
      uint32_t m2p = 0;
      int s3 = 0;
#pragma unroll 1
      for (int s = 0; s < NSEG; s++) {
        uint32_t ck = chk + (s & 1) * 7168;
        pin(ck);
        bool redo = false;
        if (s) {
          mbar_wait(bar + 8 * (B_M + (s & 1)), ((s - 1) >> 1) & 1, lim);
          while (true) {
            uint32_t v[7];
#pragma unroll
            for (int k = 0; k < 7; k++) v[k] = lds32v(ck + k * 1024);
            const uint32_t mx = __vimax3_u32(__vimax3_u32(v[0], v[1], v[2]), __vimax3_u32(v[3], v[4], v[5]), v[6]);
            if (__builtin_expect(!__any_sync(0xffffffffu, mx == 0xffffffffu) || lim <= 0, 1)) break;
            redo = true;
            cl_sync_arrive(m2r);
            if (elect()) mbar_expect(bar + 8 * B_M2, 7168);
            mbar_wait(bar + 8 * (B_M2 + 1), m2p, lim);
            if (elect()) bulk_mc(sb + O_MIMG + (s & 1) * 7168 + h * 448, gnear + s3 * XC_REG + h * 448, 448, bar + 8 * B_M2);
            mbar_wait(bar + 8 * B_M2, m2p, lim);
            m2p ^= 1;
          }
        }
        TS(23);
        if (bar_or(N_ZM, 160, redo)) bar_or(N_ZM, 160, false);
        if (s == NSEG - 1) break;
        {
          const uint32_t tz = clk();
          const uint8_t* gsrc = p_gsrc + (s & 1) * 1792;
          const bool el = elect();
          uint32_t td = D_S;
          bool xd = false;
          int k = 0;
          do {
            delay_until(tz, td);
            const bool fx = !xd && (k % XEV) == 0, fs = k >= SD0;
            k++;
            if (el) {
              asm volatile("mbarrier.expect_tx.relaxed.cta.shared::cta.b64 [%0], %1;" :: "r"(bar + 8 * B_G), "r"((fx ? 2048 : 0) + (fs ? 1792 : 0)) : "memory");
              if (fs) bulk_ld(sb + O_GX + (s & 1) * 1792, gsrc, 1792, bar + 8 * B_G);
              if (fx) bulk_ld(sb + O_GY, &g_xacc[s & 3][h][0], 2048, bar + 8 * B_G);
            }
            td += D_SS;
            xd = __all_sync(0xffffffffu, (int)lds32v(sb + O_DONE + 8) > s);
          } while (__all_sync(0xffffffffu, (int)lds32v(sb + O_DONE) <= s) && --lim > 0);
        }
        const int s3n = s3 == 2 ? 0 : s3 + 1;
        uint32_t rb = rs0 + (s & 1) * 2048;
        uint8_t* gm = gm0 + s3n * XC_REG;
        const uint32_t mdst = sb + O_MIMG + ((s + 1) & 1) * 7168 + h * 448, mb = bar + 8 * (B_M + ((s + 1) & 1));
        const uint8_t* msrc = gnear + s3n * XC_REG + h * 448;
        s3 = s3n;
        pin(rb); pinp(gm);
        mbar_wait(bar + 8 * (B_RS + (s & 1)), (s >> 1) & 1, lim);
        TS(11);
        float v[16];
#pragma unroll
        for (int k = 0; k < 16; k++) v[k] = lds_f(rb + k * 128);
        const float sum = (((v[0] + v[1]) + (v[2] + v[3])) + ((v[4] + v[5]) + (v[6] + v[7]))) +
                          (((v[8] + v[9]) + (v[10] + v[11])) + ((v[12] + v[13]) + (v[14] + v[15])));
        stg16r(gm, (uint16_t)(pack2(sum, 0.f) & 0xffff));
        stg16r(gm + XC_TWIN, (uint16_t)(pack2(sum, 0.f) & 0xffff));
        const uint32_t tm = clk();
        TS(12);
        asm volatile("st.shared.u16 [%0], %1;" :: "r"(pc_st), "h"((uint16_t)(pack2(sum, 0.f) & 0xffff)) : "memory");
        __syncwarp();
        const float4 pc = lds_f4(sb + O_PC + (lane & 3) * 16);
        if (s < NSEG - 2) {
          const uint32_t o = ((s + 1) & 1) * 1024, ob = ((s + 1) & 1) * 8;
          st_async4(mj_a + o, pc.x, pc.y, pc.z, pc.w, mj_b + ob);
          st_async4(mj_a + o + mj_st, pc.x, pc.y, pc.z, pc.w, mj_b + ob + mj_st);
        }
        const bool el = elect();
        if (el) mbar_expect(bar + 8 * (B_RS + (s & 1)), 2048);
        delay_until(tm, D_M);
        TS(25);
        if (el) bulk_mc(mdst, msrc, 448, mb);
      }
      if (elect()) mbar_arrive(bar + 8 * B_G);
      mbar_wait(bar + 8 * B_G, 0, lim);
    } else if (warp < 11) {
      const int mt = warp - 9, q = lane & 3;
#pragma unroll
      for (int t = mt * 32 + lane; t < 448; t += 64) {
        const uint4 v = *reinterpret_cast<const uint4*>(mem0 + (t & 7) * DM + (t >> 3) * 8);
        sts_u4(sb + O_MIMG + t * 16, v.x, v.y, v.z, v.w);
      }
      asm volatile("fence.proxy.async.shared::cta;" ::: "memory");
      if (mt == 1 && lane == 0) sts32v(sb + O_NEAR + 4, near_copy(xch(16) + 2 * XC_REG - (blockIdx.x % 7) * 128));
      __syncwarp();
      cluster_wait();
      cluster_arrive();
      cluster_wait();
      uint8_t* gm0 = xch(16) + (XC_R0 + (8 * j + 2 * (h >> 2) + (q >> 1)) * 128 + (2 * (h & 3) + (lane >> 4)) * 16 + (((lane >> 2) & 3) * 2 + (q & 1)) * 2);
      int s3p = 2;
#pragma unroll 1
      for (int s = 0; s < NSEG; s++) {
        mbar_wait(bar + 8 * (B_T + (s & 1)), (s >> 1) & 1, lim);
        if (s < NSEG - 1) while (__all_sync(0xffffffffu, (int)lds32v(sb + O_DONE) <= s) && --lim > 0) delay_until(clk(), 64);
        if (mt == 1 && s < NSEG - 1) {
          if (elect()) {
            mbar_expect(bar + 8 * (B_M + ((s + 1) & 1)), 7168);
            if (s < NSEG - 2) mbar_expect(bar + 8 * (B_MJ + ((s + 1) & 1)), 1024);
            if (s >= 1 && s + 2 < NSEG) {
              mbar_expect(bar + 8 * (B_X + ((s + 2) & 3)), XB);
              if (h < 7) tma2d_mc(sb + ((s + 2) & 3) * XB + h * 4096, &tmX, h * 64, (s + 2) * 32, bar + 8 * (B_X + ((s + 2) & 3)));
            }
          }
          stg16r(gm0 + s3p * XC_REG, 0xffff);
          stg16r(gm0 + s3p * XC_REG + XC_TWIN, 0xffff);
          s3p = s3p == 2 ? 0 : s3p + 1;
        }
        const uint32_t t0 = clk();
        if (mt == 0 && elect()) {
          asm volatile("cp.reduce.async.bulk.global.shared::cta.bulk_group.add.f32 [%0], [%1], 5632;" :: "l"(&g_sacc[s & 7][h][0]), "r"(sb + O_ST + (s & 1) * 5632) : "memory");
          asm volatile("cp.async.bulk.commit_group;" ::: "memory");
          asm volatile("cp.async.bulk.wait_group.read 0;" ::: "memory");
        }
        __syncwarp();
        delay_until(t0, s == NSEG - 1 ? D_TL : D_T);
        if (mt) TS(28);
        const float4* sp = reinterpret_cast<const float4*>(&g_sacc[s & 7][h][mt * 512 + lane * 4]);
        float u[7][4];
        bool stale;
        do {
          stale = false;
#pragma unroll
          for (int c = 0; c < 7; c++) {
            u[c][0] = u[c][1] = u[c][2] = 0.f; u[c][3] = 7.f;
            if (c < 4 || mt)
              asm volatile("ld.relaxed.gpu.global.v4.f32 {%0,%1,%2,%3}, [%4];" : "=f"(u[c][0]), "=f"(u[c][1]), "=f"(u[c][2]), "=f"(u[c][3]) : "l"(sp + c * 32) : "memory");
          }
#pragma unroll
          for (int c = 0; c < 7; c++) stale |= u[c][3] != 7.f;
        } while (__any_sync(0xffffffffu, stale) && --lim > 0);
        if (mt) TS(29);
        uint32_t pk[2][5];
        float v[2][10];
#pragma unroll
        for (int e = 0; e < 10; e++) {
          const int i = 4 * (e >> 1) + (e & 1);
          v[0][e] = u[i / 3][i % 3];
          v[1][e] = u[(i + 2) / 3][(i + 2) % 3];
        }
#pragma unroll
        for (int rg = 0; rg < 2; rg++) {
          const int row = 16 * mt + 8 * rg + (lane >> 2);
#pragma unroll
          for (int e = 2; e < 10; e++)
            if (8 * ((e >> 1) - 1) + 2 * q + (e & 1) > row) v[rg][e] = MASKV;
          float mx = v[rg][0];
#pragma unroll
          for (int e = 1; e < 10; e++) mx = fmaxf(mx, v[rg][e]);
          mx = qmax(mx);
          const float nb = -mx * SC2;
          float l = 0.f;
#pragma unroll
          for (int e = 0; e < 10; e++) { v[rg][e] = ex2(fmaf(v[rg][e], SC2, nb)); l += v[rg][e]; }
          const float inv = rcp(qsum(l));
#pragma unroll
          for (int n = 0; n < 5; n++) pk[rg][n] = pack2(v[rg][2 * n] * inv, v[rg][2 * n + 1] * inv);
        }
        const uint32_t pb = sb + O_P + (s & 1) * 2560 + mt * 1280;
        sts_u4(pb + lane * 16, pk[0][1], pk[1][1], pk[0][3], pk[1][3]);
        sts_u4(pb + 512 + lane * 16, pk[0][2], pk[1][2], pk[0][4], pk[1][4]);
        sts_u2(pb + 1024 + lane * 8, pk[0][0], pk[1][0]);
        __syncwarp();
        if (lane == 0) mbar_arrive(bar + 8 * (B_P + (s & 1)));
        if (mt == 1) TS(13);
        if (j + 7 * mt < 11) asm volatile("st.relaxed.gpu.global.v4.f32 [%0], {%1,%1,%1,%1};" :: "l"(&g_sacc[(s + 4) & 7][h][(j + 7 * mt) * 128 + lane * 4]), "f"(0.f) : "memory");
      }
    } else {
      const int t1 = lane >> 4, l16 = lane & 15;
      const int col = j * 64 + ((lane >> 2) & 3) * 16 + (lane & 3) * 2;
      const uint32_t epoch = ldg1r(&g_ticket[0]) / 112 + 1;
      if (lane == 0) {
        sts32v(sb + O_NEAR, near_copy(xch(h)));
      }
      __syncwarp();
      cluster_wait();
      cluster_arrive();
      cluster_wait();
      const int trow = 16 * (h >> 3) + (h & 7) + 8 * t1;
      const uint32_t xg = sb + trow * 128 + (((l16 >> 1) ^ (trow & 7)) << 4) + (l16 & 1) * 8;
      auto gate = [&](int sg) {
        mbar_wait(bar + 8 * (B_X + (sg & 3)), (sg >> 2) & 1, lim);
        float z = 0.f;
#pragma unroll 1
        for (int k = 0; k < 7; k++) {
          const uint2 xv = lds_u2(xg + (sg & 3) * XB + k * 4096);
          const uint2 gw = *reinterpret_cast<const uint2*>(gate_w + (k * 16 + l16) * 4);
          z = fmaf(bf_lo(xv.x), bf_lo(gw.x), z); z = fmaf(bf_hi(xv.x), bf_hi(gw.x), z);
          z = fmaf(bf_lo(xv.y), bf_lo(gw.y), z); z = fmaf(bf_hi(xv.y), bf_hi(gw.y), z);
        }
#pragma unroll
        for (int o = 1; o < 16; o <<= 1) z += __shfl_xor_sync(0xffffffffu, z, o);
        return rcp(1.f + ex2(-1.4426950408889634f * z));
      };
      float4 pa4 = make_float4(0.f, 0.f, 0.f, 0.f);
      bool pend = false;
      auto finish = [&](int sg) {
        if (ldg1r(&g_bflag[sg >> 1][j >> 2][0]) == epoch) {
          const int o = (sg * 32 + trow) * DM + col;
          uint32_t b0, b1, b2, b3;
          ldg2r(b0, b1, g_b + o); ldg2r(b2, b3, g_b + o + 8);
          uint32_t* op = reinterpret_cast<uint32_t*>(out + o);
          op[0] = pack2(pa4.x + __uint_as_float(b0), pa4.y + __uint_as_float(b1));
          op[4] = pack2(pa4.z + __uint_as_float(b2), pa4.w + __uint_as_float(b3));
        }
      };
      float g1 = gate(0), g2 = gate(1);
#pragma unroll 1
      for (int s = 0; s < NSEG; s++) {
        const int tok = s * 32 + trow;
        const bool have_b = ldg1r(&g_bflag[s >> 1][j >> 2][0]) == epoch;
        const float* bp = &g_b[tok * DM + col];
        uint32_t b0 = 0, b1 = 0, b2 = 0, b3 = 0;
        if (have_b) { ldg2r(b0, b1, bp); ldg2r(b2, b3, bp + 8); }
        const bool last = s >= NSEG - 2;
        mbar_wait(bar + 8 * ((last ? B_OL : B_O) + (s & 1)), last ? 0 : (s >> 1) & 1, lim);
        if (pend) { if (s >= NSEG - 2) __threadfence(); finish(s - 1); }
        if (lane < 19 && j * 19 + lane < 128)
          asm volatile("st.relaxed.gpu.global.v4.f32 [%0], {%1,%1,%1,%1};" :: "l"(&g_xacc[s & 3][h][(j * 19 + lane) * 4]), "f"(0.f) : "memory");
        const float g = g1;
        g1 = g2;
        if (s + 2 < NSEG) g2 = gate(s + 2);
        const uint32_t ob = sb + O_ORS + ((last ? 2 : 0) + (s & 1)) * 4096 + t1 * 2048 + l16 * 16;
        float e[8] = {0.f, 0.f, 0.f, 0.f, 0.f, 0.f, 0.f, 0.f};
#pragma unroll 2
        for (int k = 0; k < 8; k++) {
          const uint4 c = lds_u4(ob + k * 256);
          e[0] += bf_lo(c.x); e[1] += bf_hi(c.x); e[2] += bf_lo(c.y); e[3] += bf_hi(c.y);
          e[4] += bf_lo(c.z); e[5] += bf_hi(c.z); e[6] += bf_lo(c.w); e[7] += bf_hi(c.w);
        }
        float4 a;
        a.x = g * ((t1 ? e[4] : e[0]) + __shfl_xor_sync(0xffffffffu, t1 ? e[0] : e[4], 16));
        a.y = g * ((t1 ? e[5] : e[1]) + __shfl_xor_sync(0xffffffffu, t1 ? e[1] : e[5], 16));
        a.z = g * ((t1 ? e[6] : e[2]) + __shfl_xor_sync(0xffffffffu, t1 ? e[2] : e[6], 16));
        a.w = g * ((t1 ? e[7] : e[3]) + __shfl_xor_sync(0xffffffffu, t1 ? e[3] : e[7], 16));
        __syncwarp();
        if (lane == 0 && s < NSEG - 4) mbar_expect(bar + 8 * (B_O + (s & 1)), 4096);
        if (lane == 0) sts32v(sb + O_C3, s + 1);
        if (s == 63) PTS(30);
        float* sp = &g_stash[tok * DM + col];
        stg2r(sp, tagf(a.x, epoch & 3), tagf(a.y, epoch & 3));
        stg2r(sp + 8, tagf(a.z, epoch & 3), tagf(a.w, epoch & 3));
        if (have_b) {
          uint32_t* op = reinterpret_cast<uint32_t*>(out + tok * DM + col);
          op[0] = pack2(a.x + __uint_as_float(b0), a.y + __uint_as_float(b1));
          op[4] = pack2(a.z + __uint_as_float(b2), a.w + __uint_as_float(b3));
        }
        pend = !have_b;
        pa4 = a;
        TS(14);
      }
      if (pend) { __threadfence(); finish(NSEG - 1); }
      if (lane == 0) atomicAdd(&g_ticket[0], 1);
    }
    if (lim <= 0) g_err = 1;
    __syncwarp();
    cluster_arrive_relaxed();
    cluster_wait();
  }
}

constexpr uint32_t F_STAGE = 49152, F_BAR = 4 * F_STAGE, F_G = F_BAR + 128, F_M = F_G + 512, F_SMEM = F_M + 1024 + 1024;

template <int N>
DEVI void ffn_tile(float (&d)[N / 2], uint32_t sb, int wg, int nk, int& it, int& dead, int lane) {
#pragma unroll 1
  for (int k = 0; k < nk; k++, it++) {
    const int st = it & 3;
    mbar_wait(sb + F_BAR + 8 * st, (it >> 2) & 1, dead);
    const uint64_t da = desc128(sb + st * F_STAGE + wg * 8192, 1), db = desc128(sb + st * F_STAGE + 16384, 512);
    wg_fence();
#pragma unroll
    for (int kk = 0; kk < 4; kk++) {
      if constexpr (N == 256) wgmma_n256_kn(d, da + kk * 2, db + kk * 128, (k | kk) != 0);
      else                    wgmma_n192_kn(d, da + kk * 2, db + kk * 128, (k | kk) != 0);
    }
    wg_commit();
    if (k) { wg_wait<1>(); if (lane == 0) mbar_arrive(sb + F_BAR + 32 + 8 * ((it - 1) & 3)); }
  }
  wg_wait<0>();
  if (lane == 0) mbar_arrive(sb + F_BAR + 32 + 8 * ((it - 1) & 3));
  reg_fence(d);
}

template <int NJ>
DEVI void ffn_finish(float (&d)[NJ * 32], float g0, float g1, uint32_t sb, int r0, int row, int j0, uint32_t epoch,
                     __nv_bfloat16* __restrict__ out, int tid) {
  const int wg = tid >> 7, t = tid & 127, off = (r0 + row) * DM + j0 * 64 + 2 * (tid & 3);
#pragma unroll
  for (int n = 0; n < NJ * 8; n++) {
    d[4 * n] *= g0; d[4 * n + 1] *= g0; d[4 * n + 2] *= g1; d[4 * n + 3] *= g1;
    *reinterpret_cast<float2*>(g_b + off + n * 8) = make_float2(d[4 * n], d[4 * n + 1]);
    *reinterpret_cast<float2*>(g_b + off + 8 * DM + n * 8) = make_float2(d[4 * n + 2], d[4 * n + 3]);
  }
  asm volatile("fence.release.gpu;" ::: "memory");
  bar_sync(2 + wg, 128);
  if (t == 0) {
    asm volatile("st.relaxed.gpu.global.u32 [%0], %1;" :: "l"(&g_bflag[(r0 >> 6) + wg][j0 >> 2][0]), "r"(epoch) : "memory");
    __threadfence();
  }
  bar_sync(2 + wg, 128);
#pragma unroll
  for (int n0 = 0; n0 < NJ * 8; n0 += 8) {
    uint32_t a[8][4];
#pragma unroll
    for (int n = 0; n < 8; n++) { ldg2r(a[n][0], a[n][1], g_stash + off + (n0 + n) * 8); ldg2r(a[n][2], a[n][3], g_stash + off + 8 * DM + (n0 + n) * 8); }
#pragma unroll
    for (int n = 0; n < 8; n++)
#pragma unroll
      for (int half = 0; half < 2; half++)
        if (((a[n][2 * half] ^ epoch) & 3) == 0)
          *reinterpret_cast<uint32_t*>(out + off + half * 8 * DM + (n0 + n) * 8) =
              pack2(__uint_as_float(a[n][2 * half]) + d[4 * (n0 + n) + 2 * half], __uint_as_float(a[n][2 * half + 1]) + d[4 * (n0 + n) + 2 * half + 1]);
  }
}

__global__ void __launch_bounds__(384, 1)
ffn_kernel(const __grid_constant__ CUtensorMap tmX, const __grid_constant__ CUtensorMap tmW1,
           const __grid_constant__ CUtensorMap tmH, const __grid_constant__ CUtensorMap tmW2,
           const __nv_bfloat16* __restrict__ x, const __nv_bfloat16* __restrict__ gate_w, __nv_bfloat16* __restrict__ out) {
  extern __shared__ uint8_t smem_raw[];
  const uint32_t sb = (smem_u32(smem_raw) + 1023) & ~1023u;
  const uint32_t hbar = sb + F_BAR + 64;
  int dead = SPIN_LIMIT;
  const int tid = threadIdx.x, lane = tid & 31, warp = __shfl_sync(0xffffffffu, tid >> 5, 0), r0 = blockIdx.x * 128;
  if (tid == 0) {
    for (int i = 0; i < 4; i++) { mbar_init(sb + F_BAR + 8 * i, 1); mbar_init(sb + F_BAR + 32 + 8 * i, 8); }
    mbar_init(hbar, 256);
    asm volatile("fence.mbarrier_init.release.cluster;" ::: "memory");
    asm volatile("fence.proxy.async.shared::cta;" ::: "memory");
  }
  __syncthreads();
  if (warp >= 8) {
    asm volatile("setmaxnreg.dec.sync.aligned.u32 56;");
    if (tid == 256) {
      int it = 0;
#pragma unroll 1
      for (int t = 0; t < 9; t++) {
        const int nk = t < 7 ? 7 : 28, nb = t < 8 ? 4 : 3;
        if (t == 7) mbar_wait1(hbar, 0, dead);
#pragma unroll 1
        for (int k = 0; k < nk; k++, it++) {
          const int st = it & 3;
          const uint32_t fb = sb + F_BAR + 8 * st, a = sb + st * F_STAGE;
          if (it >= 4) mbar_wait1(fb + 32, ((it >> 2) - 1) & 1, dead);
          mbar_expect(fb, 16384 + nb * 8192);
          tma2d(a, t < 7 ? &tmX : &tmH, k * 64, r0, fb);
          for (int b = 0; b < nb; b++) tma2d(a + 16384 + b * 8192, t < 7 ? &tmW1 : &tmW2, (t < 7 ? t : t - 7) * 256 + b * 64, k * 64, fb);
        }
      }
    } else if (warp > 8) {
      const int l16 = lane & 15;
      for (int r = (warp - 9) * 2 + (lane >> 4); r < 132; r += 6) {
        const int rr = r < 128 ? r : 127;
        float z = 0.f;
#pragma unroll
        for (int k = 0; k < 7; k++) {
          const uint2 xv = *reinterpret_cast<const uint2*>(x + (r0 + rr) * DM + (k * 16 + l16) * 4);
          const uint2 gv = *reinterpret_cast<const uint2*>(gate_w + (k * 16 + l16) * 4);
          z = fmaf(bf_lo(xv.x), bf_lo(gv.x), z); z = fmaf(bf_hi(xv.x), bf_hi(gv.x), z);
          z = fmaf(bf_lo(xv.y), bf_lo(gv.y), z); z = fmaf(bf_hi(xv.y), bf_hi(gv.y), z);
        }
#pragma unroll
        for (int o = 1; o < 16; o <<= 1) z += __shfl_xor_sync(0xffffffffu, z, o);
        if (l16 == 0) sts32v(sb + F_G + rr * 4, __float_as_uint(1.f - rcp(1.f + ex2(-1.4426950408889634f * z))));
      }
      __syncwarp();
      bar_arrive(1, 352);
    }
  } else {
    asm volatile("setmaxnreg.inc.sync.aligned.u32 224;");
    const int wg = warp >> 2, row = wg * 64 + (warp & 3) * 16 + (lane >> 2), q = lane & 3;
    const uint32_t epoch = (ldg1r(&g_ticket[1]) >> 4) + 1;
    int it = 0;
#pragma unroll 1
    for (int t = 0; t < 7; t++) {
      float d[128];
      ffn_tile<256>(d, sb, wg, 7, it, dead, lane);
      __nv_bfloat16* hp = g_h + (size_t)(r0 + row) * DFF + t * 256 + 2 * q;
#pragma unroll
      for (int n = 0; n < 32; n++) {
        *reinterpret_cast<uint32_t*>(hp + n * 8) = pack2(fmaxf(d[4 * n], 0.f), fmaxf(d[4 * n + 1], 0.f));
        *reinterpret_cast<uint32_t*>(hp + 8 * DFF + n * 8) = pack2(fmaxf(d[4 * n + 2], 0.f), fmaxf(d[4 * n + 3], 0.f));
      }
    }
    __threadfence();
    asm volatile("fence.proxy.async;" ::: "memory");
    mbar_arrive(hbar);
    bar_sync(1, 352);
    const float g0 = lds_f(sb + F_G + row * 4), g1 = lds_f(sb + F_G + row * 4 + 32);
    {
      float d[128];
      ffn_tile<256>(d, sb, wg, 28, it, dead, lane);
      ffn_finish<4>(d, g0, g1, sb, r0, row, 0, epoch, out, tid);
    }
    {
      float d[96];
      ffn_tile<192>(d, sb, wg, 28, it, dead, lane);
      ffn_finish<3>(d, g0, g1, sb, r0, row, 4, epoch, out, tid);
    }
    bar_sync(1, 256);
    if (tid == 0) atomicAdd(&g_ticket[1], 1);
    if (dead <= 0) g_err = 1;
  }
}

typedef CUresult (*EncodeFn)(CUtensorMap*, CUtensorMapDataType, cuuint32_t, void*, const cuuint64_t*, const cuuint64_t*,
                             const cuuint32_t*, const cuuint32_t*, CUtensorMapInterleave, CUtensorMapSwizzle,
                             CUtensorMapL2promotion, CUtensorMapFloatOOBfill);

void make_map(EncodeFn fn, CUtensorMap* m, const void* p, uint64_t rows, uint64_t cols, uint32_t box_rows) {
  const cuuint64_t dims[2] = {cols, rows}, strides[1] = {cols * 2};
  const cuuint32_t box[2] = {64, box_rows}, es[2] = {1, 1};
  fn(m, CU_TENSOR_MAP_DATA_TYPE_BFLOAT16, 2, const_cast<void*>(p), dims, strides, box, es, CU_TENSOR_MAP_INTERLEAVE_NONE,
     CU_TENSOR_MAP_SWIZZLE_128B, CU_TENSOR_MAP_L2_PROMOTION_L2_256B, CU_TENSOR_MAP_FLOAT_OOB_FILL_NONE);
}

}

extern "C" void kernel_launch(void* const* d_in, const int* in_sizes, int n_in, void* d_out, int out_size) {
  (void)in_sizes; (void)n_in; (void)out_size;
  const __nv_bfloat16* x = (const __nv_bfloat16*)d_in[0];
  const __nv_bfloat16* mem0 = (const __nv_bfloat16*)d_in[1];
  const __nv_bfloat16* gate_w = (const __nv_bfloat16*)d_in[10];
  static EncodeFn fn = nullptr;
  static void* hptr = nullptr;
  if (!fn) {
    cudaDriverEntryPointQueryResult qr;
    cudaGetDriverEntryPoint("cuTensorMapEncodeTiled", (void**)&fn, cudaEnableDefault, &qr);
    cudaGetSymbolAddress(&hptr, g_h);
    cudaFuncSetAttribute(rmt_kernel, cudaFuncAttributeMaxDynamicSharedMemorySize, T_SMEM);
    cudaFuncSetAttribute(rmt_kernel, cudaFuncAttributeNonPortableClusterSizeAllowed, 1);
    cudaFuncSetAttribute(ffn_kernel, cudaFuncAttributeMaxDynamicSharedMemorySize, F_SMEM);
  }
  CUtensorMap mWq, mWk, mWv, mWo, mX, mXf, mW1, mH, mW2;
  make_map(fn, &mWq, d_in[2], DM, NH * DH, 64);
  make_map(fn, &mWk, d_in[3], DM, NH * DH, 224);
  make_map(fn, &mWv, d_in[4], DM, NH * DH, 224);
  make_map(fn, &mWo, d_in[5], NH * DH, DM, 256);
  make_map(fn, &mX, x, SEQ, DM, 32);
  make_map(fn, &mXf, x, SEQ, DM, 128);
  make_map(fn, &mW1, d_in[8], DM, DFF, 64);
  make_map(fn, &mH, hptr, SEQ, DFF, 128);
  make_map(fn, &mW2, d_in[9], DFF, DM, 64);

  cudaLaunchConfig_t cfg = {};
  cudaLaunchAttribute at[1];
  cfg.gridDim = dim3(112); cfg.blockDim = dim3(384); cfg.dynamicSmemBytes = T_SMEM; cfg.stream = cudaStreamPerThread;
  at[0].id = cudaLaunchAttributeClusterDimension;
  at[0].val.clusterDim.x = 16; at[0].val.clusterDim.y = 1; at[0].val.clusterDim.z = 1;
  cfg.attrs = at; cfg.numAttrs = 1;
  cudaLaunchKernelEx(&cfg, rmt_kernel, mWq, mWk, mWv, mWo, mX, x, mem0, gate_w, (__nv_bfloat16*)d_out);

  cfg.gridDim = dim3(16); cfg.dynamicSmemBytes = F_SMEM;
  at[0].id = cudaLaunchAttributeProgrammaticStreamSerialization;
  at[0].val.programmaticStreamSerializationAllowed = 1;
  cudaLaunchKernelEx(&cfg, ffn_kernel, mXf, mW1, mH, mW2, x, gate_w, (__nv_bfloat16*)d_out);
}
```

```cpp
#include <cuda_runtime.h>
#include <cuda_bf16.h>
#include <cuda.h>
#include <stdint.h>

namespace {

#define DEVI __device__ __forceinline__

constexpr int SEQ = 2048, DM = 448, NH = 16, DH = 256, NSEG = 64, DFF = 1792;
constexpr float SC2 = 1.4426950408889634f / 16.0f;
constexpr float MASKV = -1.6e10f;
constexpr int SPIN_LIMIT = 1 << 22;

#define D_M 460
#define D_X 300
#define D_T 700
#define D_SS 130
#define O_SEND 1
#define XP 2
#define D_SQ 30
#define D_XS 220
#define SD0 1
#define XEV 1
#define PFM 1
#define D_TL 450
#define D_S 180

__device__ __align__(1024) uint8_t g_xch_raw[18 * 65536];
DEVI uint8_t* xch(int blk) { return reinterpret_cast<uint8_t*>((reinterpret_cast<uintptr_t>(g_xch_raw) + 65535) & ~(uintptr_t)65535) + blk * 65536; }
constexpr uint32_t XC_R0 = 4096, XC_REG = 16384, XC_TWIN = 8192;
__device__ __align__(1024) float g_xacc[4][NH][512];
__device__ __align__(1024) float g_sacc[8][NH][1408];
__device__ __align__(1024) float g_stash[SEQ * DM];
__device__ __align__(1024) float g_b[SEQ * DM];
__device__ __align__(1024) __nv_bfloat16 g_h[SEQ * DFF];
__device__ __align__(1024) uint32_t g_bflag[32][2][8];
__device__ uint32_t g_ticket[2];
__device__ int g_err;
#define TS(i)
#define PTS(i)

DEVI uint32_t smem_u32(const void* p) { return (uint32_t)__cvta_generic_to_shared(p); }
DEVI uint32_t clk() { uint32_t c; asm volatile("mov.u32 %0, %%clock;" : "=r"(c) :: "memory"); return c; }
DEVI void mbar_init(uint32_t bar, uint32_t cnt) { asm volatile("mbarrier.init.shared::cta.b64 [%0], %1;" :: "r"(bar), "r"(cnt) : "memory"); }
DEVI void mbar_expect(uint32_t bar, uint32_t bytes) { asm volatile("mbarrier.arrive.expect_tx.shared::cta.b64 _, [%0], %1;" :: "r"(bar), "r"(bytes) : "memory"); }
DEVI void mbar_arrive(uint32_t bar) { asm volatile("mbarrier.arrive.shared::cta.b64 _, [%0];" :: "r"(bar) : "memory"); }
DEVI uint32_t lds32v(uint32_t a) { uint32_t v; asm volatile("ld.volatile.shared::cta.u32 %0, [%1];" : "=r"(v) : "r"(a) : "memory"); return v; }
DEVI void sts32v(uint32_t a, uint32_t v) { asm volatile("st.volatile.shared::cta.u32 [%0], %1;" :: "r"(a), "r"(v) : "memory"); }
DEVI void mbar_wait(uint32_t bar, uint32_t par, int& lim) {
  asm volatile("{\n.reg .pred p, q;\nWAIT_LOOP:\n"
               "mbarrier.try_wait.parity.shared::cta.b64 p, [%1], %2;\n"
               "sub.s32 %0, %0, 1;\nsetp.gt.and.s32 q, %0, 0, !p;\n@q bra.uni WAIT_LOOP;\n}"
               : "+r"(lim) : "r"(bar), "r"(par) : "memory");
}
DEVI void mbar_wait1(uint32_t bar, uint32_t par, int& lim) {
  asm volatile("{\n.reg .pred p, q;\nWAIT_LOOP:\n"
               "mbarrier.try_wait.parity.shared::cta.b64 p, [%1], %2;\n"
               "sub.s32 %0, %0, 1;\nsetp.gt.and.s32 q, %0, 0, !p;\n@q bra WAIT_LOOP;\n}"
               : "+r"(lim) : "r"(bar), "r"(par) : "memory");
}
DEVI bool elect() { uint32_t p; asm volatile("{\n.reg .pred p;\nelect.sync _|p, 0xffffffff;\nselp.u32 %0, 1, 0, p;\n}" : "=r"(p)); return p; }
DEVI void delay_until(uint32_t t0, uint32_t d) {
  asm volatile("{\n.reg .pred p;\n.reg .u32 t, u;\n.reg .u64 c;\nDELAY_LOOP:\nmov.u64 c, %%clock64;\nmov.b64 {t, u}, c;\nsub.u32 t, t, %0;\nsetp.lt.u32 p, t, %1;\n@p bra.uni DELAY_LOOP;\n}"
               :: "r"(t0), "r"(d) : "memory");
}
DEVI float rcp(float x) { float y; asm("rcp.approx.ftz.f32 %0, %1;" : "=f"(y) : "f"(x)); return y; }
DEVI uint32_t keep(uint32_t v, int lane) { return __shfl_sync(0xffffffffu, v, lane); }
template <class T> DEVI T* keepp(T* p, int lane) { return reinterpret_cast<T*>(__shfl_sync(0xffffffffu, reinterpret_cast<unsigned long long>(p), lane)); }
template <class T> DEVI void pin(T& v) { asm volatile("" : "+r"(v)); }
template <class T> DEVI void pinp(T*& v) { asm volatile("" : "+l"(v)); }
DEVI void bar_sync(int id, int n) { asm volatile("bar.sync %0, %1;" :: "r"(id), "r"(n) : "memory"); }
DEVI void bar_arrive(int id, int n) { asm volatile("bar.arrive %0, %1;" :: "r"(id), "r"(n) : "memory"); }
DEVI void cluster_arrive_relaxed() { asm volatile("barrier.cluster.arrive.relaxed.aligned;" ::: "memory"); }
DEVI void cluster_arrive() { asm volatile("barrier.cluster.arrive.release.aligned;" ::: "memory"); }
DEVI void cluster_wait() { asm volatile("barrier.cluster.wait.acquire.aligned;" ::: "memory"); }
DEVI uint32_t mapa(uint32_t a, uint32_t r) { uint32_t o; asm("mapa.shared::cluster.u32 %0, %1, %2;" : "=r"(o) : "r"(a), "r"(r)); return o; }
DEVI uint32_t pack2(float lo, float hi) { uint32_t r; asm("cvt.rn.bf16x2.f32 %0, %1, %2;" : "=r"(r) : "f"(hi), "f"(lo)); return r; }
DEVI float ex2(float x) { float y; asm("ex2.approx.ftz.f32 %0, %1;" : "=f"(y) : "f"(x)); return y; }
DEVI float bf_lo(uint32_t v) { return __uint_as_float(v << 16); }
DEVI float bf_hi(uint32_t v) { return __uint_as_float(v & 0xffff0000u); }
DEVI void ldsm4(uint32_t (&r)[4], uint32_t a) {
  asm volatile("ldmatrix.sync.aligned.m8n8.x4.shared.b16 {%0,%1,%2,%3}, [%4];" : "=r"(r[0]), "=r"(r[1]), "=r"(r[2]), "=r"(r[3]) : "r"(a) : "memory");
}
DEVI void stsm4t(uint32_t a, uint32_t r0, uint32_t r1, uint32_t r2, uint32_t r3) {
  asm volatile("stmatrix.sync.aligned.m8n8.x4.trans.shared.b16 [%0], {%1,%2,%3,%4};" :: "r"(a), "r"(r0), "r"(r1), "r"(r2), "r"(r3) : "memory");
}
DEVI void stsm2t(uint32_t a, uint32_t r0, uint32_t r1) {
  asm volatile("stmatrix.sync.aligned.m8n8.x2.trans.shared.b16 [%0], {%1,%2};" :: "r"(a), "r"(r0), "r"(r1) : "memory");
}
DEVI void mma16(float (&c)[4], uint32_t a0, uint32_t a1, uint32_t a2, uint32_t a3, uint32_t b0, uint32_t b1) {
  asm("mma.sync.aligned.m16n8k16.row.col.f32.bf16.bf16.f32 {%0,%1,%2,%3},{%4,%5,%6,%7},{%8,%9},{%0,%1,%2,%3};"
      : "+f"(c[0]), "+f"(c[1]), "+f"(c[2]), "+f"(c[3]) : "r"(a0), "r"(a1), "r"(a2), "r"(a3), "r"(b0), "r"(b1));
}
DEVI void mma8(float (&c)[4], uint32_t a0, uint32_t a1, uint32_t b0) {
  asm("mma.sync.aligned.m16n8k8.row.col.f32.bf16.bf16.f32 {%0,%1,%2,%3},{%4,%5},{%6},{%0,%1,%2,%3};"
      : "+f"(c[0]), "+f"(c[1]), "+f"(c[2]), "+f"(c[3]) : "r"(a0), "r"(a1), "r"(b0));
}
DEVI void mma16v(float (&c)[4], uint32_t a0, uint32_t a1, uint32_t a2, uint32_t a3, uint32_t b0, uint32_t b1) {
  asm volatile("mma.sync.aligned.m16n8k16.row.col.f32.bf16.bf16.f32 {%0,%1,%2,%3},{%4,%5,%6,%7},{%8,%9},{%0,%1,%2,%3};"
      : "+f"(c[0]), "+f"(c[1]), "+f"(c[2]), "+f"(c[3]) : "r"(a0), "r"(a1), "r"(a2), "r"(a3), "r"(b0), "r"(b1));
}
DEVI void mma8v(float (&c)[4], uint32_t a0, uint32_t a1, uint32_t b0) {
  asm volatile("mma.sync.aligned.m16n8k8.row.col.f32.bf16.bf16.f32 {%0,%1,%2,%3},{%4,%5},{%6},{%0,%1,%2,%3};"
      : "+f"(c[0]), "+f"(c[1]), "+f"(c[2]), "+f"(c[3]) : "r"(a0), "r"(a1), "r"(b0));
}
DEVI float2 mma_rows8(const uint32_t (&a0)[4], const uint32_t (&a1)[4], const uint32_t (&b0)[4], const uint32_t (&b1)[4]) {
  float e0[4] = {0.f, 0.f, 0.f, 0.f}, e1[4] = {0.f, 0.f, 0.f, 0.f}, e2[4] = {0.f, 0.f, 0.f, 0.f}, e3[4] = {0.f, 0.f, 0.f, 0.f};
  mma16v(e0, a0[0], a0[1], a0[2], a0[3], b0[0], b0[1]);
  mma16v(e1, a0[0], a0[1], a0[2], a0[3], b0[2], b0[3]);
  mma16v(e2, a1[0], a1[1], a1[2], a1[3], b1[0], b1[1]);
  mma16v(e3, a1[0], a1[1], a1[2], a1[3], b1[2], b1[3]);
  return make_float2((e0[0] + e1[2]) + (e2[0] + e3[2]), (e0[1] + e1[3]) + (e2[1] + e3[3]));
}
DEVI void wg_fence() { asm volatile("wgmma.fence.sync.aligned;" ::: "memory"); }
DEVI void wg_commit() { asm volatile("wgmma.commit_group.sync.aligned;" ::: "memory"); }
template <int N> DEVI void wg_wait() { asm volatile("wgmma.wait_group.sync.aligned %0;" :: "n"(N) : "memory"); }
template <int N> DEVI void reg_fence(float (&d)[N]) {
#pragma unroll
  for (int i = 0; i < N; i++) asm volatile("" : "+f"(d[i]) :: "memory");
}
DEVI uint64_t desc128(uint32_t addr, uint32_t lbo16) {
  return (uint64_t)((addr >> 4) & 0x3fff) | ((uint64_t)lbo16 << 16) | (64ull << 32) | (1ull << 62);
}
DEVI void tma2d(uint32_t dst, const CUtensorMap* tm, int c0, int c1, uint32_t bar) {
  asm volatile("cp.async.bulk.tensor.2d.shared::cluster.global.mbarrier::complete_tx::bytes [%0], [%1, {%2, %3}], [%4];"
               :: "r"(dst), "l"(tm), "r"(c0), "r"(c1), "r"(bar) : "memory");
}
DEVI void tma2d_mc(uint32_t dst, const CUtensorMap* tm, int c0, int c1, uint32_t bar) {
  asm volatile("cp.async.bulk.tensor.2d.shared::cluster.global.mbarrier::complete_tx::bytes.multicast::cluster [%0], [%1, {%2, %3}], [%4], %5;"
               :: "r"(dst), "l"(tm), "r"(c0), "r"(c1), "r"(bar), "h"((uint16_t)0xffff) : "memory");
}
DEVI void bulk_ld(uint32_t dst, const void* src, uint32_t bytes, uint32_t bar) {
  asm volatile("cp.async.bulk.shared::cluster.global.mbarrier::complete_tx::bytes [%0], [%1], %2, [%3];"
               :: "r"(dst), "l"(src), "r"(bytes), "r"(bar) : "memory");
}
DEVI void bulk_mc(uint32_t dst, const void* src, uint32_t bytes, uint32_t bar) {
  asm volatile("cp.async.bulk.shared::cluster.global.mbarrier::complete_tx::bytes.multicast::cluster [%0], [%1], %2, [%3], %4;"
               :: "r"(dst), "l"(src), "r"(bytes), "r"(bar), "h"((uint16_t)0xffff) : "memory");
}
DEVI void st_async4(uint32_t a, float x, float y, float z, float w, uint32_t bar) {
  asm volatile("st.async.weak.shared::cluster.mbarrier::complete_tx::bytes.v4.f32 [%0], {%1,%2,%3,%4}, [%5];"
               :: "r"(a), "f"(x), "f"(y), "f"(z), "f"(w), "r"(bar) : "memory");
}
DEVI void st_async4u(uint32_t a, uint32_t x, uint32_t y, uint32_t z, uint32_t w, uint32_t bar) {
  asm volatile("st.async.weak.shared::cluster.mbarrier::complete_tx::bytes.v4.b32 [%0], {%1,%2,%3,%4}, [%5];"
               :: "r"(a), "r"(x), "r"(y), "r"(z), "r"(w), "r"(bar) : "memory");
}
DEVI uint32_t ldg1r(const void* p) { uint32_t v; asm volatile("ld.relaxed.gpu.global.u32 %0, [%1];" : "=r"(v) : "l"(p) : "memory"); return v; }
DEVI uint32_t near_copy(uint8_t* blk) {
  uint32_t best[2] = {~0u, ~0u}, v = 0;
#pragma unroll 1
  for (int i = 0; i < 6; i++) {
    const uint8_t* p = blk + XC_R0 + 7936 + (i & 1) * XC_TWIN + (v & 4);
    const uint32_t t0 = clk();
    asm volatile("atom.relaxed.gpu.global.and.b32 %0, [%1], 0;" : "=r"(v) : "l"(p) : "memory");
    uint32_t t1;
    asm volatile("{\n.reg .pred p;\nPROBE_WAIT:\nsetp.eq.u32 p, %1, 0x5a5a5a5a;\n@p nanosleep.u32 32;\nmov.u32 %0, %%clock;\n}" : "=r"(t1) : "r"(v) : "memory");
    const uint32_t d = t1 - t0;
    if (i & 1) best[1] = min(best[1], d); else best[0] = min(best[0], d);
  }
  return best[1] < best[0] ? XC_TWIN : 0;
}
DEVI void tma2d_prefetch(const CUtensorMap* tm, int c0, int c1) {
  asm volatile("cp.async.bulk.prefetch.tensor.2d.L2.global [%0, {%1, %2}];" :: "l"(tm), "r"(c0), "r"(c1) : "memory");
}
DEVI void ldg2r(uint32_t& x, uint32_t& y, const void* p) { asm volatile("ld.relaxed.gpu.global.v2.u32 {%0,%1}, [%2];" : "=r"(x), "=r"(y) : "l"(p) : "memory"); }
DEVI void stg2r(void* p, uint32_t x, uint32_t y) { asm volatile("st.relaxed.gpu.global.v2.u32 [%0], {%1,%2};" :: "l"(p), "r"(x), "r"(y) : "memory"); }
DEVI float2 lds_f2(uint32_t a) { float2 v; asm volatile("ld.shared.v2.f32 {%0,%1}, [%2];" : "=f"(v.x), "=f"(v.y) : "r"(a) : "memory"); return v; }
DEVI float4 lds_f4(uint32_t a) { float4 v; asm volatile("ld.shared.v4.f32 {%0,%1,%2,%3}, [%4];" : "=f"(v.x), "=f"(v.y), "=f"(v.z), "=f"(v.w) : "r"(a) : "memory"); return v; }
DEVI uint2 lds_u2(uint32_t a) { uint2 v; asm volatile("ld.shared.v2.u32 {%0,%1}, [%2];" : "=r"(v.x), "=r"(v.y) : "r"(a) : "memory"); return v; }
DEVI uint4 lds_u4(uint32_t a) { uint4 v; asm volatile("ld.shared.v4.u32 {%0,%1,%2,%3}, [%4];" : "=r"(v.x), "=r"(v.y), "=r"(v.z), "=r"(v.w) : "r"(a) : "memory"); return v; }
DEVI void sts_f2(uint32_t a, float x, float y) { asm volatile("st.shared.v2.f32 [%0], {%1,%2};" :: "r"(a), "f"(x), "f"(y) : "memory"); }
DEVI void sts_f4(uint32_t a, float x, float y, float z, float w) { asm volatile("st.shared.v4.f32 [%0], {%1,%2,%3,%4};" :: "r"(a), "f"(x), "f"(y), "f"(z), "f"(w) : "memory"); }
DEVI void sts_u2(uint32_t a, uint32_t x, uint32_t y) { asm volatile("st.shared.v2.u32 [%0], {%1,%2};" :: "r"(a), "r"(x), "r"(y) : "memory"); }
DEVI void sts_u4(uint32_t a, uint32_t x, uint32_t y, uint32_t z, uint32_t w) { asm volatile("st.shared.v4.u32 [%0], {%1,%2,%3,%4};" :: "r"(a), "r"(x), "r"(y), "r"(z), "r"(w) : "memory"); }
DEVI uint32_t tagf(float v, uint32_t tag) { return (__float_as_uint(v) & ~3u) | tag; }
DEVI float qmax(float v) { v = fmaxf(v, __shfl_xor_sync(0xffffffffu, v, 1)); return fmaxf(v, __shfl_xor_sync(0xffffffffu, v, 2)); }
DEVI float qsum(float v) { v += __shfl_xor_sync(0xffffffffu, v, 1); return v + __shfl_xor_sync(0xffffffffu, v, 2); }

__device__ __forceinline__ void wgmma_n224_kk(float (&d)[112], uint64_t da, uint64_t db, int sc) {
  asm volatile("{\n.reg .pred p;\nsetp.ne.b32 p, %114, 0;\n"
    "wgmma.mma_async.sync.aligned.m64n224k16.f32.bf16.bf16 {%0,%1,%2,%3,%4,%5,%6,%7,%8,%9,%10,%11,%12,%13,%14,%15,%16,%17,%18,%19,%20,%21,%22,%23,%24,%25,%26,%27,%28,%29,%30,%31,%32,%33,%34,%35,%36,%37,%38,%39,%40,%41,%42,%43,%44,%45,%46,%47,%48,%49,%50,%51,%52,%53,%54,%55,%56,%57,%58,%59,%60,%61,%62,%63,%64,%65,%66,%67,%68,%69,%70,%71,%72,%73,%74,%75,%76,%77,%78,%79,%80,%81,%82,%83,%84,%85,%86,%87,%88,%89,%90,%91,%92,%93,%94,%95,%96,%97,%98,%99,%100,%101,%102,%103,%104,%105,%106,%107,%108,%109,%110,%111}, %112, %113, p, 1, 1, 0, 0;\n}"
    : "+f"(d[0]),"+f"(d[1]),"+f"(d[2]),"+f"(d[3]),"+f"(d[4]),"+f"(d[5]),"+f"(d[6]),"+f"(d[7]),"+f"(d[8]),"+f"(d[9]),"+f"(d[10]),"+f"(d[11]),"+f"(d[12]),"+f"(d[13]),"+f"(d[14]),"+f"(d[15]),"+f"(d[16]),"+f"(d[17]),"+f"(d[18]),"+f"(d[19]),"+f"(d[20]),"+f"(d[21]),"+f"(d[22]),"+f"(d[23]),"+f"(d[24]),"+f"(d[25]),"+f"(d[26]),"+f"(d[27]),"+f"(d[28]),"+f"(d[29]),"+f"(d[30]),"+f"(d[31]),"+f"(d[32]),"+f"(d[33]),"+f"(d[34]),"+f"(d[35]),"+f"(d[36]),"+f"(d[37]),"+f"(d[38]),"+f"(d[39]),"+f"(d[40]),"+f"(d[41]),"+f"(d[42]),"+f"(d[43]),"+f"(d[44]),"+f"(d[45]),"+f"(d[46]),"+f"(d[47]),"+f"(d[48]),"+f"(d[49]),"+f"(d[50]),"+f"(d[51]),"+f"(d[52]),"+f"(d[53]),"+f"(d[54]),"+f"(d[55]),"+f"(d[56]),"+f"(d[57]),"+f"(d[58]),"+f"(d[59]),"+f"(d[60]),"+f"(d[61]),"+f"(d[62]),"+f"(d[63]),"+f"(d[64]),"+f"(d[65]),"+f"(d[66]),"+f"(d[67]),"+f"(d[68]),"+f"(d[69]),"+f"(d[70]),"+f"(d[71]),"+f"(d[72]),"+f"(d[73]),"+f"(d[74]),"+f"(d[75]),"+f"(d[76]),"+f"(d[77]),"+f"(d[78]),"+f"(d[79]),"+f"(d[80]),"+f"(d[81]),"+f"(d[82]),"+f"(d[83]),"+f"(d[84]),"+f"(d[85]),"+f"(d[86]),"+f"(d[87]),"+f"(d[88]),"+f"(d[89]),"+f"(d[90]),"+f"(d[91]),"+f"(d[92]),"+f"(d[93]),"+f"(d[94]),"+f"(d[95]),"+f"(d[96]),"+f"(d[97]),"+f"(d[98]),"+f"(d[99]),"+f"(d[100]),"+f"(d[101]),"+f"(d[102]),"+f"(d[103]),"+f"(d[104]),"+f"(d[105]),"+f"(d[106]),"+f"(d[107]),"+f"(d[108]),"+f"(d[109]),"+f"(d[110]),"+f"(d[111])
    : "l"(da),"l"(db),"r"(sc));
}
__device__ __forceinline__ void wgmma_n224_mk(float (&d)[112], uint64_t da, uint64_t db, int sc) {
  asm volatile("{\n.reg .pred p;\nsetp.ne.b32 p, %114, 0;\n"
    "wgmma.mma_async.sync.aligned.m64n224k16.f32.bf16.bf16 {%0,%1,%2,%3,%4,%5,%6,%7,%8,%9,%10,%11,%12,%13,%14,%15,%16,%17,%18,%19,%20,%21,%22,%23,%24,%25,%26,%27,%28,%29,%30,%31,%32,%33,%34,%35,%36,%37,%38,%39,%40,%41,%42,%43,%44,%45,%46,%47,%48,%49,%50,%51,%52,%53,%54,%55,%56,%57,%58,%59,%60,%61,%62,%63,%64,%65,%66,%67,%68,%69,%70,%71,%72,%73,%74,%75,%76,%77,%78,%79,%80,%81,%82,%83,%84,%85,%86,%87,%88,%89,%90,%91,%92,%93,%94,%95,%96,%97,%98,%99,%100,%101,%102,%103,%104,%105,%106,%107,%108,%109,%110,%111}, %112, %113, p, 1, 1, 1, 0;\n}"
    : "+f"(d[0]),"+f"(d[1]),"+f"(d[2]),"+f"(d[3]),"+f"(d[4]),"+f"(d[5]),"+f"(d[6]),"+f"(d[7]),"+f"(d[8]),"+f"(d[9]),"+f"(d[10]),"+f"(d[11]),"+f"(d[12]),"+f"(d[13]),"+f"(d[14]),"+f"(d[15]),"+f"(d[16]),"+f"(d[17]),"+f"(d[18]),"+f"(d[19]),"+f"(d[20]),"+f"(d[21]),"+f"(d[22]),"+f"(d[23]),"+f"(d[24]),"+f"(d[25]),"+f"(d[26]),"+f"(d[27]),"+f"(d[28]),"+f"(d[29]),"+f"(d[30]),"+f"(d[31]),"+f"(d[32]),"+f"(d[33]),"+f"(d[34]),"+f"(d[35]),"+f"(d[36]),"+f"(d[37]),"+f"(d[38]),"+f"(d[39]),"+f"(d[40]),"+f"(d[41]),"+f"(d[42]),"+f"(d[43]),"+f"(d[44]),"+f"(d[45]),"+f"(d[46]),"+f"(d[47]),"+f"(d[48]),"+f"(d[49]),"+f"(d[50]),"+f"(d[51]),"+f"(d[52]),"+f"(d[53]),"+f"(d[54]),"+f"(d[55]),"+f"(d[56]),"+f"(d[57]),"+f"(d[58]),"+f"(d[59]),"+f"(d[60]),"+f"(d[61]),"+f"(d[62]),"+f"(d[63]),"+f"(d[64]),"+f"(d[65]),"+f"(d[66]),"+f"(d[67]),"+f"(d[68]),"+f"(d[69]),"+f"(d[70]),"+f"(d[71]),"+f"(d[72]),"+f"(d[73]),"+f"(d[74]),"+f"(d[75]),"+f"(d[76]),"+f"(d[77]),"+f"(d[78]),"+f"(d[79]),"+f"(d[80]),"+f"(d[81]),"+f"(d[82]),"+f"(d[83]),"+f"(d[84]),"+f"(d[85]),"+f"(d[86]),"+f"(d[87]),"+f"(d[88]),"+f"(d[89]),"+f"(d[90]),"+f"(d[91]),"+f"(d[92]),"+f"(d[93]),"+f"(d[94]),"+f"(d[95]),"+f"(d[96]),"+f"(d[97]),"+f"(d[98]),"+f"(d[99]),"+f"(d[100]),"+f"(d[101]),"+f"(d[102]),"+f"(d[103]),"+f"(d[104]),"+f"(d[105]),"+f"(d[106]),"+f"(d[107]),"+f"(d[108]),"+f"(d[109]),"+f"(d[110]),"+f"(d[111])
    : "l"(da),"l"(db),"r"(sc));
}
__device__ __forceinline__ void wgmma_n32_rs(float (&d)[16], const uint32_t (&a)[4], uint64_t db, int sc) {
  asm volatile("{\n.reg .pred p;\nsetp.ne.b32 p, %21, 0;\n"
    "wgmma.mma_async.sync.aligned.m64n32k16.f32.bf16.bf16 {%0,%1,%2,%3,%4,%5,%6,%7,%8,%9,%10,%11,%12,%13,%14,%15}, {%16,%17,%18,%19}, %20, p, 1, 1, 0;\n}"
    : "+f"(d[0]),"+f"(d[1]),"+f"(d[2]),"+f"(d[3]),"+f"(d[4]),"+f"(d[5]),"+f"(d[6]),"+f"(d[7]),"+f"(d[8]),"+f"(d[9]),"+f"(d[10]),"+f"(d[11]),"+f"(d[12]),"+f"(d[13]),"+f"(d[14]),"+f"(d[15])
    : "r"(a[0]),"r"(a[1]),"r"(a[2]),"r"(a[3]),"l"(db),"r"(sc));
}
__device__ __forceinline__ void wgmma_n8_rs(float (&d)[4], const uint32_t (&a)[4], uint64_t db, int sc) {
  asm volatile("{\n.reg .pred p;\nsetp.ne.b32 p, %9, 0;\n"
    "wgmma.mma_async.sync.aligned.m64n8k16.f32.bf16.bf16 {%0,%1,%2,%3}, {%4,%5,%6,%7}, %8, p, 1, 1, 0;\n}"
    : "+f"(d[0]),"+f"(d[1]),"+f"(d[2]),"+f"(d[3])
    : "r"(a[0]),"r"(a[1]),"r"(a[2]),"r"(a[3]),"l"(db),"r"(sc));
}
__device__ __forceinline__ void wgmma_n256_kn(float (&d)[128], uint64_t da, uint64_t db, int sc) {
  asm volatile("{\n.reg .pred p;\nsetp.ne.b32 p, %130, 0;\n"
    "wgmma.mma_async.sync.aligned.m64n256k16.f32.bf16.bf16 {%0,%1,%2,%3,%4,%5,%6,%7,%8,%9,%10,%11,%12,%13,%14,%15,%16,%17,%18,%19,%20,%21,%22,%23,%24,%25,%26,%27,%28,%29,%30,%31,%32,%33,%34,%35,%36,%37,%38,%39,%40,%41,%42,%43,%44,%45,%46,%47,%48,%49,%50,%51,%52,%53,%54,%55,%56,%57,%58,%59,%60,%61,%62,%63,%64,%65,%66,%67,%68,%69,%70,%71,%72,%73,%74,%75,%76,%77,%78,%79,%80,%81,%82,%83,%84,%85,%86,%87,%88,%89,%90,%91,%92,%93,%94,%95,%96,%97,%98,%99,%100,%101,%102,%103,%104,%105,%106,%107,%108,%109,%110,%111,%112,%113,%114,%115,%116,%117,%118,%119,%120,%121,%122,%123,%124,%125,%126,%127}, %128, %129, p, 1, 1, 0, 1;\n}"
    : "+f"(d[0]),"+f"(d[1]),"+f"(d[2]),"+f"(d[3]),"+f"(d[4]),"+f"(d[5]),"+f"(d[6]),"+f"(d[7]),"+f"(d[8]),"+f"(d[9]),"+f"(d[10]),"+f"(d[11]),"+f"(d[12]),"+f"(d[13]),"+f"(d[14]),"+f"(d[15]),"+f"(d[16]),"+f"(d[17]),"+f"(d[18]),"+f"(d[19]),"+f"(d[20]),"+f"(d[21]),"+f"(d[22]),"+f"(d[23]),"+f"(d[24]),"+f"(d[25]),"+f"(d[26]),"+f"(d[27]),"+f"(d[28]),"+f"(d[29]),"+f"(d[30]),"+f"(d[31]),"+f"(d[32]),"+f"(d[33]),"+f"(d[34]),"+f"(d[35]),"+f"(d[36]),"+f"(d[37]),"+f"(d[38]),"+f"(d[39]),"+f"(d[40]),"+f"(d[41]),"+f"(d[42]),"+f"(d[43]),"+f"(d[44]),"+f"(d[45]),"+f"(d[46]),"+f"(d[47]),"+f"(d[48]),"+f"(d[49]),"+f"(d[50]),"+f"(d[51]),"+f"(d[52]),"+f"(d[53]),"+f"(d[54]),"+f"(d[55]),"+f"(d[56]),"+f"(d[57]),"+f"(d[58]),"+f"(d[59]),"+f"(d[60]),"+f"(d[61]),"+f"(d[62]),"+f"(d[63]),"+f"(d[64]),"+f"(d[65]),"+f"(d[66]),"+f"(d[67]),"+f"(d[68]),"+f"(d[69]),"+f"(d[70]),"+f"(d[71]),"+f"(d[72]),"+f"(d[73]),"+f"(d[74]),"+f"(d[75]),"+f"(d[76]),"+f"(d[77]),"+f"(d[78]),"+f"(d[79]),"+f"(d[80]),"+f"(d[81]),"+f"(d[82]),"+f"(d[83]),"+f"(d[84]),"+f"(d[85]),"+f"(d[86]),"+f"(d[87]),"+f"(d[88]),"+f"(d[89]),"+f"(d[90]),"+f"(d[91]),"+f"(d[92]),"+f"(d[93]),"+f"(d[94]),"+f"(d[95]),"+f"(d[96]),"+f"(d[97]),"+f"(d[98]),"+f"(d[99]),"+f"(d[100]),"+f"(d[101]),"+f"(d[102]),"+f"(d[103]),"+f"(d[104]),"+f"(d[105]),"+f"(d[106]),"+f"(d[107]),"+f"(d[108]),"+f"(d[109]),"+f"(d[110]),"+f"(d[111]),"+f"(d[112]),"+f"(d[113]),"+f"(d[114]),"+f"(d[115]),"+f"(d[116]),"+f"(d[117]),"+f"(d[118]),"+f"(d[119]),"+f"(d[120]),"+f"(d[121]),"+f"(d[122]),"+f"(d[123]),"+f"(d[124]),"+f"(d[125]),"+f"(d[126]),"+f"(d[127])
    : "l"(da),"l"(db),"r"(sc));
}
__device__ __forceinline__ void wgmma_n192_kn(float (&d)[96], uint64_t da, uint64_t db, int sc) {
  asm volatile("{\n.reg .pred p;\nsetp.ne.b32 p, %98, 0;\n"
    "wgmma.mma_async.sync.aligned.m64n192k16.f32.bf16.bf16 {%0,%1,%2,%3,%4,%5,%6,%7,%8,%9,%10,%11,%12,%13,%14,%15,%16,%17,%18,%19,%20,%21,%22,%23,%24,%25,%26,%27,%28,%29,%30,%31,%32,%33,%34,%35,%36,%37,%38,%39,%40,%41,%42,%43,%44,%45,%46,%47,%48,%49,%50,%51,%52,%53,%54,%55,%56,%57,%58,%59,%60,%61,%62,%63,%64,%65,%66,%67,%68,%69,%70,%71,%72,%73,%74,%75,%76,%77,%78,%79,%80,%81,%82,%83,%84,%85,%86,%87,%88,%89,%90,%91,%92,%93,%94,%95}, %96, %97, p, 1, 1, 0, 1;\n}"
    : "+f"(d[0]),"+f"(d[1]),"+f"(d[2]),"+f"(d[3]),"+f"(d[4]),"+f"(d[5]),"+f"(d[6]),"+f"(d[7]),"+f"(d[8]),"+f"(d[9]),"+f"(d[10]),"+f"(d[11]),"+f"(d[12]),"+f"(d[13]),"+f"(d[14]),"+f"(d[15]),"+f"(d[16]),"+f"(d[17]),"+f"(d[18]),"+f"(d[19]),"+f"(d[20]),"+f"(d[21]),"+f"(d[22]),"+f"(d[23]),"+f"(d[24]),"+f"(d[25]),"+f"(d[26]),"+f"(d[27]),"+f"(d[28]),"+f"(d[29]),"+f"(d[30]),"+f"(d[31]),"+f"(d[32]),"+f"(d[33]),"+f"(d[34]),"+f"(d[35]),"+f"(d[36]),"+f"(d[37]),"+f"(d[38]),"+f"(d[39]),"+f"(d[40]),"+f"(d[41]),"+f"(d[42]),"+f"(d[43]),"+f"(d[44]),"+f"(d[45]),"+f"(d[46]),"+f"(d[47]),"+f"(d[48]),"+f"(d[49]),"+f"(d[50]),"+f"(d[51]),"+f"(d[52]),"+f"(d[53]),"+f"(d[54]),"+f"(d[55]),"+f"(d[56]),"+f"(d[57]),"+f"(d[58]),"+f"(d[59]),"+f"(d[60]),"+f"(d[61]),"+f"(d[62]),"+f"(d[63]),"+f"(d[64]),"+f"(d[65]),"+f"(d[66]),"+f"(d[67]),"+f"(d[68]),"+f"(d[69]),"+f"(d[70]),"+f"(d[71]),"+f"(d[72]),"+f"(d[73]),"+f"(d[74]),"+f"(d[75]),"+f"(d[76]),"+f"(d[77]),"+f"(d[78]),"+f"(d[79]),"+f"(d[80]),"+f"(d[81]),"+f"(d[82]),"+f"(d[83]),"+f"(d[84]),"+f"(d[85]),"+f"(d[86]),"+f"(d[87]),"+f"(d[88]),"+f"(d[89]),"+f"(d[90]),"+f"(d[91]),"+f"(d[92]),"+f"(d[93]),"+f"(d[94]),"+f"(d[95])
    : "l"(da),"l"(db),"r"(sc));
}

constexpr uint32_t XB = 28672;
constexpr uint32_t O_WQ = 5 * XB;
constexpr uint32_t O_WO = O_WQ + 32768;
constexpr uint32_t O_MIMG = O_WO + 32768;
constexpr uint32_t O_BAR = O_MIMG + 2 * 7168;
constexpr uint32_t O_TS = O_BAR + 384;
constexpr uint32_t T_SMEM = O_TS + 4096 + 128 + 1024;
constexpr uint32_t O_Z = 4 * XB;
constexpr uint32_t O_RS = O_Z + 2 * 5120;
constexpr uint32_t O_ORS = O_RS + 2 * 2048;
constexpr uint32_t O_P = O_ORS + 4 * 4096;
constexpr uint32_t O_SX = O_P + 2 * 2560;
constexpr uint32_t O_MJ = O_SX + 1536;
constexpr uint32_t O_ST = O_MJ + 2048;
constexpr uint32_t O_PC = O_ST + 2 * 5632;
constexpr uint32_t O_YB = O_PC + 128;
constexpr uint32_t O_GX = O_YB + 2 * 5120;
constexpr uint32_t O_GY = O_GX + 2 * 1792;
enum { B_X = 0, B_M = 4, B_RS = 6, B_O = 8, B_ZX = 10, B_P = 12, B_PF = 14, B_PE = 18, B_WQ = 22, B_WO = 23, B_T = 24, B_MJ = 26, B_OL = 28, B_G = 30, B_M2 = 31, B_YM = 33, B_GY = 34, B_N = 35 };
constexpr uint32_t O_NEAR = O_BAR + 8 * B_N, O_DONE = O_NEAR + 8, O_C3 = O_DONE + 8, O_REDO = O_C3 + 4;
enum { N_ZM = 1, N_MOK = 2, N_W1 = 3, N_INIT = 4, N_ZX = 5, N_REDO = 6, N_YX = 7, N_SS = 8, N_ST = 9 };

DEVI void gemm_m(const uint32_t (&w)[28][4], uint32_t img_lane, float (&c)[4]) {
  float acc[4][4];
#pragma unroll
  for (int i = 0; i < 4; i++) { acc[i][0] = acc[i][1] = acc[i][2] = acc[i][3] = 0.f; }
  uint32_t r[14][4];
#pragma unroll
  for (int u = 0; u < 14; u++) ldsm4(r[u], img_lane + u * 512);
#pragma unroll
  for (int u = 0; u < 14; u++) {
    mma16v(acc[(2 * u) & 3], w[2 * u][0], w[2 * u][1], w[2 * u][2], w[2 * u][3], r[u][0], r[u][1]);
    mma16v(acc[(2 * u + 1) & 3], w[2 * u + 1][0], w[2 * u + 1][1], w[2 * u + 1][2], w[2 * u + 1][3], r[u][2], r[u][3]);
  }
#pragma unroll
  for (int i = 0; i < 4; i++) c[i] = (acc[0][i] + acc[1][i]) + (acc[2][i] + acc[3][i]);
}

DEVI void gemm_x_issue(const uint32_t (&w)[28][4], uint32_t xbuf, float (&d)[16]) {
  const uint64_t b0 = desc128(xbuf, 1);
  wg_fence();
#pragma unroll
  for (int k = 0; k < 28; k++) wgmma_n32_rs(d, w[k], b0 + (uint64_t)((k >> 2) * 256 + (k & 3) * 2), k != 0);
  wg_commit();
}
DEVI void gemm_x(const uint32_t (&w)[28][4], uint32_t xbuf, float (&d)[16]) {
  gemm_x_issue(w, xbuf, d);
  wg_wait<0>();
  reg_fence(d);
}

template <int WHICH>
DEVI void build_weights(uint32_t (&w)[28][4], uint32_t sb, int& dead, int lane) {
  const uint32_t bar = sb + O_BAR;
  mbar_wait(bar + 8 * (WHICH ? B_WO : B_WQ), 0, dead);
  if ((threadIdx.x & 127) == 0) PTS(4 + WHICH);
#pragma unroll
  for (int half = 0; half < 2; half++) {
    float d[112];
#pragma unroll 1
    for (int fk = 0; fk < 4; fk++) {
      const int c = 2 * (4 * half + fk) + WHICH, st = c & 3;
      mbar_wait(bar + 8 * (B_PF + st), (c >> 2) & 1, dead);
      if ((threadIdx.x & 127) == 0) PTS(8 + c);
      const uint64_t db = desc128(sb + (st + 1) * XB, 1);
      wg_fence();
#pragma unroll
      for (int kk = 0; kk < 4; kk++) {
        if (WHICH == 0) wgmma_n224_kk(d, desc128(sb + O_WQ + fk * 8192 + kk * 32, 1), db + kk * 2, (fk | kk) != 0);
        else            wgmma_n224_mk(d, desc128(sb + O_WO + (fk * 4 + kk) * 2048, 1), db + kk * 2, (fk | kk) != 0);
      }
      wg_commit();
      wg_wait<0>();
      if (lane == 0) mbar_arrive(bar + 8 * (B_PE + st));
    }
    reg_fence(d);
#pragma unroll
    for (int kk = 0; kk < 14; kk++) {
      w[14 * half + kk][0] = pack2(d[8 * kk + 0], d[8 * kk + 1]);
      w[14 * half + kk][1] = pack2(d[8 * kk + 2], d[8 * kk + 3]);
      w[14 * half + kk][2] = pack2(d[8 * kk + 4], d[8 * kk + 5]);
      w[14 * half + kk][3] = pack2(d[8 * kk + 6], d[8 * kk + 7]);
    }
  }
}

DEVI bool stale7(const uint32_t (&v)[14], uint32_t tag) {
  const uint32_t o = ((v[0] | v[1] | v[2]) | (v[3] | v[4] | v[5]) | (v[6] | v[7] | v[8])) | ((v[9] | v[10] | v[11]) | (v[12] | v[13]));
  const uint32_t a = ((v[0] & v[1] & v[2]) & (v[3] & v[4] & v[5]) & (v[6] & v[7] & v[8])) & ((v[9] & v[10] & v[11]) & (v[12] & v[13]));
  return (((o ^ tag) | (a ^ tag)) & 3u) != 0;
}
DEVI float2 add7(const uint32_t (&v)[14]) {
  float2 r;
  r.x = ((__uint_as_float(v[0]) + __uint_as_float(v[2])) + (__uint_as_float(v[4]) + __uint_as_float(v[6]))) +
        ((__uint_as_float(v[8]) + __uint_as_float(v[10])) + __uint_as_float(v[12]));
  r.y = ((__uint_as_float(v[1]) + __uint_as_float(v[3])) + (__uint_as_float(v[5]) + __uint_as_float(v[7]))) +
        ((__uint_as_float(v[9]) + __uint_as_float(v[11])) + __uint_as_float(v[13]));
  return r;
}

__global__ void __launch_bounds__(384, 1)
rmt_kernel(const __grid_constant__ CUtensorMap tmWq, const __grid_constant__ CUtensorMap tmWk,
           const __grid_constant__ CUtensorMap tmWv, const __grid_constant__ CUtensorMap tmWo,
           const __grid_constant__ CUtensorMap tmX, const __nv_bfloat16* __restrict__ x,
           const __nv_bfloat16* __restrict__ mem0, const __nv_bfloat16* __restrict__ gate_w, __nv_bfloat16* __restrict__ out) {
  extern __shared__ uint8_t smem_raw[];
  const uint32_t sb = (smem_u32(smem_raw) + 1023) & ~1023u;
  const uint32_t bar = sb + O_BAR;
  int lim = SPIN_LIMIT;
  int tid;
  uint32_t h, j;
  asm volatile("mov.u32 %0, %%tid.x;" : "=r"(tid));
  asm volatile("mov.u32 %0, %%cluster_ctarank;" : "=r"(h));
  asm volatile("mov.u32 %0, %%clusterid.x;" : "=r"(j));
  tid = __shfl_sync(0xffffffffu, tid, tid & 31);
  const int lane = tid & 31, warp = __shfl_sync(0xffffffffu, tid >> 5, 0);
  if (warp == 0) PTS(0);

  if (warp == 8) {
    if (elect()) {
#pragma unroll
      for (int i = 0; i < 4; i++) mbar_init(bar + 8 * (B_PF + i), 1);
      mbar_init(bar + 8 * B_WQ, 1);
      mbar_init(bar + 8 * B_WO, 1);
      asm volatile("fence.mbarrier_init.release.cluster;" ::: "memory");
      PTS(1);
      mbar_expect(bar + 8 * B_PF, XB);
      tma2d(sb + XB, &tmWk, h * DH, 0, bar + 8 * B_PF);
      mbar_expect(bar + 8 * B_WQ, 32768);
#pragma unroll
      for (int k = 0; k < 4; k++) tma2d(sb + O_WQ + k * 8192, &tmWq, h * DH + k * 64, j * 64, bar + 8 * B_WQ);
      mbar_expect(bar + 8 * B_WO, 32768);
      tma2d(sb + O_WO, &tmWo, j * 64, h * DH, bar + 8 * B_WO);
#pragma unroll
      for (int c = 1; c < 4; c++) {
        mbar_expect(bar + 8 * (B_PF + c), XB);
        tma2d(sb + (c + 1) * XB, (c & 1) ? &tmWv : &tmWk, h * DH + (c >> 1) * 64, 0, bar + 8 * (B_PF + c));
      }
    }
  } else if (warp == 9) {
    if (elect()) {
#pragma unroll
      for (int i = 0; i < B_N; i++)
        if (i < B_PF || (i >= B_PE && i < B_WQ) || i >= B_T) mbar_init(bar + 8 * i, i == B_M2 + 1 ? 16 : i >= B_MJ ? 1 : i >= B_T ? 3 : i >= B_PE ? 4 : i >= B_P ? 2 : i >= B_ZX ? 4 : 1);
      sts32v(sb + O_DONE, 0);
      sts32v(sb + O_C3, 0);
      sts32v(sb + O_REDO + 4, 0);
      sts32v(sb + O_DONE + 4, 0);
      mbar_expect(bar + 8 * B_X, XB);
      mbar_expect(bar + 8 * B_OL, 4096);
      mbar_expect(bar + 8 * (B_OL + 1), 4096);
#pragma unroll
      for (int i = 0; i < 2; i++) { mbar_expect(bar + 8 * (B_RS + i), 2048); mbar_expect(bar + 8 * (B_O + i), 4096); }
      asm volatile("fence.mbarrier_init.release.cluster;" ::: "memory");
    }
  }
  asm volatile("griddepcontrol.launch_dependents;");
  if (warp == 8) PTS(2);
  __syncthreads();
  cluster_arrive_relaxed();
  if (warp == 0) PTS(3);

  if (warp < 4) {
    asm volatile("setmaxnreg.inc.sync.aligned.u32 216;");
    uint32_t w[28][4];
    build_weights<0>(w, sb, lim, lane);
    if (warp == 0) PTS(6);
    cluster_wait();
    cluster_arrive_relaxed();
    uint32_t zst = sb + O_Z + ((2 * warp + ((lane >> 3) & 1)) * 40 + 8 * (lane >> 4) + (lane & 7)) * 16;
    const int mt = warp & 1, n0 = (warp >> 1) * 3;
    const int ch = lane >> 3, chp = (ch >> 1) | ((ch & 1) << 1);
    uint32_t zld = sb + O_Z + ((warp == 2 ? chp : ch) * 40 + (lane & 7)) * 16 + (warp == 2 ? 0 : n0 * 128);
    uint32_t zx = sb + O_Z + (chp * 40 + 8 + 8 * warp + (lane & 7)) * 16;
    float* p_smx = &g_xacc[0][h][warp * 128 + lane * 4];
    const int xrow = 16 * mt + (lane & 15);
    uint32_t xq = sb + j * 4096 + xrow * 128 + (((lane >> 4) ^ (xrow & 7)) << 4);
    uint32_t mimg = sb + O_MIMG + lane * 16, sta = sb + O_ST + (warp == 3 ? 4096 : mt * 2048) + lane * 16;
    uint8_t* p_smm = xch(h) + (XC_R0 + 2 * XC_REG + j * 256 + lane * 8);
    zst = keep(zst, lane); zld = keep(zld, lane); xq = keep(xq, lane); mimg = keep(mimg, lane); sta = keep(sta, lane); zx = keep(zx, lane);
    p_smm = keepp(p_smm, lane); p_smx = keepp(p_smx, lane);
    {
      float d[16];
      mbar_wait(bar + 8 * B_X, 0, lim);
      gemm_x(w, sb, d);
      if (warp == 0) PTS(7);
      cluster_wait();
      if (warp == 0) PTS(24);
      stsm4t(zst + 8 * 16, pack2(d[0], d[1]), pack2(d[2], d[3]), pack2(d[4], d[5]), pack2(d[6], d[7]));
      stsm4t(zst + 24 * 16, pack2(d[8], d[9]), pack2(d[10], d[11]), pack2(d[12], d[13]), pack2(d[14], d[15]));
    }
    const uint32_t rda0 = keep(sb + O_REDO, lane);
    const uint32_t o_a = keep(mapa(sb + O_ORS + h * 256 + warp * 64 + (lane & 3) * 16, lane >> 2), lane);
    const uint32_t o_b = keep(mapa(bar + 8 * B_O, lane >> 2), lane);
    const uint32_t o_st = mapa(sb, 8) - mapa(sb, 0);
    uint32_t oh[8];
    auto token_pv = [&](int sp) {
      const uint32_t p16 = mimg + (O_P - O_MIMG) + (sp & 1) * 2560, p8 = p16 + 1024 - lane * 8, yb = sb + O_YB + (sp & 1) * 5120 + tid * 16;
      const uint4 y0 = lds_u4(yb), y1 = lds_u4(yb + 2048);
      const uint2 ymp = lds_u2(yb + 4096 - tid * 8);
      mbar_wait(bar + 8 * (B_P + (sp & 1)), (sp >> 1) & 1, lim);
      const uint2 m0 = lds_u2(p8), m1 = lds_u2(p8 + 1280);
      const uint4 p0 = lds_u4(p16), p1 = lds_u4(p16 + 512), p2 = lds_u4(p16 + 1280), p3 = lds_u4(p16 + 1280 + 512);
      float o0[4] = {0.f, 0.f, 0.f, 0.f}, o1[4] = {0.f, 0.f, 0.f, 0.f}, o2[4] = {0.f, 0.f, 0.f, 0.f}, o3[4] = {0.f, 0.f, 0.f, 0.f};
      mma8(o0, m0.x, m0.y, ymp.x);
      mma8(o1, m0.x, m0.y, ymp.y);
      mma8(o2, m1.x, m1.y, ymp.x);
      mma8(o3, m1.x, m1.y, ymp.y);
      mma16(o0, p0.x, p0.y, p0.z, p0.w, y0.x, y0.y);
      mma16(o1, p0.x, p0.y, p0.z, p0.w, y0.z, y0.w);
      mma16(o2, p2.x, p2.y, p2.z, p2.w, y0.x, y0.y);
      mma16(o3, p2.x, p2.y, p2.z, p2.w, y0.z, y0.w);
      mma16(o0, p1.x, p1.y, p1.z, p1.w, y1.x, y1.y);
      mma16(o1, p1.x, p1.y, p1.z, p1.w, y1.z, y1.w);
      mma16(o2, p3.x, p3.y, p3.z, p3.w, y1.x, y1.y);
      mma16(o3, p3.x, p3.y, p3.z, p3.w, y1.z, y1.w);
      oh[0] = pack2(o0[0], o0[1]); oh[1] = pack2(o1[0], o1[1]); oh[2] = pack2(o0[2], o0[3]); oh[3] = pack2(o1[2], o1[3]);
      oh[4] = pack2(o2[0], o2[1]); oh[5] = pack2(o3[0], o3[1]); oh[6] = pack2(o2[2], o2[3]); oh[7] = pack2(o3[2], o3[3]);
    };
    auto token_send = [&](int sp) {
      const bool last = sp >= NSEG - 2;
      const uint32_t oa = o_a + ((last ? 2 : 0) + (sp & 1)) * 4096, ob = o_b + ((last ? B_OL - B_O : 0) + (sp & 1)) * 8;
      st_async4u(oa, oh[0], oh[1], oh[2], oh[3], ob);
      st_async4u(oa + o_st, oh[4], oh[5], oh[6], oh[7], ob + o_st);
    };
#pragma unroll 1
    for (int s = 0; s < NSEG; s++) {
      const bool rec = s < NSEG - 1;
      uint32_t img = mimg + (s & 1) * 7168, zs = zst + (s & 1) * 5120, zl = zld + (s & 1) * 5120;
      uint32_t tag = ((s >> 1) + 1) & 3;
      uint8_t* smm = p_smm + (s & 1) * 1792;
      pin(img); pin(zs); pin(zl); pin(tag); pinp(smm);
      uint32_t a[4][4];
      if (rec) {
        uint32_t zb0[4], zb1[4];
        bar_sync(N_W1, 128);
        ldsm4(zb0, zx + (s & 1) * 5120);
        ldsm4(zb1, zx + (s & 1) * 5120 + 4 * 640);
        const uint32_t mj = s ? mimg + (O_MJ - O_MIMG) + (s & 1) * 1024 : img + j * 1024;
        if (s) mbar_wait(bar + 8 * (B_MJ + (s & 1)), ((s - 1) >> 1) & 1, lim);
        ldsm4(a[0], mj);
        ldsm4(a[1], mj + 512);
        const float2 e = mma_rows8(a[0], a[1], zb0, zb1);
        asm volatile("red.relaxed.gpu.global.add.v4.f32 [%0], {%1,%2,%3,%4};" :: "l"(p_smx + (s & 3) * (NH * 512)), "f"(e.x), "f"(e.y), "f"((float)(s + 1)), "f"(0.f) : "memory");
        if (warp == 0) TS(15);
      }
      if (s) mbar_wait(bar + 8 * (B_M + (s & 1)), ((s - 1) >> 1) & 1, lim);
      if (warp == 2) TS(0);
      if (warp == 2 && s == 63) PTS(27);
      if (warp == 2 && s == 0) PTS(28);
      if (warp == 2 && s == 1) PTS(29);
      float c[4];
      uint32_t b0[4], b1[4], rda = rda0;
      while (true) {
        gemm_m(w, img, c);
        stsm2t(zs, pack2(c[0], c[1]), pack2(c[2], c[3]));
        if (warp == 1) TS(24);
        bar_sync(N_ZM, 160);
        if (warp == 2) { ldsm4(b0, zl); ldsm4(b1, zl + 4 * 640); }
        const uint32_t redo = lds32v(rda);
        rda += 4;
        if (warp == 2) {
          const float2 e = mma_rows8(a[0], a[1], b0, b1);
          if (rec && !redo) { stg2r(smm, tagf(e.x, tag), tagf(e.y, tag)); stg2r(smm + XC_TWIN, tagf(e.x, tag), tagf(e.y, tag)); }
          if (lane == 0 && !redo) mbar_arrive(bar + 8 * B_YM);
          TS(2);
        }
        if (__builtin_expect(!__any_sync(0xffffffffu, redo), 1)) break;
        bar_sync(N_MOK, 128);
      }
      bar_sync(N_SS, 128);
      if (s >= 2) token_send(s - 2);
      if (warp != 2) {
        const uint32_t st = sta + (s & 1) * 5632, aq = xq + (s & 3) * XB;
        uint32_t b2[4], b3[4], b4[4], b5[4];
        ldsm4(a[0], aq); ldsm4(b0, zl); ldsm4(b2, zl + 128); ldsm4(b4, zl + 256); ldsm4(a[1], aq ^ 32);
        ldsm4(a[2], aq ^ 64); ldsm4(b1, zl + 2560); ldsm4(b3, zl + 2560 + 128); ldsm4(b5, zl + 2560 + 256); ldsm4(a[3], aq ^ 96);
        float e0[4] = {0.f, 0.f, 0.f, 0.f}, e1[4] = {0.f, 0.f, 0.f, 0.f}, e2[4] = {0.f, 0.f, 0.f, 0.f};
        mma16(e0, a[0][0], a[0][1], a[0][2], a[0][3], b0[0], b0[1]);
        mma16(e1, a[0][0], a[0][1], a[0][2], a[0][3], b2[0], b2[1]);
        mma16(e2, a[0][0], a[0][1], a[0][2], a[0][3], b4[0], b4[1]);
        mma16(e0, a[1][0], a[1][1], a[1][2], a[1][3], b0[2], b0[3]);
        mma16(e1, a[1][0], a[1][1], a[1][2], a[1][3], b2[2], b2[3]);
        mma16(e2, a[1][0], a[1][1], a[1][2], a[1][3], b4[2], b4[3]);
        mma16(e0, a[2][0], a[2][1], a[2][2], a[2][3], b1[0], b1[1]);
        mma16(e1, a[2][0], a[2][1], a[2][2], a[2][3], b3[0], b3[1]);
        mma16(e2, a[2][0], a[2][1], a[2][2], a[2][3], b5[0], b5[1]);
        mma16(e0, a[3][0], a[3][1], a[3][2], a[3][3], b1[2], b1[3]);
        mma16(e1, a[3][0], a[3][1], a[3][2], a[3][3], b3[2], b3[3]);
        mma16(e2, a[3][0], a[3][1], a[3][2], a[3][3], b5[2], b5[3]);
        sts_f4(st, e0[0], e0[1], e0[2], 1.f);
        sts_f4(st + 512, e0[3], e1[0], e1[1], 1.f);
        sts_f4(st + 1024, e1[2], e1[3], n0 ? 0.f : e2[0], 1.f);
        if (n0 == 0) sts_f4(st + 1536, e2[1], e2[2], e2[3], 1.f);
        if (warp == 1) TS(19);
        asm volatile("fence.proxy.async.shared::cta;" ::: "memory");
        __syncwarp();
        if (lane == 0) mbar_arrive(bar + 8 * (B_T + (s & 1)));
      }
      if (s) token_pv(s - 1);
      if (warp == 1) TS(5);
      if (rec) {
        float d[16];
        if (warp == 1) TS(16);
        mbar_wait(bar + 8 * (B_X + ((s + 1) & 3)), ((s + 1) >> 2) & 1, lim);
        bar_sync(N_ZX, 256);
        if (warp == 1) TS(17);
        gemm_x_issue(w, sb + ((s + 1) & 3) * XB, d);
        wg_wait<0>();
        reg_fence(d);
        if (warp == 1) TS(18);
        const uint32_t zn = zst + ((s + 1) & 1) * 5120;
        stsm4t(zn + 8 * 16, pack2(d[0], d[1]), pack2(d[2], d[3]), pack2(d[4], d[5]), pack2(d[6], d[7]));
        stsm4t(zn + 24 * 16, pack2(d[8], d[9]), pack2(d[10], d[11]), pack2(d[12], d[13]), pack2(d[14], d[15]));
        if (warp == 2) TS(3);
      }
    }
    token_send(NSEG - 2);
    bar_sync(N_ST, 256);
    token_pv(NSEG - 1);
    token_send(NSEG - 1);
    if (lim <= 0) g_err = 1;
    __syncwarp();
    if (warp == 0) PTS(25);
    cluster_arrive_relaxed();
    cluster_wait();
  } else if (warp < 8) {
    asm volatile("setmaxnreg.inc.sync.aligned.u32 216;");
    const int wq = warp - 4;
    uint32_t w[28][4];
    build_weights<1>(w, sb, lim, lane);
    cluster_wait();
    cluster_arrive_relaxed();
    uint32_t yx[8], ym[2];
    {
      float d[16];
      mbar_wait(bar + 8 * B_X, 0, lim);
      gemm_x(w, sb, d);
#pragma unroll
      for (int i = 0; i < 8; i++) yx[i] = pack2(d[2 * i], d[2 * i + 1]);
      cluster_wait();
    }
    const int ri = lane >> 2, q = lane & 3;
    uint32_t rs_a = mapa(sb + O_RS + h * 128 + ((ri & 1) * 4 + q) * 16, 4 * wq + (ri >> 1));
    uint32_t rs_b = mapa(bar + 8 * B_RS, 4 * wq + (ri >> 1));
    uint32_t mimg = sb + O_MIMG + lane * 16, l8 = sb + lane * 8;
    for (int k = wq; k < 22; k += 4) sts_u2(sb + O_GX + k * 256 + lane * 8, 0, 0);
    asm volatile("fence.proxy.async.shared::cta;" ::: "memory");
    bar_sync(N_INIT, 160);
    const uint32_t yb = sb + O_YB + (tid & 127) * 16;
    sts_u4(yb, yx[0], yx[4], yx[1], yx[5]);
    sts_u4(yb + 2048, yx[2], yx[6], yx[3], yx[7]);
    rs_a = keep(rs_a, lane); rs_b = keep(rs_b, lane); mimg = keep(mimg, lane); l8 = keep(l8, lane);

#pragma unroll 1
    for (int s = 0; s < NSEG; s++) {
      const bool rec = s < NSEG - 1;
      uint32_t img = mimg + (s & 1) * 7168, tag = ((s >> 1) + 1) & 3;
      uint32_t ra = rs_a + (s & 1) * 2048, rb = rs_b + (s & 1) * 8;
      pin(img); pin(tag); pin(ra); pin(rb);
      if (rec) {
        while (__all_sync(0xffffffffu, (int)lds32v(sb + O_C3) < s - 2) && --lim > 0) {}
      }
      if (wq == 0) TS(20);
      mbar_wait(bar + 8 * B_YM, s & 1, lim);
      float c[4];
      {
        const uint64_t dm = (uint64_t)(((sb + O_MIMG + (s & 1) * 7168) >> 4) & 0x3fff) | (8ull << 16) | (8ull << 32);
        wg_fence();
#pragma unroll
        for (int k = 0; k < 28; k++) wgmma_n8_rs(c, w[k], dm + k * 16, k != 0);
        wg_commit();
        if (wq == 0) TS(21);
      }
      float v[4][4], mxl = 0.f;
      if (rec) {
        const float full = 7.f * (s + 1);
        do {
#pragma unroll
          for (int n = 0; n < 4; n++)
            asm volatile("ld.volatile.shared.v4.f32 {%0,%1,%2,%3}, [%4];" : "=f"(v[n][0]), "=f"(v[n][1]), "=f"(v[n][2]), "=f"(v[n][3]) : "r"(mimg + (O_GY - O_MIMG) + n * 512) : "memory");
        } while (__any_sync(0xffffffffu, (v[0][2] + v[0][3] != full) | (v[1][2] + v[1][3] != full) | (v[2][2] + v[2][3] != full) | (v[3][2] + v[3][3] != full)) && --lim > 0);
        sts32v(sb + O_DONE + 4, s + 1);
        mxl = fmaxf(fmaxf(fmaxf(v[0][0], v[0][1]), fmaxf(v[1][0], v[1][1])), fmaxf(fmaxf(v[2][0], v[2][1]), fmaxf(v[3][0], v[3][1])));
        if (wq == 0) TS(22);
      }
      wg_wait<0>();
      reg_fence(c);
      ym[0] = pack2(c[0], c[1]);
      ym[1] = pack2(c[2], c[3]);
      if (rec) {
        uint32_t vm[14];
        const uint32_t gx = l8 + O_GX + (s & 1) * 1792;
        do {
#pragma unroll
          for (int k = 0; k < 7; k++) asm volatile("ld.volatile.shared.v2.u32 {%0,%1}, [%2];" : "=r"(vm[2 * k]), "=r"(vm[2 * k + 1]) : "r"(gx + k * 256) : "memory");
        } while (__any_sync(0xffffffffu, stale7(vm, tag)) && --lim > 0);
        sts32v(sb + O_DONE, s + 1);
        const float2 sm = add7(vm);
        if (wq == 0) TS(8);
        const float mx = qmax(fmaxf(mxl, fmaxf(sm.x, sm.y)));
        const float nb = -mx * SC2;
        uint32_t pa[4];
        float l = 0.f;
#pragma unroll
        for (int n = 0; n < 4; n++) {
          const float p0 = ex2(fmaf(v[n][0], SC2, nb)), p1 = ex2(fmaf(v[n][1], SC2, nb));
          l += p0 + p1;
          pa[n] = pack2(p0, p1);
        }
        float o0[4] = {0.f, 0.f, 0.f, 0.f}, o1[4] = {0.f, 0.f, 0.f, 0.f}, u0[4] = {0.f, 0.f, 0.f, 0.f}, u1[4] = {0.f, 0.f, 0.f, 0.f};
        mma16v(o0, pa[0], pa[1], pa[2], pa[3], yx[0], yx[4]);
        mma16v(o1, pa[0], pa[1], pa[2], pa[3], yx[1], yx[5]);
        mma16v(u0, pa[0], pa[1], pa[2], pa[3], yx[2], yx[6]);
        mma16v(u1, pa[0], pa[1], pa[2], pa[3], yx[3], yx[7]);
        const float p0 = ex2(fmaf(sm.x, SC2, nb)), p1 = ex2(fmaf(sm.y, SC2, nb));
        const uint32_t pp = pack2(p0, p1);
        mma8v(o0, pp, pp, ym[0]);
        mma8v(o1, pp, pp, ym[1]);
        const float inv = rcp(qsum(l + (p0 + p1)));
        st_async4(ra, (o0[0] + u0[2]) * inv, (o0[1] + u0[3]) * inv, (o1[0] + u1[2]) * inv, (o1[1] + u1[3]) * inv, rb);
      }
      sts_u2(yb + 4096 - (tid & 127) * 8 + (s & 1) * 5120, ym[0], ym[1]);
      if (!rec) bar_arrive(N_ST, 256);
      if (rec) {
        bar_arrive(N_ZX, 256);
        if (wq == 0) TS(9);
      }
      if (rec) {
        float d[16];
        mbar_wait(bar + 8 * (B_X + ((s + 1) & 3)), ((s + 1) >> 2) & 1, lim);
        gemm_x(w, sb + ((s + 1) & 3) * XB, d);
#pragma unroll
        for (int i = 0; i < 8; i++) yx[i] = pack2(d[2 * i], d[2 * i + 1]);
        sts_u4(yb + ((s + 1) & 1) * 5120, yx[0], yx[4], yx[1], yx[5]);
        sts_u4(yb + ((s + 1) & 1) * 5120 + 2048, yx[2], yx[6], yx[3], yx[7]);
        if (wq == 0) TS(10);
      }
    }
    if (lim <= 0) g_err = 1;
    __syncwarp();
    cluster_arrive_relaxed();
    cluster_wait();
  } else {
    asm volatile("setmaxnreg.dec.sync.aligned.u32 72;");
    if (warp == 8) {
      const int u = (lane & 15) >> 1, nt = lane & 1;
      uint8_t* gm0 = xch(16) + (XC_R0 + (lane >> 4) * XC_TWIN + (8 * j + 2 * (h >> 2) + nt) * 128 + (2 * (h & 3) + (u >> 2)) * 16 + (u & 3) * 4);
#pragma unroll
      for (int k = 0; k < 3; k++) asm volatile("st.relaxed.gpu.global.u32 [%0], 0xffffffff;" :: "l"(gm0 + k * XC_REG) : "memory");
      cluster_wait();
      if (lane == 0) {
        int lim1 = SPIN_LIMIT;
        if (h < 7) tma2d_mc(sb + h * 4096, &tmX, h * 64, 0, bar + 8 * B_X);
#pragma unroll 1
        for (int c = 4; c < 16; c++) {
          const int st = c & 3;
          mbar_wait1(bar + 8 * (B_PE + st), ((c >> 2) - 1) & 1, lim1);
          mbar_expect(bar + 8 * (B_PF + st), XB);
          tma2d(sb + (st + 1) * XB, (c & 1) ? &tmWv : &tmWk, h * DH + ((c >> 1) & 3) * 64, (c >> 3) * 224, bar + 8 * (B_PF + st));
        }
      }
      __syncwarp();
      cluster_arrive();
      cluster_wait();
      if (lane == 0) {
        for (int k = 1; k < 3; k++) {
          mbar_expect(bar + 8 * (B_X + k), XB);
          if (h < 7) tma2d_mc(sb + k * XB + h * 4096, &tmX, h * 64, k * 32, bar + 8 * (B_X + k));
        }
      }
      uint32_t chk = sb + O_MIMG + lane * 32 + (lane >> 2) * 4, rs0 = sb + O_RS + (lane >> 4) * 1024 + (lane & 15) * 8;
      const uint8_t* gnear = xch(16) + (XC_R0 + __shfl_sync(0xffffffffu, lds32v(sb + O_NEAR + 4), 0));
      const uint32_t pc_st = keep(sb + O_PC + (nt * 2 + (u >> 2)) * 16 + (u & 3) * 4, lane);
      const uint32_t mj_a = keep(mapa(sb + O_MJ + (2 * (h >> 2) + ((lane >> 1) & 1)) * 128 + (2 * (h & 3) + (lane & 1)) * 16, lane >> 2), lane);
      const uint32_t mj_b = keep(mapa(bar + 8 * B_MJ, lane >> 2), lane), mj_st = mapa(sb, 8) - mapa(sb, 0);
      chk = keep(chk, lane); rs0 = keep(rs0, lane); gm0 = keepp(gm0, lane);
      const uint32_t m2r = mapa(bar + 8 * (B_M2 + 1), lane & 15);
      auto cl_sync_arrive = [&](uint32_t a) { if (lane < 16) asm volatile("mbarrier.arrive.relaxed.cluster.shared::cluster.b64 _, [%0];" :: "r"(a) : "memory"); __syncwarp(); };
      const uint8_t* p_gsrc = xch(h) + (XC_R0 + 2 * XC_REG + __shfl_sync(0xffffffffu, lds32v(sb + O_NEAR), 0));
      bar_sync(N_INIT, 160);
      uint32_t m2p = 0;
      int s3 = 0;
#pragma unroll 1
      for (int s = 0; s < NSEG; s++) {
        uint32_t ck = chk + (s & 1) * 7168;
        pin(ck);
        bool redo = false;
        if (s) {
          mbar_wait(bar + 8 * (B_M + (s & 1)), ((s - 1) >> 1) & 1, lim);
          while (true) {
            uint32_t v[7];
#pragma unroll
            for (int k = 0; k < 7; k++) v[k] = lds32v(ck + k * 1024);
            const uint32_t mx = __vimax3_u32(__vimax3_u32(v[0], v[1], v[2]), __vimax3_u32(v[3], v[4], v[5]), v[6]);
            if (__builtin_expect(!__any_sync(0xffffffffu, mx == 0xffffffffu) || lim <= 0, 1)) break;
            redo = true;
            cl_sync_arrive(m2r);
            if (elect()) mbar_expect(bar + 8 * B_M2, 7168);
            mbar_wait(bar + 8 * (B_M2 + 1), m2p, lim);
            if (elect()) bulk_mc(sb + O_MIMG + (s & 1) * 7168 + h * 448, gnear + s3 * XC_REG + h * 448, 448, bar + 8 * B_M2);
            mbar_wait(bar + 8 * B_M2, m2p, lim);
            m2p ^= 1;
          }
        }
        TS(23);
        sts32v(sb + O_REDO, redo);
        bar_sync(N_ZM, 160);
        if (redo) bar_sync(N_ZM, 160);
        if (s == NSEG - 1) break;
        {
          const uint32_t tz = clk();
          const uint8_t* gsrc = p_gsrc + (s & 1) * 1792;
          asm volatile("{\n.reg .pred e, p, q, x;\n.reg .u32 t, u, f0, f1, td, n;\n.reg .u64 c;\n"
                       "elect.sync _|e, 0xffffffff;\nmov.u32 td, %9;\n"
                       "@e mbarrier.expect_tx.relaxed.cta.shared::cta.b64 [%3], 2048;\n"
                       "@e cp.async.bulk.shared::cluster.global.mbarrier::complete_tx::bytes [%6], [%7], 2048, [%3];\n"
                       "setp.eq.u32 x, td, td;\n"
                       "REFRESH:\nmov.u64 c, %%clock64;\nmov.b64 {t, u}, c;\nsub.u32 t, t, %1;\nsetp.lt.u32 p, t, td;\n@p bra.uni REFRESH;\n"
                       "selp.u32 n, 3840, 1792, x;\nand.pred q, e, x;\n"
                       "@e mbarrier.expect_tx.relaxed.cta.shared::cta.b64 [%3], n;\n"
                       "@e cp.async.bulk.shared::cluster.global.mbarrier::complete_tx::bytes [%4], [%5], 1792, [%3];\n"
                       "@q cp.async.bulk.shared::cluster.global.mbarrier::complete_tx::bytes [%6], [%7], 2048, [%3];\n"
                       "ld.volatile.shared.v2.u32 {f0, f1}, [%8];\nadd.u32 td, td, %10;\nsub.s32 %0, %0, 1;\n"
                       "setp.le.s32 x, f1, %2;\nsetp.le.s32 p, f0, %2;\nsetp.gt.and.s32 p, %0, 0, p;\n@p bra.uni REFRESH;\n}"
                       : "+r"(lim)
                       : "r"(tz), "r"(s), "r"(bar + 8 * B_G), "r"(sb + O_GX + (s & 1) * 1792), "l"(gsrc), "r"(sb + O_GY), "l"(&g_xacc[s & 3][h][0]),
                         "r"(sb + O_DONE), "n"(D_S), "n"(D_SS)
                       : "memory");
        }
        const int s3n = s3 == 2 ? 0 : s3 + 1;
        uint32_t rb = rs0 + (s & 1) * 2048;
        uint8_t* gm = gm0 + s3n * XC_REG;
        const uint32_t mdst = sb + O_MIMG + ((s + 1) & 1) * 7168 + h * 448, mb = bar + 8 * (B_M + ((s + 1) & 1));
        const uint8_t* msrc = gnear + s3n * XC_REG + h * 448;
        s3 = s3n;
        pin(rb); pinp(gm);
        mbar_wait(bar + 8 * (B_RS + (s & 1)), (s >> 1) & 1, lim);
        TS(11);
        uint2 v[8];
#pragma unroll
        for (int k = 0; k < 8; k++) v[k] = lds_u2(rb + k * 128);
        float s0 = ((__uint_as_float(v[0].x) + __uint_as_float(v[1].x)) + (__uint_as_float(v[2].x) + __uint_as_float(v[3].x))) +
                   ((__uint_as_float(v[4].x) + __uint_as_float(v[5].x)) + (__uint_as_float(v[6].x) + __uint_as_float(v[7].x)));
        float s1 = ((__uint_as_float(v[0].y) + __uint_as_float(v[1].y)) + (__uint_as_float(v[2].y) + __uint_as_float(v[3].y))) +
                   ((__uint_as_float(v[4].y) + __uint_as_float(v[5].y)) + (__uint_as_float(v[6].y) + __uint_as_float(v[7].y)));
        s0 += __shfl_xor_sync(0xffffffffu, s0, 16);
        s1 += __shfl_xor_sync(0xffffffffu, s1, 16);
        const uint32_t mw = pack2(s0, s1);
        asm volatile("st.relaxed.gpu.global.u32 [%0], %1;" :: "l"(gm), "r"(mw) : "memory");
        const uint32_t tm = clk();
        TS(12);
        sts32v(pc_st, mw);
        __syncwarp();
        const float4 pc = lds_f4(sb + O_PC + (lane & 3) * 16);
        if (s < NSEG - 2) {
          const uint32_t o = ((s + 1) & 1) * 1024, ob = ((s + 1) & 1) * 8;
          st_async4(mj_a + o, pc.x, pc.y, pc.z, pc.w, mj_b + ob);
          st_async4(mj_a + o + mj_st, pc.x, pc.y, pc.z, pc.w, mj_b + ob + mj_st);
        }
        const bool el = elect();
        if (el) mbar_expect(bar + 8 * (B_RS + (s & 1)), 2048);
        delay_until(tm, D_M);
        TS(25);
        if (el) bulk_mc(mdst, msrc, 448, mb);
      }
      if (elect()) mbar_arrive(bar + 8 * B_G);
      mbar_wait(bar + 8 * B_G, 0, lim);
    } else if (warp < 11) {
      const int mt = warp - 9, q = lane & 3;
#pragma unroll
      for (int t = mt * 32 + lane; t < 448; t += 64) {
        const uint4 v = *reinterpret_cast<const uint4*>(mem0 + (t & 7) * DM + (t >> 3) * 8);
        sts_u4(sb + O_MIMG + t * 16, v.x, v.y, v.z, v.w);
      }
      asm volatile("fence.proxy.async.shared::cta;" ::: "memory");
      if (mt == 1 && lane == 0) sts32v(sb + O_NEAR + 4, near_copy(xch(16) + 2 * XC_REG - (blockIdx.x % 7) * 128));
      __syncwarp();
      cluster_wait();
      cluster_arrive();
      cluster_wait();
      uint8_t* gm0 = xch(16) + (XC_R0 + (lane >> 4) * XC_TWIN + (8 * j + 2 * (h >> 2) + (lane & 1)) * 128 + (2 * (h & 3) + ((lane >> 3) & 1)) * 16 + ((lane >> 1) & 3) * 4);
      int s3p = 2;
#pragma unroll 1
      for (int s = 0; s < NSEG; s++) {
        mbar_wait(bar + 8 * (B_T + (s & 1)), (s >> 1) & 1, lim);
        if (s < NSEG - 1) while (__all_sync(0xffffffffu, (int)lds32v(sb + O_DONE) <= s) && --lim > 0) delay_until(clk(), 64);
        if (mt == 1 && s < NSEG - 1) {
          if (elect()) {
            mbar_expect(bar + 8 * (B_M + ((s + 1) & 1)), 7168);
            if (s < NSEG - 2) mbar_expect(bar + 8 * (B_MJ + ((s + 1) & 1)), 1024);
            if (s >= 1 && s + 2 < NSEG) {
              mbar_expect(bar + 8 * (B_X + ((s + 2) & 3)), XB);
              if (h < 7) tma2d_mc(sb + ((s + 2) & 3) * XB + h * 4096, &tmX, h * 64, (s + 2) * 32, bar + 8 * (B_X + ((s + 2) & 3)));
            }
          }
          asm volatile("st.relaxed.gpu.global.u32 [%0], 0xffffffff;" :: "l"(gm0 + s3p * XC_REG) : "memory");
          s3p = s3p == 2 ? 0 : s3p + 1;
        }
        const uint32_t t0 = clk();
        if (mt == 0 && elect()) {
          asm volatile("cp.reduce.async.bulk.global.shared::cta.bulk_group.add.f32 [%0], [%1], 5632;" :: "l"(&g_sacc[s & 7][h][0]), "r"(sb + O_ST + (s & 1) * 5632) : "memory");
          asm volatile("cp.async.bulk.commit_group;" ::: "memory");
          asm volatile("cp.async.bulk.wait_group.read 0;" ::: "memory");
        }
        __syncwarp();
        delay_until(t0, s == NSEG - 1 ? D_TL : D_T);
        if (mt) TS(28);
        const float4* sp = reinterpret_cast<const float4*>(&g_sacc[s & 7][h][mt * 512 + lane * 4]);
        float u[7][4];
        bool stale;
        do {
          stale = false;
#pragma unroll
          for (int c = 0; c < 7; c++) {
            u[c][0] = u[c][1] = u[c][2] = 0.f; u[c][3] = 7.f;
            if (c < 4 || mt)
              asm volatile("ld.relaxed.gpu.global.v4.f32 {%0,%1,%2,%3}, [%4];" : "=f"(u[c][0]), "=f"(u[c][1]), "=f"(u[c][2]), "=f"(u[c][3]) : "l"(sp + c * 32) : "memory");
          }
#pragma unroll
          for (int c = 0; c < 7; c++) stale |= u[c][3] != 7.f;
        } while (__any_sync(0xffffffffu, stale) && --lim > 0);
        if (mt) TS(29);
        uint32_t pk[2][5];
        float v[2][10];
#pragma unroll
        for (int e = 0; e < 10; e++) {
          const int i = 4 * (e >> 1) + (e & 1);
          v[0][e] = u[i / 3][i % 3];
          v[1][e] = u[(i + 2) / 3][(i + 2) % 3];
        }
#pragma unroll
        for (int rg = 0; rg < 2; rg++) {
          const int row = 16 * mt + 8 * rg + (lane >> 2);
#pragma unroll
          for (int e = 2; e < 10; e++)
            if (8 * ((e >> 1) - 1) + 2 * q + (e & 1) > row) v[rg][e] = MASKV;
          float mx = v[rg][0];
#pragma unroll
          for (int e = 1; e < 10; e++) mx = fmaxf(mx, v[rg][e]);
          mx = qmax(mx);
          const float nb = -mx * SC2;
          float l = 0.f;
#pragma unroll
          for (int e = 0; e < 10; e++) { v[rg][e] = ex2(fmaf(v[rg][e], SC2, nb)); l += v[rg][e]; }
          const float inv = rcp(qsum(l));
#pragma unroll
          for (int n = 0; n < 5; n++) pk[rg][n] = pack2(v[rg][2 * n] * inv, v[rg][2 * n + 1] * inv);
        }
        const uint32_t pb = sb + O_P + (s & 1) * 2560 + mt * 1280;
        sts_u4(pb + lane * 16, pk[0][1], pk[1][1], pk[0][3], pk[1][3]);
        sts_u4(pb + 512 + lane * 16, pk[0][2], pk[1][2], pk[0][4], pk[1][4]);
        sts_u2(pb + 1024 + lane * 8, pk[0][0], pk[1][0]);
        __syncwarp();
        if (lane == 0) mbar_arrive(bar + 8 * (B_P + (s & 1)));
        if (mt == 1) TS(13);
        if (j + 7 * mt < 11) asm volatile("st.relaxed.gpu.global.v4.f32 [%0], {%1,%1,%1,%1};" :: "l"(&g_sacc[(s + 4) & 7][h][(j + 7 * mt) * 128 + lane * 4]), "f"(0.f) : "memory");
      }
    } else {
      const int t1 = lane >> 4, l16 = lane & 15;
      const int col = j * 64 + ((lane >> 2) & 3) * 16 + (lane & 3) * 2;
      const uint32_t epoch = ldg1r(&g_ticket[0]) / 112 + 1;
      if (lane == 0) {
        sts32v(sb + O_NEAR, near_copy(xch(h)));
      }
      __syncwarp();
      cluster_wait();
      cluster_arrive();
      cluster_wait();
      const int trow = 16 * (h >> 3) + (h & 7) + 8 * t1;
      const uint32_t xg = sb + trow * 128 + (((l16 >> 1) ^ (trow & 7)) << 4) + (l16 & 1) * 8;
      auto gate = [&](int sg) {
        mbar_wait(bar + 8 * (B_X + (sg & 3)), (sg >> 2) & 1, lim);
        float z = 0.f;
#pragma unroll 1
        for (int k = 0; k < 7; k++) {
          const uint2 xv = lds_u2(xg + (sg & 3) * XB + k * 4096);
          const uint2 gw = *reinterpret_cast<const uint2*>(gate_w + (k * 16 + l16) * 4);
          z = fmaf(bf_lo(xv.x), bf_lo(gw.x), z); z = fmaf(bf_hi(xv.x), bf_hi(gw.x), z);
          z = fmaf(bf_lo(xv.y), bf_lo(gw.y), z); z = fmaf(bf_hi(xv.y), bf_hi(gw.y), z);
        }
#pragma unroll
        for (int o = 1; o < 16; o <<= 1) z += __shfl_xor_sync(0xffffffffu, z, o);
        return rcp(1.f + ex2(-1.4426950408889634f * z));
      };
      float4 pa4 = make_float4(0.f, 0.f, 0.f, 0.f);
      bool pend = false;
      auto finish = [&](int sg) {
        if (ldg1r(&g_bflag[sg >> 1][j >> 2][0]) == epoch) {
          const int o = (sg * 32 + trow) * DM + col;
          uint32_t b0, b1, b2, b3;
          ldg2r(b0, b1, g_b + o); ldg2r(b2, b3, g_b + o + 8);
          uint32_t* op = reinterpret_cast<uint32_t*>(out + o);
          op[0] = pack2(pa4.x + __uint_as_float(b0), pa4.y + __uint_as_float(b1));
          op[4] = pack2(pa4.z + __uint_as_float(b2), pa4.w + __uint_as_float(b3));
        }
      };
      float g1 = gate(0), g2 = gate(1);
#pragma unroll 1
      for (int s = 0; s < NSEG; s++) {
        const int tok = s * 32 + trow;
        const bool have_b = ldg1r(&g_bflag[s >> 1][j >> 2][0]) == epoch;
        const float* bp = &g_b[tok * DM + col];
        uint32_t b0 = 0, b1 = 0, b2 = 0, b3 = 0;
        if (have_b) { ldg2r(b0, b1, bp); ldg2r(b2, b3, bp + 8); }
        const bool last = s >= NSEG - 2;
        mbar_wait(bar + 8 * ((last ? B_OL : B_O) + (s & 1)), last ? 0 : (s >> 1) & 1, lim);
        if (pend) { if (s >= NSEG - 2) __threadfence(); finish(s - 1); }
        if (lane < 19 && j * 19 + lane < 128)
          asm volatile("st.relaxed.gpu.global.v4.f32 [%0], {%1,%1,%1,%1};" :: "l"(&g_xacc[s & 3][h][(j * 19 + lane) * 4]), "f"(0.f) : "memory");
        const float g = g1;
        g1 = g2;
        if (s + 2 < NSEG) g2 = gate(s + 2);
        const uint32_t ob = sb + O_ORS + ((last ? 2 : 0) + (s & 1)) * 4096 + t1 * 2048 + l16 * 16;
        float e[8] = {0.f, 0.f, 0.f, 0.f, 0.f, 0.f, 0.f, 0.f};
#pragma unroll 2
        for (int k = 0; k < 8; k++) {
          const uint4 c = lds_u4(ob + k * 256);
          e[0] += bf_lo(c.x); e[1] += bf_hi(c.x); e[2] += bf_lo(c.y); e[3] += bf_hi(c.y);
          e[4] += bf_lo(c.z); e[5] += bf_hi(c.z); e[6] += bf_lo(c.w); e[7] += bf_hi(c.w);
        }
        float4 a;
        a.x = g * ((t1 ? e[4] : e[0]) + __shfl_xor_sync(0xffffffffu, t1 ? e[0] : e[4], 16));
        a.y = g * ((t1 ? e[5] : e[1]) + __shfl_xor_sync(0xffffffffu, t1 ? e[1] : e[5], 16));
        a.z = g * ((t1 ? e[6] : e[2]) + __shfl_xor_sync(0xffffffffu, t1 ? e[2] : e[6], 16));
        a.w = g * ((t1 ? e[7] : e[3]) + __shfl_xor_sync(0xffffffffu, t1 ? e[3] : e[7], 16));
        __syncwarp();
        if (lane == 0 && s < NSEG - 4) mbar_expect(bar + 8 * (B_O + (s & 1)), 4096);
        if (lane == 0) sts32v(sb + O_C3, s + 1);
        if (s == 63) PTS(30);
        float* sp = &g_stash[tok * DM + col];
        stg2r(sp, tagf(a.x, epoch & 3), tagf(a.y, epoch & 3));
        stg2r(sp + 8, tagf(a.z, epoch & 3), tagf(a.w, epoch & 3));
        if (have_b) {
          uint32_t* op = reinterpret_cast<uint32_t*>(out + tok * DM + col);
          op[0] = pack2(a.x + __uint_as_float(b0), a.y + __uint_as_float(b1));
          op[4] = pack2(a.z + __uint_as_float(b2), a.w + __uint_as_float(b3));
        }
        pend = !have_b;
        pa4 = a;
        TS(14);
      }
      if (pend) { __threadfence(); finish(NSEG - 1); }
      if (lane == 0) atomicAdd(&g_ticket[0], 1);
    }
    if (lim <= 0) g_err = 1;
    __syncwarp();
    cluster_arrive_relaxed();
    cluster_wait();
  }
}

constexpr uint32_t F_STAGE = 49152, F_BAR = 4 * F_STAGE, F_G = F_BAR + 128, F_M = F_G + 512, F_SMEM = F_M + 1024 + 1024;

DEVI void release_stage(uint32_t sb, int st, int lane) {
  if (lane < 2) asm volatile("mbarrier.arrive.relaxed.cluster.shared::cluster.b64 _, [%0];" :: "r"(mapa(sb + F_BAR + 32 + 8 * st, lane)) : "memory");
}
template <int N>
DEVI void ffn_tile(float (&d)[N / 2], uint32_t sb, int wg, int nk, int& it, int& dead, int lane) {
#pragma unroll 1
  for (int k = 0; k < nk; k++, it++) {
    const int st = it & 3;
    mbar_wait(sb + F_BAR + 8 * st, (it >> 2) & 1, dead);
    const uint64_t da = desc128(sb + st * F_STAGE + wg * 8192, 1), db = desc128(sb + st * F_STAGE + 16384, 512);
    wg_fence();
#pragma unroll
    for (int kk = 0; kk < 4; kk++) {
      if constexpr (N == 256) wgmma_n256_kn(d, da + kk * 2, db + kk * 128, (k | kk) != 0);
      else                    wgmma_n192_kn(d, da + kk * 2, db + kk * 128, (k | kk) != 0);
    }
    wg_commit();
    if (k) { wg_wait<1>(); release_stage(sb, (it - 1) & 3, lane); }
  }
  wg_wait<0>();
  release_stage(sb, (it - 1) & 3, lane);
  reg_fence(d);
}

template <int NJ>
DEVI void ffn_finish(float (&d)[NJ * 32], float g0, float g1, uint32_t sb, int r0, int row, int j0, uint32_t epoch,
                     __nv_bfloat16* __restrict__ out, int tid) {
  const int wg = tid >> 7, t = tid & 127, off = (r0 + row) * DM + j0 * 64 + 2 * (tid & 3);
#pragma unroll
  for (int n = 0; n < NJ * 8; n++) {
    d[4 * n] *= g0; d[4 * n + 1] *= g0; d[4 * n + 2] *= g1; d[4 * n + 3] *= g1;
    *reinterpret_cast<float2*>(g_b + off + n * 8) = make_float2(d[4 * n], d[4 * n + 1]);
    *reinterpret_cast<float2*>(g_b + off + 8 * DM + n * 8) = make_float2(d[4 * n + 2], d[4 * n + 3]);
  }
  asm volatile("fence.release.gpu;" ::: "memory");
  bar_sync(2 + wg, 128);
  if (t == 0) {
    asm volatile("st.relaxed.gpu.global.u32 [%0], %1;" :: "l"(&g_bflag[(r0 >> 6) + wg][j0 >> 2][0]), "r"(epoch) : "memory");
    __threadfence();
  }
  bar_sync(2 + wg, 128);
#pragma unroll
  for (int n0 = 0; n0 < NJ * 8; n0 += 8) {
    uint32_t a[8][4];
#pragma unroll
    for (int n = 0; n < 8; n++) { ldg2r(a[n][0], a[n][1], g_stash + off + (n0 + n) * 8); ldg2r(a[n][2], a[n][3], g_stash + off + 8 * DM + (n0 + n) * 8); }
#pragma unroll
    for (int n = 0; n < 8; n++)
#pragma unroll
      for (int half = 0; half < 2; half++)
        if (((a[n][2 * half] ^ epoch) & 3) == 0)
          *reinterpret_cast<uint32_t*>(out + off + half * 8 * DM + (n0 + n) * 8) =
              pack2(__uint_as_float(a[n][2 * half]) + d[4 * (n0 + n) + 2 * half], __uint_as_float(a[n][2 * half + 1]) + d[4 * (n0 + n) + 2 * half + 1]);
  }
}

__global__ void __launch_bounds__(384, 1)
ffn_kernel(const __grid_constant__ CUtensorMap tmX, const __grid_constant__ CUtensorMap tmW1,
           const __grid_constant__ CUtensorMap tmH, const __grid_constant__ CUtensorMap tmW2,
           const __nv_bfloat16* __restrict__ x, const __nv_bfloat16* __restrict__ gate_w, __nv_bfloat16* __restrict__ out) {
  extern __shared__ uint8_t smem_raw[];
  const uint32_t sb = (smem_u32(smem_raw) + 1023) & ~1023u;
  const uint32_t hbar = sb + F_BAR + 64;
  int dead = SPIN_LIMIT;
  const int tid = threadIdx.x, lane = tid & 31, warp = __shfl_sync(0xffffffffu, tid >> 5, 0), r0 = blockIdx.x * 128;
  if (tid == 0) {
    for (int i = 0; i < 4; i++) { mbar_init(sb + F_BAR + 8 * i, 1); mbar_init(sb + F_BAR + 32 + 8 * i, 16); }
    mbar_init(hbar, 256);
    asm volatile("fence.mbarrier_init.release.cluster;" ::: "memory");
    asm volatile("fence.proxy.async.shared::cta;" ::: "memory");
  }
  __syncthreads();
  cluster_arrive_relaxed();
  cluster_wait();
  if (warp >= 8) {
    asm volatile("setmaxnreg.dec.sync.aligned.u32 56;");
    if (tid == 256) {
      int it = 0;
#pragma unroll 1
      for (int t = 0; t < 9; t++) {
        const int nk = t < 7 ? 7 : 28, nb = t < 8 ? 4 : 3;
        if (t == 7) mbar_wait1(hbar, 0, dead);
#pragma unroll 1
        for (int k = 0; k < nk; k++, it++) {
          const int st = it & 3;
          const uint32_t fb = sb + F_BAR + 8 * st, a = sb + st * F_STAGE;
          if (it >= 4) mbar_wait1(fb + 32, ((it >> 2) - 1) & 1, dead);
          mbar_expect(fb, 16384 + nb * 8192);
          tma2d(a, t < 7 ? &tmX : &tmH, k * 64, r0, fb);
          for (int b = blockIdx.x & 1; b < nb; b += 2)
            asm volatile("cp.async.bulk.tensor.2d.shared::cluster.global.mbarrier::complete_tx::bytes.multicast::cluster [%0], [%1, {%2, %3}], [%4], %5;"
                         :: "r"(a + 16384 + b * 8192), "l"(t < 7 ? &tmW1 : &tmW2), "r"((t < 7 ? t : t - 7) * 256 + b * 64), "r"(k * 64), "r"(fb), "h"((uint16_t)3) : "memory");
        }
      }
    } else if (warp > 8) {
      const int l16 = lane & 15;
      for (int r = (warp - 9) * 2 + (lane >> 4); r < 132; r += 6) {
        const int rr = r < 128 ? r : 127;
        float z = 0.f;
#pragma unroll
        for (int k = 0; k < 7; k++) {
          const uint2 xv = *reinterpret_cast<const uint2*>(x + (r0 + rr) * DM + (k * 16 + l16) * 4);
          const uint2 gv = *reinterpret_cast<const uint2*>(gate_w + (k * 16 + l16) * 4);
          z = fmaf(bf_lo(xv.x), bf_lo(gv.x), z); z = fmaf(bf_hi(xv.x), bf_hi(gv.x), z);
          z = fmaf(bf_lo(xv.y), bf_lo(gv.y), z); z = fmaf(bf_hi(xv.y), bf_hi(gv.y), z);
        }
#pragma unroll
        for (int o = 1; o < 16; o <<= 1) z += __shfl_xor_sync(0xffffffffu, z, o);
        if (l16 == 0) sts32v(sb + F_G + rr * 4, __float_as_uint(1.f - rcp(1.f + ex2(-1.4426950408889634f * z))));
      }
      __syncwarp();
      bar_arrive(1, 352);
    }
    __syncwarp();
    cluster_arrive_relaxed();
    cluster_wait();
  } else {
    asm volatile("setmaxnreg.inc.sync.aligned.u32 224;");
    const int wg = warp >> 2, row = wg * 64 + (warp & 3) * 16 + (lane >> 2), q = lane & 3;
    const uint32_t epoch = (ldg1r(&g_ticket[1]) >> 4) + 1;
    int it = 0;
#pragma unroll 1
    for (int t = 0; t < 7; t++) {
      float d[128];
      ffn_tile<256>(d, sb, wg, 7, it, dead, lane);
      __nv_bfloat16* hp = g_h + (size_t)(r0 + row) * DFF + t * 256 + 2 * q;
#pragma unroll
      for (int n = 0; n < 32; n++) {
        *reinterpret_cast<uint32_t*>(hp + n * 8) = pack2(fmaxf(d[4 * n], 0.f), fmaxf(d[4 * n + 1], 0.f));
        *reinterpret_cast<uint32_t*>(hp + 8 * DFF + n * 8) = pack2(fmaxf(d[4 * n + 2], 0.f), fmaxf(d[4 * n + 3], 0.f));
      }
    }
    __threadfence();
    asm volatile("fence.proxy.async;" ::: "memory");
    mbar_arrive(hbar);
    bar_sync(1, 352);
    const float g0 = __uint_as_float(lds32v(sb + F_G + row * 4)), g1 = __uint_as_float(lds32v(sb + F_G + row * 4 + 32));
    {
      float d[128];
      ffn_tile<256>(d, sb, wg, 28, it, dead, lane);
      ffn_finish<4>(d, g0, g1, sb, r0, row, 0, epoch, out, tid);
    }
    {
      float d[96];
      ffn_tile<192>(d, sb, wg, 28, it, dead, lane);
      ffn_finish<3>(d, g0, g1, sb, r0, row, 4, epoch, out, tid);
    }
    bar_sync(1, 256);
    if (tid == 0) atomicAdd(&g_ticket[1], 1);
    if (dead <= 0) g_err = 1;
    cluster_arrive_relaxed();
    cluster_wait();
  }
}

typedef CUresult (*EncodeFn)(CUtensorMap*, CUtensorMapDataType, cuuint32_t, void*, const cuuint64_t*, const cuuint64_t*,
                             const cuuint32_t*, const cuuint32_t*, CUtensorMapInterleave, CUtensorMapSwizzle,
                             CUtensorMapL2promotion, CUtensorMapFloatOOBfill);

void make_map(EncodeFn fn, CUtensorMap* m, const void* p, uint64_t rows, uint64_t cols, uint32_t box_rows) {
  const cuuint64_t dims[2] = {cols, rows}, strides[1] = {cols * 2};
  const cuuint32_t box[2] = {64, box_rows}, es[2] = {1, 1};
  fn(m, CU_TENSOR_MAP_DATA_TYPE_BFLOAT16, 2, const_cast<void*>(p), dims, strides, box, es, CU_TENSOR_MAP_INTERLEAVE_NONE,
     CU_TENSOR_MAP_SWIZZLE_128B, CU_TENSOR_MAP_L2_PROMOTION_L2_256B, CU_TENSOR_MAP_FLOAT_OOB_FILL_NONE);
}

}

extern "C" void kernel_launch(void* const* d_in, const int* in_sizes, int n_in, void* d_out, int out_size) {
  (void)in_sizes; (void)n_in; (void)out_size;
  const __nv_bfloat16* x = (const __nv_bfloat16*)d_in[0];
  const __nv_bfloat16* mem0 = (const __nv_bfloat16*)d_in[1];
  const __nv_bfloat16* gate_w = (const __nv_bfloat16*)d_in[10];
  static EncodeFn fn = nullptr;
  static void* hptr = nullptr;
  if (!fn) {
    cudaDriverEntryPointQueryResult qr;
    cudaGetDriverEntryPoint("cuTensorMapEncodeTiled", (void**)&fn, cudaEnableDefault, &qr);
    cudaGetSymbolAddress(&hptr, g_h);
    cudaFuncSetAttribute(rmt_kernel, cudaFuncAttributeMaxDynamicSharedMemorySize, T_SMEM);
    cudaFuncSetAttribute(rmt_kernel, cudaFuncAttributeNonPortableClusterSizeAllowed, 1);
    cudaFuncSetAttribute(ffn_kernel, cudaFuncAttributeMaxDynamicSharedMemorySize, F_SMEM);
  }
  CUtensorMap mWq, mWk, mWv, mWo, mX, mXf, mW1, mH, mW2;
  make_map(fn, &mWq, d_in[2], DM, NH * DH, 64);
  make_map(fn, &mWk, d_in[3], DM, NH * DH, 224);
  make_map(fn, &mWv, d_in[4], DM, NH * DH, 224);
  make_map(fn, &mWo, d_in[5], NH * DH, DM, 256);
  make_map(fn, &mX, x, SEQ, DM, 32);
  make_map(fn, &mXf, x, SEQ, DM, 128);
  make_map(fn, &mW1, d_in[8], DM, DFF, 64);
  make_map(fn, &mH, hptr, SEQ, DFF, 128);
  make_map(fn, &mW2, d_in[9], DFF, DM, 64);

  cudaLaunchConfig_t cfg = {};
  cudaLaunchAttribute at[2];
  cfg.gridDim = dim3(112); cfg.blockDim = dim3(384); cfg.dynamicSmemBytes = T_SMEM; cfg.stream = cudaStreamPerThread;
  at[0].id = cudaLaunchAttributeClusterDimension;
  at[0].val.clusterDim.x = 16; at[0].val.clusterDim.y = 1; at[0].val.clusterDim.z = 1;
  cfg.attrs = at; cfg.numAttrs = 1;
  cudaLaunchKernelEx(&cfg, rmt_kernel, mWq, mWk, mWv, mWo, mX, x, mem0, gate_w, (__nv_bfloat16*)d_out);

  cfg.gridDim = dim3(16); cfg.dynamicSmemBytes = F_SMEM;
  at[0].val.clusterDim.x = 2;
  at[1].id = cudaLaunchAttributeProgrammaticStreamSerialization;
  at[1].val.programmaticStreamSerializationAllowed = 1;
  cfg.numAttrs = 2;
  cudaLaunchKernelEx(&cfg, ffn_kernel, mXf, mW1, mH, mW2, x, gate_w, (__nv_bfloat16*)d_out);
}
```

```cpp
#include <cuda_runtime.h>
#include <cuda_bf16.h>
#include <cuda.h>
#include <stdint.h>

namespace {

#define DEVI __device__ __forceinline__

constexpr int SEQ = 2048, DM = 448, NH = 16, DH = 256, NSEG = 64, DFF = 1792;
constexpr float SC2 = 1.4426950408889634f / 16.0f;
constexpr float MASKV = -1.6e10f;
constexpr int SPIN_LIMIT = 1 << 20;

#define D_M 430
#define D_T 700
#define D_SS 145
#define D_TL 450
#define FFN_AT 12
#define D_S 140

__device__ __align__(1024) uint8_t g_mslot[3][8192];
__device__ __align__(1024) float g_smm[NH][2][7][64];
__device__ __align__(1024) float g_xacc[8][NH][512];
__device__ __align__(1024) float g_sacc[8][NH][1408];
__device__ __align__(1024) float g_stash[SEQ * DM];
__device__ __align__(1024) float g_b[SEQ * DM];
__device__ __align__(1024) __nv_bfloat16 g_h[SEQ * DFF];
__device__ __align__(1024) uint32_t g_bflag[32][2][8];
__device__ uint32_t g_ticket[2];
__device__ int g_err;

DEVI uint32_t smem_u32(const void* p) { return (uint32_t)__cvta_generic_to_shared(p); }
DEVI uint32_t clk() { uint32_t c; asm volatile("mov.u32 %0, %%clock;" : "=r"(c) :: "memory"); return c; }
DEVI void mbar_init(uint32_t bar, uint32_t cnt) { asm volatile("mbarrier.init.shared::cta.b64 [%0], %1;" :: "r"(bar), "r"(cnt) : "memory"); }
DEVI void mbar_expect(uint32_t bar, uint32_t bytes) { asm volatile("mbarrier.arrive.expect_tx.shared::cta.b64 _, [%0], %1;" :: "r"(bar), "r"(bytes) : "memory"); }
DEVI void mbar_arrive(uint32_t bar) { asm volatile("mbarrier.arrive.shared::cta.b64 _, [%0];" :: "r"(bar) : "memory"); }
DEVI uint32_t lds32v(uint32_t a) { uint32_t v; asm volatile("ld.volatile.shared::cta.u32 %0, [%1];" : "=r"(v) : "r"(a) : "memory"); return v; }
DEVI void sts32v(uint32_t a, uint32_t v) { asm volatile("st.volatile.shared::cta.u32 [%0], %1;" :: "r"(a), "r"(v) : "memory"); }
DEVI void mbar_wait(uint32_t bar, uint32_t par, int& lim) {
  asm volatile("{\n.reg .pred p, q;\nWAIT_LOOP:\n"
               "mbarrier.try_wait.parity.shared::cta.b64 p, [%1], %2;\n"
               "sub.s32 %0, %0, 1;\nsetp.gt.and.s32 q, %0, 0, !p;\n@q bra.uni WAIT_LOOP;\n}"
               : "+r"(lim) : "r"(bar), "r"(par) : "memory");
}
DEVI void mbar_wait1(uint32_t bar, uint32_t par, int& lim) {
  asm volatile("{\n.reg .pred p, q;\nWAIT_LOOP:\n"
               "mbarrier.try_wait.parity.shared::cta.b64 p, [%1], %2;\n"
               "sub.s32 %0, %0, 1;\nsetp.gt.and.s32 q, %0, 0, !p;\n@q bra WAIT_LOOP;\n}"
               : "+r"(lim) : "r"(bar), "r"(par) : "memory");
}
DEVI bool elect() { uint32_t p; asm volatile("{\n.reg .pred p;\nelect.sync _|p, 0xffffffff;\nselp.u32 %0, 1, 0, p;\n}" : "=r"(p)); return p; }
DEVI void delay_until(uint32_t t0, uint32_t d) {
  asm volatile("{\n.reg .pred p;\n.reg .u32 t, u;\n.reg .u64 c;\nDELAY_LOOP:\nmov.u64 c, %%clock64;\nmov.b64 {t, u}, c;\nsub.u32 t, t, %0;\nsetp.lt.u32 p, t, %1;\n@p bra.uni DELAY_LOOP;\n}"
               :: "r"(t0), "r"(d) : "memory");
}
DEVI float rcp(float x) { float y; asm("rcp.approx.ftz.f32 %0, %1;" : "=f"(y) : "f"(x)); return y; }
DEVI uint32_t keep(uint32_t v, int lane) { return __shfl_sync(0xffffffffu, v, lane); }
template <class T> DEVI T* keepp(T* p, int lane) { return reinterpret_cast<T*>(__shfl_sync(0xffffffffu, reinterpret_cast<unsigned long long>(p), lane)); }
template <class T> DEVI void pin(T& v) { asm volatile("" : "+r"(v)); }
template <class T> DEVI void pinp(T*& v) { asm volatile("" : "+l"(v)); }
DEVI void bar_sync(int id, int n) { asm volatile("bar.sync %0, %1;" :: "r"(id), "r"(n) : "memory"); }
DEVI void bar_arrive(int id, int n) { asm volatile("bar.arrive %0, %1;" :: "r"(id), "r"(n) : "memory"); }
DEVI void cluster_arrive_relaxed() { asm volatile("barrier.cluster.arrive.relaxed.aligned;" ::: "memory"); }
DEVI void cluster_arrive() { asm volatile("barrier.cluster.arrive.release.aligned;" ::: "memory"); }
DEVI void cluster_wait() { asm volatile("barrier.cluster.wait.acquire.aligned;" ::: "memory"); }
DEVI uint32_t mapa(uint32_t a, uint32_t r) { uint32_t o; asm("mapa.shared::cluster.u32 %0, %1, %2;" : "=r"(o) : "r"(a), "r"(r)); return o; }
DEVI uint32_t pack2(float lo, float hi) { uint32_t r; asm("cvt.rn.bf16x2.f32 %0, %1, %2;" : "=r"(r) : "f"(hi), "f"(lo)); return r; }
DEVI float ex2(float x) { float y; asm("ex2.approx.ftz.f32 %0, %1;" : "=f"(y) : "f"(x)); return y; }
DEVI float bf_lo(uint32_t v) { return __uint_as_float(v << 16); }
DEVI float bf_hi(uint32_t v) { return __uint_as_float(v & 0xffff0000u); }
DEVI void ldsm4(uint32_t (&r)[4], uint32_t a) {
  asm volatile("ldmatrix.sync.aligned.m8n8.x4.shared.b16 {%0,%1,%2,%3}, [%4];" : "=r"(r[0]), "=r"(r[1]), "=r"(r[2]), "=r"(r[3]) : "r"(a) : "memory");
}
DEVI void stsm4t(uint32_t a, uint32_t r0, uint32_t r1, uint32_t r2, uint32_t r3) {
  asm volatile("stmatrix.sync.aligned.m8n8.x4.trans.shared.b16 [%0], {%1,%2,%3,%4};" :: "r"(a), "r"(r0), "r"(r1), "r"(r2), "r"(r3) : "memory");
}
DEVI void stsm2t(uint32_t a, uint32_t r0, uint32_t r1) {
  asm volatile("stmatrix.sync.aligned.m8n8.x2.trans.shared.b16 [%0], {%1,%2};" :: "r"(a), "r"(r0), "r"(r1) : "memory");
}
DEVI void mma16(float (&c)[4], uint32_t a0, uint32_t a1, uint32_t a2, uint32_t a3, uint32_t b0, uint32_t b1) {
  asm("mma.sync.aligned.m16n8k16.row.col.f32.bf16.bf16.f32 {%0,%1,%2,%3},{%4,%5,%6,%7},{%8,%9},{%0,%1,%2,%3};"
      : "+f"(c[0]), "+f"(c[1]), "+f"(c[2]), "+f"(c[3]) : "r"(a0), "r"(a1), "r"(a2), "r"(a3), "r"(b0), "r"(b1));
}
DEVI void mma8(float (&c)[4], uint32_t a0, uint32_t a1, uint32_t b0) {
  asm("mma.sync.aligned.m16n8k8.row.col.f32.bf16.bf16.f32 {%0,%1,%2,%3},{%4,%5},{%6},{%0,%1,%2,%3};"
      : "+f"(c[0]), "+f"(c[1]), "+f"(c[2]), "+f"(c[3]) : "r"(a0), "r"(a1), "r"(b0));
}
DEVI void mma16v(float (&c)[4], uint32_t a0, uint32_t a1, uint32_t a2, uint32_t a3, uint32_t b0, uint32_t b1) {
  asm volatile("mma.sync.aligned.m16n8k16.row.col.f32.bf16.bf16.f32 {%0,%1,%2,%3},{%4,%5,%6,%7},{%8,%9},{%0,%1,%2,%3};"
      : "+f"(c[0]), "+f"(c[1]), "+f"(c[2]), "+f"(c[3]) : "r"(a0), "r"(a1), "r"(a2), "r"(a3), "r"(b0), "r"(b1));
}
DEVI void mma8v(float (&c)[4], uint32_t a0, uint32_t a1, uint32_t b0) {
  asm volatile("mma.sync.aligned.m16n8k8.row.col.f32.bf16.bf16.f32 {%0,%1,%2,%3},{%4,%5},{%6},{%0,%1,%2,%3};"
      : "+f"(c[0]), "+f"(c[1]), "+f"(c[2]), "+f"(c[3]) : "r"(a0), "r"(a1), "r"(b0));
}
DEVI float2 mma_rows8(const uint32_t (&a0)[4], const uint32_t (&a1)[4], const uint32_t (&b0)[4], const uint32_t (&b1)[4]) {
  float e0[4] = {0.f, 0.f, 0.f, 0.f}, e1[4] = {0.f, 0.f, 0.f, 0.f}, e2[4] = {0.f, 0.f, 0.f, 0.f}, e3[4] = {0.f, 0.f, 0.f, 0.f};
  mma16v(e0, a0[0], a0[1], a0[2], a0[3], b0[0], b0[1]);
  mma16v(e1, a0[0], a0[1], a0[2], a0[3], b0[2], b0[3]);
  mma16v(e2, a1[0], a1[1], a1[2], a1[3], b1[0], b1[1]);
  mma16v(e3, a1[0], a1[1], a1[2], a1[3], b1[2], b1[3]);
  return make_float2((e0[0] + e1[2]) + (e2[0] + e3[2]), (e0[1] + e1[3]) + (e2[1] + e3[3]));
}
DEVI void wg_fence() { asm volatile("wgmma.fence.sync.aligned;" ::: "memory"); }
DEVI void wg_commit() { asm volatile("wgmma.commit_group.sync.aligned;" ::: "memory"); }
template <int N> DEVI void wg_wait() { asm volatile("wgmma.wait_group.sync.aligned %0;" :: "n"(N) : "memory"); }
template <int N> DEVI void reg_fence(float (&d)[N]) {
#pragma unroll
  for (int i = 0; i < N; i++) asm volatile("" : "+f"(d[i]) :: "memory");
}
DEVI uint64_t desc128(uint32_t addr, uint32_t lbo16) {
  return (uint64_t)((addr >> 4) & 0x3fff) | ((uint64_t)lbo16 << 16) | (64ull << 32) | (1ull << 62);
}
DEVI void tma2d(uint32_t dst, const CUtensorMap* tm, int c0, int c1, uint32_t bar) {
  asm volatile("cp.async.bulk.tensor.2d.shared::cluster.global.mbarrier::complete_tx::bytes [%0], [%1, {%2, %3}], [%4];"
               :: "r"(dst), "l"(tm), "r"(c0), "r"(c1), "r"(bar) : "memory");
}
DEVI void tma2d_mc(uint32_t dst, const CUtensorMap* tm, int c0, int c1, uint32_t bar) {
  asm volatile("cp.async.bulk.tensor.2d.shared::cluster.global.mbarrier::complete_tx::bytes.multicast::cluster [%0], [%1, {%2, %3}], [%4], %5;"
               :: "r"(dst), "l"(tm), "r"(c0), "r"(c1), "r"(bar), "h"((uint16_t)0xffff) : "memory");
}
DEVI void bulk_ld(uint32_t dst, const void* src, uint32_t bytes, uint32_t bar) {
  asm volatile("cp.async.bulk.shared::cluster.global.mbarrier::complete_tx::bytes [%0], [%1], %2, [%3];"
               :: "r"(dst), "l"(src), "r"(bytes), "r"(bar) : "memory");
}
DEVI void bulk_mc(uint32_t dst, const void* src, uint32_t bytes, uint32_t bar) {
  asm volatile("cp.async.bulk.shared::cluster.global.mbarrier::complete_tx::bytes.multicast::cluster [%0], [%1], %2, [%3], %4;"
               :: "r"(dst), "l"(src), "r"(bytes), "r"(bar), "h"((uint16_t)0xffff) : "memory");
}
DEVI void st_async4(uint32_t a, float x, float y, float z, float w, uint32_t bar) {
  asm volatile("st.async.weak.shared::cluster.mbarrier::complete_tx::bytes.v4.f32 [%0], {%1,%2,%3,%4}, [%5];"
               :: "r"(a), "f"(x), "f"(y), "f"(z), "f"(w), "r"(bar) : "memory");
}
DEVI void st_async4u(uint32_t a, uint32_t x, uint32_t y, uint32_t z, uint32_t w, uint32_t bar) {
  asm volatile("st.async.weak.shared::cluster.mbarrier::complete_tx::bytes.v4.b32 [%0], {%1,%2,%3,%4}, [%5];"
               :: "r"(a), "r"(x), "r"(y), "r"(z), "r"(w), "r"(bar) : "memory");
}
DEVI uint32_t ldg1r(const void* p) { uint32_t v; asm volatile("ld.relaxed.gpu.global.u32 %0, [%1];" : "=r"(v) : "l"(p) : "memory"); return v; }
DEVI void ldg2r(uint32_t& x, uint32_t& y, const void* p) { asm volatile("ld.relaxed.gpu.global.v2.u32 {%0,%1}, [%2];" : "=r"(x), "=r"(y) : "l"(p) : "memory"); }
DEVI void stg2r(void* p, uint32_t x, uint32_t y) { asm volatile("st.relaxed.gpu.global.v2.u32 [%0], {%1,%2};" :: "l"(p), "r"(x), "r"(y) : "memory"); }
DEVI float2 lds_f2(uint32_t a) { float2 v; asm volatile("ld.shared.v2.f32 {%0,%1}, [%2];" : "=f"(v.x), "=f"(v.y) : "r"(a) : "memory"); return v; }
DEVI float4 lds_f4(uint32_t a) { float4 v; asm volatile("ld.shared.v4.f32 {%0,%1,%2,%3}, [%4];" : "=f"(v.x), "=f"(v.y), "=f"(v.z), "=f"(v.w) : "r"(a) : "memory"); return v; }
DEVI uint2 lds_u2(uint32_t a) { uint2 v; asm volatile("ld.shared.v2.u32 {%0,%1}, [%2];" : "=r"(v.x), "=r"(v.y) : "r"(a) : "memory"); return v; }
DEVI uint4 lds_u4(uint32_t a) { uint4 v; asm volatile("ld.shared.v4.u32 {%0,%1,%2,%3}, [%4];" : "=r"(v.x), "=r"(v.y), "=r"(v.z), "=r"(v.w) : "r"(a) : "memory"); return v; }
DEVI void sts_f2(uint32_t a, float x, float y) { asm volatile("st.shared.v2.f32 [%0], {%1,%2};" :: "r"(a), "f"(x), "f"(y) : "memory"); }
DEVI void sts_f4(uint32_t a, float x, float y, float z, float w) { asm volatile("st.shared.v4.f32 [%0], {%1,%2,%3,%4};" :: "r"(a), "f"(x), "f"(y), "f"(z), "f"(w) : "memory"); }
DEVI void sts_u2(uint32_t a, uint32_t x, uint32_t y) { asm volatile("st.shared.v2.u32 [%0], {%1,%2};" :: "r"(a), "r"(x), "r"(y) : "memory"); }
DEVI void sts_u4(uint32_t a, uint32_t x, uint32_t y, uint32_t z, uint32_t w) { asm volatile("st.shared.v4.u32 [%0], {%1,%2,%3,%4};" :: "r"(a), "r"(x), "r"(y), "r"(z), "r"(w) : "memory"); }
DEVI uint32_t tagf(float v, uint32_t tag) { return (__float_as_uint(v) & ~3u) | tag; }
DEVI float qmax(float v) { v = fmaxf(v, __shfl_xor_sync(0xffffffffu, v, 1)); return fmaxf(v, __shfl_xor_sync(0xffffffffu, v, 2)); }
DEVI float qsum(float v) { v += __shfl_xor_sync(0xffffffffu, v, 1); return v + __shfl_xor_sync(0xffffffffu, v, 2); }

__device__ __forceinline__ void wgmma_n224_kk(float (&d)[112], uint64_t da, uint64_t db, int sc) {
  asm volatile("{\n.reg .pred p;\nsetp.ne.b32 p, %114, 0;\n"
    "wgmma.mma_async.sync.aligned.m64n224k16.f32.bf16.bf16 {%0,%1,%2,%3,%4,%5,%6,%7,%8,%9,%10,%11,%12,%13,%14,%15,%16,%17,%18,%19,%20,%21,%22,%23,%24,%25,%26,%27,%28,%29,%30,%31,%32,%33,%34,%35,%36,%37,%38,%39,%40,%41,%42,%43,%44,%45,%46,%47,%48,%49,%50,%51,%52,%53,%54,%55,%56,%57,%58,%59,%60,%61,%62,%63,%64,%65,%66,%67,%68,%69,%70,%71,%72,%73,%74,%75,%76,%77,%78,%79,%80,%81,%82,%83,%84,%85,%86,%87,%88,%89,%90,%91,%92,%93,%94,%95,%96,%97,%98,%99,%100,%101,%102,%103,%104,%105,%106,%107,%108,%109,%110,%111}, %112, %113, p, 1, 1, 0, 0;\n}"
    : "+f"(d[0]),"+f"(d[1]),"+f"(d[2]),"+f"(d[3]),"+f"(d[4]),"+f"(d[5]),"+f"(d[6]),"+f"(d[7]),"+f"(d[8]),"+f"(d[9]),"+f"(d[10]),"+f"(d[11]),"+f"(d[12]),"+f"(d[13]),"+f"(d[14]),"+f"(d[15]),"+f"(d[16]),"+f"(d[17]),"+f"(d[18]),"+f"(d[19]),"+f"(d[20]),"+f"(d[21]),"+f"(d[22]),"+f"(d[23]),"+f"(d[24]),"+f"(d[25]),"+f"(d[26]),"+f"(d[27]),"+f"(d[28]),"+f"(d[29]),"+f"(d[30]),"+f"(d[31]),"+f"(d[32]),"+f"(d[33]),"+f"(d[34]),"+f"(d[35]),"+f"(d[36]),"+f"(d[37]),"+f"(d[38]),"+f"(d[39]),"+f"(d[40]),"+f"(d[41]),"+f"(d[42]),"+f"(d[43]),"+f"(d[44]),"+f"(d[45]),"+f"(d[46]),"+f"(d[47]),"+f"(d[48]),"+f"(d[49]),"+f"(d[50]),"+f"(d[51]),"+f"(d[52]),"+f"(d[53]),"+f"(d[54]),"+f"(d[55]),"+f"(d[56]),"+f"(d[57]),"+f"(d[58]),"+f"(d[59]),"+f"(d[60]),"+f"(d[61]),"+f"(d[62]),"+f"(d[63]),"+f"(d[64]),"+f"(d[65]),"+f"(d[66]),"+f"(d[67]),"+f"(d[68]),"+f"(d[69]),"+f"(d[70]),"+f"(d[71]),"+f"(d[72]),"+f"(d[73]),"+f"(d[74]),"+f"(d[75]),"+f"(d[76]),"+f"(d[77]),"+f"(d[78]),"+f"(d[79]),"+f"(d[80]),"+f"(d[81]),"+f"(d[82]),"+f"(d[83]),"+f"(d[84]),"+f"(d[85]),"+f"(d[86]),"+f"(d[87]),"+f"(d[88]),"+f"(d[89]),"+f"(d[90]),"+f"(d[91]),"+f"(d[92]),"+f"(d[93]),"+f"(d[94]),"+f"(d[95]),"+f"(d[96]),"+f"(d[97]),"+f"(d[98]),"+f"(d[99]),"+f"(d[100]),"+f"(d[101]),"+f"(d[102]),"+f"(d[103]),"+f"(d[104]),"+f"(d[105]),"+f"(d[106]),"+f"(d[107]),"+f"(d[108]),"+f"(d[109]),"+f"(d[110]),"+f"(d[111])
    : "l"(da),"l"(db),"r"(sc));
}
__device__ __forceinline__ void wgmma_n224_mk(float (&d)[112], uint64_t da, uint64_t db, int sc) {
  asm volatile("{\n.reg .pred p;\nsetp.ne.b32 p, %114, 0;\n"
    "wgmma.mma_async.sync.aligned.m64n224k16.f32.bf16.bf16 {%0,%1,%2,%3,%4,%5,%6,%7,%8,%9,%10,%11,%12,%13,%14,%15,%16,%17,%18,%19,%20,%21,%22,%23,%24,%25,%26,%27,%28,%29,%30,%31,%32,%33,%34,%35,%36,%37,%38,%39,%40,%41,%42,%43,%44,%45,%46,%47,%48,%49,%50,%51,%52,%53,%54,%55,%56,%57,%58,%59,%60,%61,%62,%63,%64,%65,%66,%67,%68,%69,%70,%71,%72,%73,%74,%75,%76,%77,%78,%79,%80,%81,%82,%83,%84,%85,%86,%87,%88,%89,%90,%91,%92,%93,%94,%95,%96,%97,%98,%99,%100,%101,%102,%103,%104,%105,%106,%107,%108,%109,%110,%111}, %112, %113, p, 1, 1, 1, 0;\n}"
    : "+f"(d[0]),"+f"(d[1]),"+f"(d[2]),"+f"(d[3]),"+f"(d[4]),"+f"(d[5]),"+f"(d[6]),"+f"(d[7]),"+f"(d[8]),"+f"(d[9]),"+f"(d[10]),"+f"(d[11]),"+f"(d[12]),"+f"(d[13]),"+f"(d[14]),"+f"(d[15]),"+f"(d[16]),"+f"(d[17]),"+f"(d[18]),"+f"(d[19]),"+f"(d[20]),"+f"(d[21]),"+f"(d[22]),"+f"(d[23]),"+f"(d[24]),"+f"(d[25]),"+f"(d[26]),"+f"(d[27]),"+f"(d[28]),"+f"(d[29]),"+f"(d[30]),"+f"(d[31]),"+f"(d[32]),"+f"(d[33]),"+f"(d[34]),"+f"(d[35]),"+f"(d[36]),"+f"(d[37]),"+f"(d[38]),"+f"(d[39]),"+f"(d[40]),"+f"(d[41]),"+f"(d[42]),"+f"(d[43]),"+f"(d[44]),"+f"(d[45]),"+f"(d[46]),"+f"(d[47]),"+f"(d[48]),"+f"(d[49]),"+f"(d[50]),"+f"(d[51]),"+f"(d[52]),"+f"(d[53]),"+f"(d[54]),"+f"(d[55]),"+f"(d[56]),"+f"(d[57]),"+f"(d[58]),"+f"(d[59]),"+f"(d[60]),"+f"(d[61]),"+f"(d[62]),"+f"(d[63]),"+f"(d[64]),"+f"(d[65]),"+f"(d[66]),"+f"(d[67]),"+f"(d[68]),"+f"(d[69]),"+f"(d[70]),"+f"(d[71]),"+f"(d[72]),"+f"(d[73]),"+f"(d[74]),"+f"(d[75]),"+f"(d[76]),"+f"(d[77]),"+f"(d[78]),"+f"(d[79]),"+f"(d[80]),"+f"(d[81]),"+f"(d[82]),"+f"(d[83]),"+f"(d[84]),"+f"(d[85]),"+f"(d[86]),"+f"(d[87]),"+f"(d[88]),"+f"(d[89]),"+f"(d[90]),"+f"(d[91]),"+f"(d[92]),"+f"(d[93]),"+f"(d[94]),"+f"(d[95]),"+f"(d[96]),"+f"(d[97]),"+f"(d[98]),"+f"(d[99]),"+f"(d[100]),"+f"(d[101]),"+f"(d[102]),"+f"(d[103]),"+f"(d[104]),"+f"(d[105]),"+f"(d[106]),"+f"(d[107]),"+f"(d[108]),"+f"(d[109]),"+f"(d[110]),"+f"(d[111])
    : "l"(da),"l"(db),"r"(sc));
}
__device__ __forceinline__ void wgmma_n32_rs(float (&d)[16], const uint32_t (&a)[4], uint64_t db, int sc) {
  asm volatile("{\n.reg .pred p;\nsetp.ne.b32 p, %21, 0;\n"
    "wgmma.mma_async.sync.aligned.m64n32k16.f32.bf16.bf16 {%0,%1,%2,%3,%4,%5,%6,%7,%8,%9,%10,%11,%12,%13,%14,%15}, {%16,%17,%18,%19}, %20, p, 1, 1, 0;\n}"
    : "+f"(d[0]),"+f"(d[1]),"+f"(d[2]),"+f"(d[3]),"+f"(d[4]),"+f"(d[5]),"+f"(d[6]),"+f"(d[7]),"+f"(d[8]),"+f"(d[9]),"+f"(d[10]),"+f"(d[11]),"+f"(d[12]),"+f"(d[13]),"+f"(d[14]),"+f"(d[15])
    : "r"(a[0]),"r"(a[1]),"r"(a[2]),"r"(a[3]),"l"(db),"r"(sc));
}
__device__ __forceinline__ void wgmma_n8_rs(float (&d)[4], const uint32_t (&a)[4], uint64_t db, int sc) {
  asm volatile("{\n.reg .pred p;\nsetp.ne.b32 p, %9, 0;\n"
    "wgmma.mma_async.sync.aligned.m64n8k16.f32.bf16.bf16 {%0,%1,%2,%3}, {%4,%5,%6,%7}, %8, p, 1, 1, 0;\n}"
    : "+f"(d[0]),"+f"(d[1]),"+f"(d[2]),"+f"(d[3])
    : "r"(a[0]),"r"(a[1]),"r"(a[2]),"r"(a[3]),"l"(db),"r"(sc));
}
__device__ __forceinline__ void wgmma_n256_kn(float (&d)[128], uint64_t da, uint64_t db, int sc) {
  asm volatile("{\n.reg .pred p;\nsetp.ne.b32 p, %130, 0;\n"
    "wgmma.mma_async.sync.aligned.m64n256k16.f32.bf16.bf16 {%0,%1,%2,%3,%4,%5,%6,%7,%8,%9,%10,%11,%12,%13,%14,%15,%16,%17,%18,%19,%20,%21,%22,%23,%24,%25,%26,%27,%28,%29,%30,%31,%32,%33,%34,%35,%36,%37,%38,%39,%40,%41,%42,%43,%44,%45,%46,%47,%48,%49,%50,%51,%52,%53,%54,%55,%56,%57,%58,%59,%60,%61,%62,%63,%64,%65,%66,%67,%68,%69,%70,%71,%72,%73,%74,%75,%76,%77,%78,%79,%80,%81,%82,%83,%84,%85,%86,%87,%88,%89,%90,%91,%92,%93,%94,%95,%96,%97,%98,%99,%100,%101,%102,%103,%104,%105,%106,%107,%108,%109,%110,%111,%112,%113,%114,%115,%116,%117,%118,%119,%120,%121,%122,%123,%124,%125,%126,%127}, %128, %129, p, 1, 1, 0, 1;\n}"
    : "+f"(d[0]),"+f"(d[1]),"+f"(d[2]),"+f"(d[3]),"+f"(d[4]),"+f"(d[5]),"+f"(d[6]),"+f"(d[7]),"+f"(d[8]),"+f"(d[9]),"+f"(d[10]),"+f"(d[11]),"+f"(d[12]),"+f"(d[13]),"+f"(d[14]),"+f"(d[15]),"+f"(d[16]),"+f"(d[17]),"+f"(d[18]),"+f"(d[19]),"+f"(d[20]),"+f"(d[21]),"+f"(d[22]),"+f"(d[23]),"+f"(d[24]),"+f"(d[25]),"+f"(d[26]),"+f"(d[27]),"+f"(d[28]),"+f"(d[29]),"+f"(d[30]),"+f"(d[31]),"+f"(d[32]),"+f"(d[33]),"+f"(d[34]),"+f"(d[35]),"+f"(d[36]),"+f"(d[37]),"+f"(d[38]),"+f"(d[39]),"+f"(d[40]),"+f"(d[41]),"+f"(d[42]),"+f"(d[43]),"+f"(d[44]),"+f"(d[45]),"+f"(d[46]),"+f"(d[47]),"+f"(d[48]),"+f"(d[49]),"+f"(d[50]),"+f"(d[51]),"+f"(d[52]),"+f"(d[53]),"+f"(d[54]),"+f"(d[55]),"+f"(d[56]),"+f"(d[57]),"+f"(d[58]),"+f"(d[59]),"+f"(d[60]),"+f"(d[61]),"+f"(d[62]),"+f"(d[63]),"+f"(d[64]),"+f"(d[65]),"+f"(d[66]),"+f"(d[67]),"+f"(d[68]),"+f"(d[69]),"+f"(d[70]),"+f"(d[71]),"+f"(d[72]),"+f"(d[73]),"+f"(d[74]),"+f"(d[75]),"+f"(d[76]),"+f"(d[77]),"+f"(d[78]),"+f"(d[79]),"+f"(d[80]),"+f"(d[81]),"+f"(d[82]),"+f"(d[83]),"+f"(d[84]),"+f"(d[85]),"+f"(d[86]),"+f"(d[87]),"+f"(d[88]),"+f"(d[89]),"+f"(d[90]),"+f"(d[91]),"+f"(d[92]),"+f"(d[93]),"+f"(d[94]),"+f"(d[95]),"+f"(d[96]),"+f"(d[97]),"+f"(d[98]),"+f"(d[99]),"+f"(d[100]),"+f"(d[101]),"+f"(d[102]),"+f"(d[103]),"+f"(d[104]),"+f"(d[105]),"+f"(d[106]),"+f"(d[107]),"+f"(d[108]),"+f"(d[109]),"+f"(d[110]),"+f"(d[111]),"+f"(d[112]),"+f"(d[113]),"+f"(d[114]),"+f"(d[115]),"+f"(d[116]),"+f"(d[117]),"+f"(d[118]),"+f"(d[119]),"+f"(d[120]),"+f"(d[121]),"+f"(d[122]),"+f"(d[123]),"+f"(d[124]),"+f"(d[125]),"+f"(d[126]),"+f"(d[127])
    : "l"(da),"l"(db),"r"(sc));
}
__device__ __forceinline__ void wgmma_n192_kn(float (&d)[96], uint64_t da, uint64_t db, int sc) {
  asm volatile("{\n.reg .pred p;\nsetp.ne.b32 p, %98, 0;\n"
    "wgmma.mma_async.sync.aligned.m64n192k16.f32.bf16.bf16 {%0,%1,%2,%3,%4,%5,%6,%7,%8,%9,%10,%11,%12,%13,%14,%15,%16,%17,%18,%19,%20,%21,%22,%23,%24,%25,%26,%27,%28,%29,%30,%31,%32,%33,%34,%35,%36,%37,%38,%39,%40,%41,%42,%43,%44,%45,%46,%47,%48,%49,%50,%51,%52,%53,%54,%55,%56,%57,%58,%59,%60,%61,%62,%63,%64,%65,%66,%67,%68,%69,%70,%71,%72,%73,%74,%75,%76,%77,%78,%79,%80,%81,%82,%83,%84,%85,%86,%87,%88,%89,%90,%91,%92,%93,%94,%95}, %96, %97, p, 1, 1, 0, 1;\n}"
    : "+f"(d[0]),"+f"(d[1]),"+f"(d[2]),"+f"(d[3]),"+f"(d[4]),"+f"(d[5]),"+f"(d[6]),"+f"(d[7]),"+f"(d[8]),"+f"(d[9]),"+f"(d[10]),"+f"(d[11]),"+f"(d[12]),"+f"(d[13]),"+f"(d[14]),"+f"(d[15]),"+f"(d[16]),"+f"(d[17]),"+f"(d[18]),"+f"(d[19]),"+f"(d[20]),"+f"(d[21]),"+f"(d[22]),"+f"(d[23]),"+f"(d[24]),"+f"(d[25]),"+f"(d[26]),"+f"(d[27]),"+f"(d[28]),"+f"(d[29]),"+f"(d[30]),"+f"(d[31]),"+f"(d[32]),"+f"(d[33]),"+f"(d[34]),"+f"(d[35]),"+f"(d[36]),"+f"(d[37]),"+f"(d[38]),"+f"(d[39]),"+f"(d[40]),"+f"(d[41]),"+f"(d[42]),"+f"(d[43]),"+f"(d[44]),"+f"(d[45]),"+f"(d[46]),"+f"(d[47]),"+f"(d[48]),"+f"(d[49]),"+f"(d[50]),"+f"(d[51]),"+f"(d[52]),"+f"(d[53]),"+f"(d[54]),"+f"(d[55]),"+f"(d[56]),"+f"(d[57]),"+f"(d[58]),"+f"(d[59]),"+f"(d[60]),"+f"(d[61]),"+f"(d[62]),"+f"(d[63]),"+f"(d[64]),"+f"(d[65]),"+f"(d[66]),"+f"(d[67]),"+f"(d[68]),"+f"(d[69]),"+f"(d[70]),"+f"(d[71]),"+f"(d[72]),"+f"(d[73]),"+f"(d[74]),"+f"(d[75]),"+f"(d[76]),"+f"(d[77]),"+f"(d[78]),"+f"(d[79]),"+f"(d[80]),"+f"(d[81]),"+f"(d[82]),"+f"(d[83]),"+f"(d[84]),"+f"(d[85]),"+f"(d[86]),"+f"(d[87]),"+f"(d[88]),"+f"(d[89]),"+f"(d[90]),"+f"(d[91]),"+f"(d[92]),"+f"(d[93]),"+f"(d[94]),"+f"(d[95])
    : "l"(da),"l"(db),"r"(sc));
}

constexpr uint32_t XB = 28672;
constexpr uint32_t O_WQ = 5 * XB;
constexpr uint32_t O_WO = O_WQ + 32768;
constexpr uint32_t O_MIMG = O_WO + 32768;
constexpr uint32_t O_BAR = O_MIMG + 2 * 7168;
constexpr uint32_t O_TS = O_BAR + 384;
constexpr uint32_t T_SMEM = O_TS + 4096 + 128 + 1024;
constexpr uint32_t O_Z = 4 * XB;
constexpr uint32_t O_RS = O_Z + 2 * 5120;
constexpr uint32_t O_ORS = O_RS + 2 * 2048;
constexpr uint32_t O_P = O_ORS + 4 * 4096;
constexpr uint32_t O_SX = O_P + 2 * 2560;
constexpr uint32_t O_MJ = O_SX + 1536;
constexpr uint32_t O_ST = O_MJ + 2048;
constexpr uint32_t O_PC = O_ST + 2 * 5632;
constexpr uint32_t O_YB = O_PC + 128;
constexpr uint32_t O_GX = O_YB + 2 * 5120;
constexpr uint32_t O_GY = O_GX + 2 * 1792;
enum { B_X = 0, B_M = 4, B_RS = 6, B_O = 8, B_ZX = 10, B_P = 12, B_PF = 14, B_PE = 18, B_WQ = 22, B_WO = 23, B_T = 24, B_MJ = 26, B_OL = 28, B_G = 30, B_M2 = 31, B_YM = 33, B_N = 34 };
constexpr uint32_t O_DONE = O_BAR + 8 * B_N, O_C3 = O_DONE + 8, O_REDO = O_C3 + 4;
enum { N_ZM = 1, N_MOK = 2, N_W1 = 3, N_INIT = 4, N_ZX = 5, N_REDO = 6, N_YX = 7, N_SS = 8, N_ST = 9 };

DEVI void gemm_m(const uint32_t (&w)[28][4], uint32_t img_lane, float (&c)[4]) {
  float acc[4][4];
#pragma unroll
  for (int i = 0; i < 4; i++) { acc[i][0] = acc[i][1] = acc[i][2] = acc[i][3] = 0.f; }
  uint32_t r[14][4];
#pragma unroll
  for (int u = 0; u < 14; u++) ldsm4(r[u], img_lane + u * 512);
#pragma unroll
  for (int u = 0; u < 14; u++) {
    mma16v(acc[(2 * u) & 3], w[2 * u][0], w[2 * u][1], w[2 * u][2], w[2 * u][3], r[u][0], r[u][1]);
    mma16v(acc[(2 * u + 1) & 3], w[2 * u + 1][0], w[2 * u + 1][1], w[2 * u + 1][2], w[2 * u + 1][3], r[u][2], r[u][3]);
  }
#pragma unroll
  for (int i = 0; i < 4; i++) c[i] = (acc[0][i] + acc[1][i]) + (acc[2][i] + acc[3][i]);
}

DEVI void gemm_x_issue(const uint32_t (&w)[28][4], uint32_t xbuf, float (&d)[16]) {
  const uint64_t b0 = desc128(xbuf, 1);
  wg_fence();
#pragma unroll
  for (int k = 0; k < 28; k++) wgmma_n32_rs(d, w[k], b0 + (uint64_t)((k >> 2) * 256 + (k & 3) * 2), k != 0);
  wg_commit();
}
DEVI void gemm_x(const uint32_t (&w)[28][4], uint32_t xbuf, float (&d)[16]) {
  gemm_x_issue(w, xbuf, d);
  wg_wait<0>();
  reg_fence(d);
}

template <int WHICH>
DEVI void build_weights(uint32_t (&w)[28][4], uint32_t sb, int& dead, int lane) {
  const uint32_t bar = sb + O_BAR;
  mbar_wait(bar + 8 * (WHICH ? B_WO : B_WQ), 0, dead);
#pragma unroll
  for (int half = 0; half < 2; half++) {
    float d[112];
#pragma unroll 1
    for (int fk = 0; fk < 4; fk++) {
      const int c = 2 * (4 * half + fk) + WHICH, st = c & 3;
      mbar_wait(bar + 8 * (B_PF + st), (c >> 2) & 1, dead);
      const uint64_t db = desc128(sb + (st + 1) * XB, 1);
      wg_fence();
#pragma unroll
      for (int kk = 0; kk < 4; kk++) {
        if (WHICH == 0) wgmma_n224_kk(d, desc128(sb + O_WQ + fk * 8192 + kk * 32, 1), db + kk * 2, (fk | kk) != 0);
        else            wgmma_n224_mk(d, desc128(sb + O_WO + (fk * 4 + kk) * 2048, 1), db + kk * 2, (fk | kk) != 0);
      }
      wg_commit();
      wg_wait<0>();
      if (lane == 0) mbar_arrive(bar + 8 * (B_PE + st));
    }
    reg_fence(d);
#pragma unroll
    for (int kk = 0; kk < 14; kk++) {
      w[14 * half + kk][0] = pack2(d[8 * kk + 0], d[8 * kk + 1]);
      w[14 * half + kk][1] = pack2(d[8 * kk + 2], d[8 * kk + 3]);
      w[14 * half + kk][2] = pack2(d[8 * kk + 4], d[8 * kk + 5]);
      w[14 * half + kk][3] = pack2(d[8 * kk + 6], d[8 * kk + 7]);
    }
  }
}

DEVI bool stale7(const uint32_t (&v)[14], uint32_t tag) {
  const uint32_t o = ((v[0] | v[1] | v[2]) | (v[3] | v[4] | v[5]) | (v[6] | v[7] | v[8])) | ((v[9] | v[10] | v[11]) | (v[12] | v[13]));
  const uint32_t a = ((v[0] & v[1] & v[2]) & (v[3] & v[4] & v[5]) & (v[6] & v[7] & v[8])) & ((v[9] & v[10] & v[11]) & (v[12] & v[13]));
  return (((o ^ tag) | (a ^ tag)) & 3u) != 0;
}
DEVI float2 add7(const uint32_t (&v)[14]) {
  float2 r;
  r.x = ((__uint_as_float(v[0]) + __uint_as_float(v[2])) + (__uint_as_float(v[4]) + __uint_as_float(v[6]))) +
        ((__uint_as_float(v[8]) + __uint_as_float(v[10])) + __uint_as_float(v[12]));
  r.y = ((__uint_as_float(v[1]) + __uint_as_float(v[3])) + (__uint_as_float(v[5]) + __uint_as_float(v[7]))) +
        ((__uint_as_float(v[9]) + __uint_as_float(v[11])) + __uint_as_float(v[13]));
  return r;
}

__global__ void __launch_bounds__(384, 1)
rmt_kernel(const __grid_constant__ CUtensorMap tmWq, const __grid_constant__ CUtensorMap tmWk,
           const __grid_constant__ CUtensorMap tmWv, const __grid_constant__ CUtensorMap tmWo,
           const __grid_constant__ CUtensorMap tmX, const __nv_bfloat16* __restrict__ x,
           const __nv_bfloat16* __restrict__ mem0, const __nv_bfloat16* __restrict__ gate_w, __nv_bfloat16* __restrict__ out) {
  extern __shared__ uint8_t smem_raw[];
  const uint32_t sb = (smem_u32(smem_raw) + 1023) & ~1023u;
  const uint32_t bar = sb + O_BAR;
  int lim = SPIN_LIMIT;
  int tid;
  uint32_t h, j;
  asm volatile("mov.u32 %0, %%tid.x;" : "=r"(tid));
  asm volatile("mov.u32 %0, %%cluster_ctarank;" : "=r"(h));
  asm volatile("mov.u32 %0, %%clusterid.x;" : "=r"(j));
  tid = __shfl_sync(0xffffffffu, tid, tid & 31);
  const int lane = tid & 31, warp = __shfl_sync(0xffffffffu, tid >> 5, 0);

  if (warp == 8) {
    if (elect()) {
#pragma unroll
      for (int i = 0; i < 4; i++) mbar_init(bar + 8 * (B_PF + i), 1);
      mbar_init(bar + 8 * B_WQ, 1);
      mbar_init(bar + 8 * B_WO, 1);
      asm volatile("fence.mbarrier_init.release.cluster;" ::: "memory");
      mbar_expect(bar + 8 * B_PF, XB);
      tma2d(sb + XB, &tmWk, h * DH, 0, bar + 8 * B_PF);
      mbar_expect(bar + 8 * B_WQ, 32768);
#pragma unroll
      for (int k = 0; k < 4; k++) tma2d(sb + O_WQ + k * 8192, &tmWq, h * DH + k * 64, j * 64, bar + 8 * B_WQ);
      mbar_expect(bar + 8 * B_WO, 32768);
      tma2d(sb + O_WO, &tmWo, j * 64, h * DH, bar + 8 * B_WO);
#pragma unroll
      for (int c = 1; c < 4; c++) {
        mbar_expect(bar + 8 * (B_PF + c), XB);
        tma2d(sb + (c + 1) * XB, (c & 1) ? &tmWv : &tmWk, h * DH + (c >> 1) * 64, 0, bar + 8 * (B_PF + c));
      }
    }
  } else if (warp == 9) {
    if (elect()) {
#pragma unroll
      for (int i = 0; i < B_N; i++)
        if (i < B_PF || (i >= B_PE && i < B_WQ) || i >= B_T) mbar_init(bar + 8 * i, i == B_M2 + 1 ? 16 : i >= B_MJ ? 1 : i >= B_T ? 3 : i >= B_PE ? 4 : i >= B_P ? 2 : i >= B_ZX ? 4 : 1);
      sts32v(sb + O_DONE, 0);
      sts32v(sb + O_C3, 0);
      sts32v(sb + O_REDO + 4, 0);
      sts32v(sb + O_DONE + 4, 0);
      mbar_expect(bar + 8 * B_X, XB);
      mbar_expect(bar + 8 * B_OL, 4096);
      mbar_expect(bar + 8 * (B_OL + 1), 4096);
#pragma unroll
      for (int i = 0; i < 2; i++) { mbar_expect(bar + 8 * (B_RS + i), 2048); mbar_expect(bar + 8 * (B_O + i), 4096); }
      asm volatile("fence.mbarrier_init.release.cluster;" ::: "memory");
    }
  }
  if (FFN_AT == 0) asm volatile("griddepcontrol.launch_dependents;");
  __syncthreads();
  cluster_arrive_relaxed();

  if (warp < 4) {
    asm volatile("setmaxnreg.inc.sync.aligned.u32 216;");
    uint32_t w[28][4];
    build_weights<0>(w, sb, lim, lane);
    cluster_wait();
    cluster_arrive_relaxed();
    uint32_t zst = sb + O_Z + ((2 * warp + ((lane >> 3) & 1)) * 40 + 8 * (lane >> 4) + (lane & 7)) * 16;
    const int mt = warp & 1, n0 = (warp >> 1) * 3;
    const int ch = lane >> 3, chp = (ch >> 1) | ((ch & 1) << 1);
    uint32_t zld = sb + O_Z + ((warp == 2 ? chp : ch) * 40 + (lane & 7)) * 16 + (warp == 2 ? 0 : n0 * 128);
    uint32_t zx = sb + O_Z + (chp * 40 + 8 + 8 * warp + (lane & 7)) * 16;
    float* p_smx = &g_xacc[0][h][warp * 128 + lane * 4];
    const int xrow = 16 * mt + (lane & 15);
    uint32_t xq = sb + j * 4096 + xrow * 128 + (((lane >> 4) ^ (xrow & 7)) << 4);
    uint32_t mimg = sb + O_MIMG + lane * 16, sta = sb + O_ST + (warp == 3 ? 4096 : mt * 2048) + lane * 16;
    float* p_smm = &g_smm[h][0][j][lane * 2];
    zst = keep(zst, lane); zld = keep(zld, lane); xq = keep(xq, lane); mimg = keep(mimg, lane); sta = keep(sta, lane); zx = keep(zx, lane);
    p_smm = keepp(p_smm, lane); p_smx = keepp(p_smx, lane);
    {
      float d[16];
      mbar_wait(bar + 8 * B_X, 0, lim);
      gemm_x(w, sb, d);
      cluster_wait();
      stsm4t(zst + 8 * 16, pack2(d[0], d[1]), pack2(d[2], d[3]), pack2(d[4], d[5]), pack2(d[6], d[7]));
      stsm4t(zst + 24 * 16, pack2(d[8], d[9]), pack2(d[10], d[11]), pack2(d[12], d[13]), pack2(d[14], d[15]));
    }
    const uint32_t rda0 = keep(sb + O_REDO, lane);
    const uint32_t o_a = keep(mapa(sb + O_ORS + h * 256 + warp * 64 + (lane & 3) * 16, lane >> 2), lane);
    const uint32_t o_b = keep(mapa(bar + 8 * B_O, lane >> 2), lane);
    const uint32_t o_st = mapa(sb, 8) - mapa(sb, 0);
    uint32_t oh[8];
    auto token_pv = [&](int sp) {
      const uint32_t p16 = mimg + (O_P - O_MIMG) + (sp & 1) * 2560, p8 = p16 + 1024 - lane * 8, yb = sb + O_YB + (sp & 1) * 5120 + tid * 16;
      const uint4 y0 = lds_u4(yb), y1 = lds_u4(yb + 2048);
      const uint2 ymp = lds_u2(yb + 4096 - tid * 8);
      mbar_wait(bar + 8 * (B_P + (sp & 1)), (sp >> 1) & 1, lim);
      const uint2 m0 = lds_u2(p8), m1 = lds_u2(p8 + 1280);
      const uint4 p0 = lds_u4(p16), p1 = lds_u4(p16 + 512), p2 = lds_u4(p16 + 1280), p3 = lds_u4(p16 + 1280 + 512);
      float o0[4] = {0.f, 0.f, 0.f, 0.f}, o1[4] = {0.f, 0.f, 0.f, 0.f}, o2[4] = {0.f, 0.f, 0.f, 0.f}, o3[4] = {0.f, 0.f, 0.f, 0.f};
      mma8(o0, m0.x, m0.y, ymp.x);
      mma8(o1, m0.x, m0.y, ymp.y);
      mma8(o2, m1.x, m1.y, ymp.x);
      mma8(o3, m1.x, m1.y, ymp.y);
      mma16(o0, p0.x, p0.y, p0.z, p0.w, y0.x, y0.y);
      mma16(o1, p0.x, p0.y, p0.z, p0.w, y0.z, y0.w);
      mma16(o2, p2.x, p2.y, p2.z, p2.w, y0.x, y0.y);
      mma16(o3, p2.x, p2.y, p2.z, p2.w, y0.z, y0.w);
      mma16(o0, p1.x, p1.y, p1.z, p1.w, y1.x, y1.y);
      mma16(o1, p1.x, p1.y, p1.z, p1.w, y1.z, y1.w);
      mma16(o2, p3.x, p3.y, p3.z, p3.w, y1.x, y1.y);
      mma16(o3, p3.x, p3.y, p3.z, p3.w, y1.z, y1.w);
      oh[0] = pack2(o0[0], o0[1]); oh[1] = pack2(o1[0], o1[1]); oh[2] = pack2(o0[2], o0[3]); oh[3] = pack2(o1[2], o1[3]);
      oh[4] = pack2(o2[0], o2[1]); oh[5] = pack2(o3[0], o3[1]); oh[6] = pack2(o2[2], o2[3]); oh[7] = pack2(o3[2], o3[3]);
    };
    auto token_send = [&](int sp) {
      const bool last = sp >= NSEG - 2;
      const uint32_t oa = o_a + ((last ? 2 : 0) + (sp & 1)) * 4096, ob = o_b + ((last ? B_OL - B_O : 0) + (sp & 1)) * 8;
      st_async4u(oa, oh[0], oh[1], oh[2], oh[3], ob);
      st_async4u(oa + o_st, oh[4], oh[5], oh[6], oh[7], ob + o_st);
    };
#pragma unroll 1
    for (int s = 0; s < NSEG; s++) {
      const bool rec = s < NSEG - 1;
      uint32_t img = mimg + (s & 1) * 7168, zs = zst + (s & 1) * 5120, zl = zld + (s & 1) * 5120;
      uint32_t tag = ((s >> 1) + 1) & 3;
      float* smm = p_smm + (s & 1) * 448;
      pin(img); pin(zs); pin(zl); pin(tag); pinp(smm);
      uint32_t a[4][4];
      if (rec) {
        uint32_t zb0[4], zb1[4];
        bar_sync(N_W1, 128);
        ldsm4(zb0, zx + (s & 1) * 5120);
        ldsm4(zb1, zx + (s & 1) * 5120 + 4 * 640);
        const uint32_t mj = s ? mimg + (O_MJ - O_MIMG) + (s & 1) * 1024 : img + j * 1024;
        if (s) mbar_wait(bar + 8 * (B_MJ + (s & 1)), ((s - 1) >> 1) & 1, lim);
        ldsm4(a[0], mj);
        ldsm4(a[1], mj + 512);
        const float2 e = mma_rows8(a[0], a[1], zb0, zb1);
        asm volatile("red.relaxed.gpu.global.add.v4.f32 [%0], {%1,%2,%3,%4};" :: "l"(p_smx + (s & 7) * (NH * 512)), "f"(e.x), "f"(e.y), "f"((float)(s + 1)), "f"(0.f) : "memory");
      }
      if (s) mbar_wait(bar + 8 * (B_M + (s & 1)), ((s - 1) >> 1) & 1, lim);
      float c[4];
      uint32_t b0[4], b1[4], rda = rda0;
      while (true) {
        gemm_m(w, img, c);
        stsm2t(zs, pack2(c[0], c[1]), pack2(c[2], c[3]));
        bar_sync(N_ZM, 160);
        if (warp == 2) { ldsm4(b0, zl); ldsm4(b1, zl + 4 * 640); }
        const uint32_t redo = lds32v(rda);
        rda += 4;
        if (warp == 2) {
          const float2 e = mma_rows8(a[0], a[1], b0, b1);
          if (rec && !redo) stg2r(smm, tagf(e.x, tag), tagf(e.y, tag));
          if (lane == 0 && !redo) mbar_arrive(bar + 8 * B_YM);
        }
        if (__builtin_expect(!__any_sync(0xffffffffu, redo), 1)) break;
        bar_sync(N_MOK, 128);
      }
      bar_sync(N_SS, 128);
      if (s >= 2) token_send(s - 2);
      if (warp != 2) {
        const uint32_t st = sta + (s & 1) * 5632, aq = xq + (s & 3) * XB;
        uint32_t b2[4], b3[4], b4[4], b5[4];
        ldsm4(a[0], aq); ldsm4(b0, zl); ldsm4(b2, zl + 128); ldsm4(b4, zl + 256); ldsm4(a[1], aq ^ 32);
        ldsm4(a[2], aq ^ 64); ldsm4(b1, zl + 2560); ldsm4(b3, zl + 2560 + 128); ldsm4(b5, zl + 2560 + 256); ldsm4(a[3], aq ^ 96);
        float e0[4] = {0.f, 0.f, 0.f, 0.f}, e1[4] = {0.f, 0.f, 0.f, 0.f}, e2[4] = {0.f, 0.f, 0.f, 0.f};
        mma16(e0, a[0][0], a[0][1], a[0][2], a[0][3], b0[0], b0[1]);
        mma16(e1, a[0][0], a[0][1], a[0][2], a[0][3], b2[0], b2[1]);
        mma16(e2, a[0][0], a[0][1], a[0][2], a[0][3], b4[0], b4[1]);
        mma16(e0, a[1][0], a[1][1], a[1][2], a[1][3], b0[2], b0[3]);
        mma16(e1, a[1][0], a[1][1], a[1][2], a[1][3], b2[2], b2[3]);
        mma16(e2, a[1][0], a[1][1], a[1][2], a[1][3], b4[2], b4[3]);
        mma16(e0, a[2][0], a[2][1], a[2][2], a[2][3], b1[0], b1[1]);
        mma16(e1, a[2][0], a[2][1], a[2][2], a[2][3], b3[0], b3[1]);
        mma16(e2, a[2][0], a[2][1], a[2][2], a[2][3], b5[0], b5[1]);
        mma16(e0, a[3][0], a[3][1], a[3][2], a[3][3], b1[2], b1[3]);
        mma16(e1, a[3][0], a[3][1], a[3][2], a[3][3], b3[2], b3[3]);
        mma16(e2, a[3][0], a[3][1], a[3][2], a[3][3], b5[2], b5[3]);
        sts_f4(st, e0[0], e0[1], e0[2], 1.f);
        sts_f4(st + 512, e0[3], e1[0], e1[1], 1.f);
        sts_f4(st + 1024, e1[2], e1[3], n0 ? 0.f : e2[0], 1.f);
        if (n0 == 0) sts_f4(st + 1536, e2[1], e2[2], e2[3], 1.f);
        asm volatile("fence.proxy.async.shared::cta;" ::: "memory");
        __syncwarp();
        if (lane == 0) mbar_arrive(bar + 8 * (B_T + (s & 1)));
      }
      if (s) token_pv(s - 1);
      if (rec) {
        float d[16];
        mbar_wait(bar + 8 * (B_X + ((s + 1) & 3)), ((s + 1) >> 2) & 1, lim);
        bar_sync(N_ZX, 256);
        gemm_x_issue(w, sb + ((s + 1) & 3) * XB, d);
        wg_wait<0>();
        reg_fence(d);
        const uint32_t zn = zst + ((s + 1) & 1) * 5120;
        stsm4t(zn + 8 * 16, pack2(d[0], d[1]), pack2(d[2], d[3]), pack2(d[4], d[5]), pack2(d[6], d[7]));
        stsm4t(zn + 24 * 16, pack2(d[8], d[9]), pack2(d[10], d[11]), pack2(d[12], d[13]), pack2(d[14], d[15]));
      }
    }
    token_send(NSEG - 2);
    bar_sync(N_ST, 256);
    token_pv(NSEG - 1);
    token_send(NSEG - 1);
    if (lim <= 0) g_err = 1;
    __syncwarp();
    cluster_arrive_relaxed();
    cluster_wait();
  } else if (warp < 8) {
    asm volatile("setmaxnreg.inc.sync.aligned.u32 216;");
    const int wq = warp - 4;
    uint32_t w[28][4];
    build_weights<1>(w, sb, lim, lane);
    cluster_wait();
    cluster_arrive_relaxed();
    uint32_t yx[8], ym[2];
    {
      float d[16];
      mbar_wait(bar + 8 * B_X, 0, lim);
      gemm_x(w, sb, d);
#pragma unroll
      for (int i = 0; i < 8; i++) yx[i] = pack2(d[2 * i], d[2 * i + 1]);
      cluster_wait();
    }
    const int ri = lane >> 2, q = lane & 3;
    uint32_t rs_a = mapa(sb + O_RS + h * 128 + ((ri & 1) * 4 + q) * 16, 4 * wq + (ri >> 1));
    uint32_t rs_b = mapa(bar + 8 * B_RS, 4 * wq + (ri >> 1));
    uint32_t mimg = sb + O_MIMG + lane * 16, l8 = sb + lane * 8;
    for (int k = wq; k < 22; k += 4) sts_u2(sb + O_GX + k * 256 + lane * 8, 0, 0);
    asm volatile("fence.proxy.async.shared::cta;" ::: "memory");
    bar_sync(N_INIT, 160);
    const uint32_t yb = sb + O_YB + (tid & 127) * 16;
    sts_u4(yb, yx[0], yx[4], yx[1], yx[5]);
    sts_u4(yb + 2048, yx[2], yx[6], yx[3], yx[7]);
    rs_a = keep(rs_a, lane); rs_b = keep(rs_b, lane); mimg = keep(mimg, lane); l8 = keep(l8, lane);

#pragma unroll 1
    for (int s = 0; s < NSEG; s++) {
      const bool rec = s < NSEG - 1;
      uint32_t img = mimg + (s & 1) * 7168, tag = ((s >> 1) + 1) & 3;
      uint32_t ra = rs_a + (s & 1) * 2048, rb = rs_b + (s & 1) * 8;
      pin(img); pin(tag); pin(ra); pin(rb);
      mbar_wait(bar + 8 * B_YM, s & 1, lim);
      float c[4];
      {
        const uint64_t dm = (uint64_t)(((sb + O_MIMG + (s & 1) * 7168) >> 4) & 0x3fff) | (8ull << 16) | (8ull << 32);
        wg_fence();
#pragma unroll
        for (int k = 0; k < 28; k++) wgmma_n8_rs(c, w[k], dm + k * 16, k != 0);
        wg_commit();
      }
      float v[4][4], mxl = 0.f;
      if (rec) {
        const float full = 7.f * (s + 1);
        do {
#pragma unroll
          for (int n = 0; n < 4; n++)
            asm volatile("ld.volatile.shared.v4.f32 {%0,%1,%2,%3}, [%4];" : "=f"(v[n][0]), "=f"(v[n][1]), "=f"(v[n][2]), "=f"(v[n][3]) : "r"(mimg + (O_GY - O_MIMG) + n * 512) : "memory");
        } while (__any_sync(0xffffffffu, (v[0][2] + v[0][3] != full) | (v[1][2] + v[1][3] != full) | (v[2][2] + v[2][3] != full) | (v[3][2] + v[3][3] != full)) && --lim > 0);
        sts32v(sb + O_DONE + 4, s + 1);
        mxl = fmaxf(fmaxf(fmaxf(v[0][0], v[0][1]), fmaxf(v[1][0], v[1][1])), fmaxf(fmaxf(v[2][0], v[2][1]), fmaxf(v[3][0], v[3][1])));
      }
      wg_wait<0>();
      reg_fence(c);
      ym[0] = pack2(c[0], c[1]);
      ym[1] = pack2(c[2], c[3]);
      if (rec) {
        uint32_t vm[14];
        const uint32_t gx = l8 + O_GX + (s & 1) * 1792;
        do {
#pragma unroll
          for (int k = 0; k < 7; k++) asm volatile("ld.volatile.shared.v2.u32 {%0,%1}, [%2];" : "=r"(vm[2 * k]), "=r"(vm[2 * k + 1]) : "r"(gx + k * 256) : "memory");
        } while (__any_sync(0xffffffffu, stale7(vm, tag)) && --lim > 0);
        sts32v(sb + O_DONE, s + 1);
        const float2 sm = add7(vm);
        const float mx = qmax(fmaxf(mxl, fmaxf(sm.x, sm.y)));
        const float nb = -mx * SC2;
        uint32_t pa[4];
        float l = 0.f;
#pragma unroll
        for (int n = 0; n < 4; n++) {
          const float p0 = ex2(fmaf(v[n][0], SC2, nb)), p1 = ex2(fmaf(v[n][1], SC2, nb));
          l += p0 + p1;
          pa[n] = pack2(p0, p1);
        }
        float o0[4] = {0.f, 0.f, 0.f, 0.f}, o1[4] = {0.f, 0.f, 0.f, 0.f}, u0[4] = {0.f, 0.f, 0.f, 0.f}, u1[4] = {0.f, 0.f, 0.f, 0.f};
        mma16v(o0, pa[0], pa[1], pa[2], pa[3], yx[0], yx[4]);
        mma16v(o1, pa[0], pa[1], pa[2], pa[3], yx[1], yx[5]);
        mma16v(u0, pa[0], pa[1], pa[2], pa[3], yx[2], yx[6]);
        mma16v(u1, pa[0], pa[1], pa[2], pa[3], yx[3], yx[7]);
        const float p0 = ex2(fmaf(sm.x, SC2, nb)), p1 = ex2(fmaf(sm.y, SC2, nb));
        const uint32_t pp = pack2(p0, p1);
        mma8v(o0, pp, pp, ym[0]);
        mma8v(o1, pp, pp, ym[1]);
        const float inv = rcp(qsum(l + (p0 + p1)));
        st_async4(ra, (o0[0] + u0[2]) * inv, (o0[1] + u0[3]) * inv, (o1[0] + u1[2]) * inv, (o1[1] + u1[3]) * inv, rb);
      }
      sts_u2(yb + 4096 - (tid & 127) * 8 + (s & 1) * 5120, ym[0], ym[1]);
      if (!rec) bar_arrive(N_ST, 256);
      if (rec) {
        bar_arrive(N_ZX, 256);
      }
      if (rec) {
        float d[16];
        mbar_wait(bar + 8 * (B_X + ((s + 1) & 3)), ((s + 1) >> 2) & 1, lim);
        gemm_x(w, sb + ((s + 1) & 3) * XB, d);
#pragma unroll
        for (int i = 0; i < 8; i++) yx[i] = pack2(d[2 * i], d[2 * i + 1]);
        sts_u4(yb + ((s + 1) & 1) * 5120, yx[0], yx[4], yx[1], yx[5]);
        sts_u4(yb + ((s + 1) & 1) * 5120 + 2048, yx[2], yx[6], yx[3], yx[7]);
      }
    }
    if (lim <= 0) g_err = 1;
    __syncwarp();
    cluster_arrive_relaxed();
    cluster_wait();
  } else {
    asm volatile("setmaxnreg.dec.sync.aligned.u32 72;");
    if (warp == 8) {
      const int u = (lane & 15) >> 1, nt = lane & 1;
      uint8_t* gm0 = &g_mslot[0][(8 * j + 2 * (h >> 2) + nt) * 128 + (2 * (h & 3) + (u >> 2)) * 16 + (u & 3) * 4];
#pragma unroll
      for (int k = 0; k < 3; k++) asm volatile("st.relaxed.gpu.global.u32 [%0], 0xffffffff;" :: "l"(gm0 + k * 8192) : "memory");
      cluster_wait();
      if (lane == 0) {
        int lim1 = SPIN_LIMIT;
        if (h < 7) tma2d_mc(sb + h * 4096, &tmX, h * 64, 0, bar + 8 * B_X);
#pragma unroll 1
        for (int c = 4; c < 16; c++) {
          const int st = c & 3;
          mbar_wait1(bar + 8 * (B_PE + st), ((c >> 2) - 1) & 1, lim1);
          if (c == FFN_AT) asm volatile("griddepcontrol.launch_dependents;");
          mbar_expect(bar + 8 * (B_PF + st), XB);
          tma2d(sb + (st + 1) * XB, (c & 1) ? &tmWv : &tmWk, h * DH + ((c >> 1) & 3) * 64, (c >> 3) * 224, bar + 8 * (B_PF + st));
        }
      }
      __syncwarp();
      cluster_arrive();
      cluster_wait();
      if (lane == 0) {
        for (int k = 1; k < 3; k++) {
          mbar_expect(bar + 8 * (B_X + k), XB);
          if (h < 7) tma2d_mc(sb + k * XB + h * 4096, &tmX, h * 64, k * 32, bar + 8 * (B_X + k));
        }
      }
      uint32_t chk = sb + O_MIMG + lane * 32 + (lane >> 2) * 4, rs0 = sb + O_RS + (lane >> 4) * 1024 + (lane & 15) * 8;
      const uint8_t* gnear = &g_mslot[0][0];
      const uint32_t pc_st = keep(sb + O_PC + (nt * 2 + (u >> 2)) * 16 + (u & 3) * 4, lane);
      const uint32_t mj_a = keep(mapa(sb + O_MJ + (2 * (h >> 2) + ((lane >> 1) & 1)) * 128 + (2 * (h & 3) + (lane & 1)) * 16, lane >> 2), lane);
      const uint32_t mj_b = keep(mapa(bar + 8 * B_MJ, lane >> 2), lane), mj_st = mapa(sb, 8) - mapa(sb, 0);
      chk = keep(chk, lane); rs0 = keep(rs0, lane); gm0 = keepp(gm0, lane);
      const uint32_t m2r = mapa(bar + 8 * (B_M2 + 1), lane & 15);
      auto cl_sync_arrive = [&](uint32_t a) { if (lane < 16) asm volatile("mbarrier.arrive.relaxed.cluster.shared::cluster.b64 _, [%0];" :: "r"(a) : "memory"); __syncwarp(); };
      const uint8_t* p_gsrc = reinterpret_cast<const uint8_t*>(&g_smm[h][0][0][0]);
      bar_sync(N_INIT, 160);
      uint32_t m2p = 0;
      int s3 = 0;
#pragma unroll 1
      for (int s = 0; s < NSEG; s++) {
        uint32_t ck = chk + (s & 1) * 7168;
        pin(ck);
        bool redo = false;
        if (s) {
          mbar_wait(bar + 8 * (B_M + (s & 1)), ((s - 1) >> 1) & 1, lim);
          while (true) {
            uint32_t v[7];
#pragma unroll
            for (int k = 0; k < 7; k++) v[k] = lds32v(ck + k * 1024);
            const uint32_t mx = __vimax3_u32(__vimax3_u32(v[0], v[1], v[2]), __vimax3_u32(v[3], v[4], v[5]), v[6]);
            if (__builtin_expect(!__any_sync(0xffffffffu, mx == 0xffffffffu) || lim <= 0, 1)) break;
            redo = true;
            cl_sync_arrive(m2r);
            if (elect()) mbar_expect(bar + 8 * B_M2, 7168);
            mbar_wait(bar + 8 * (B_M2 + 1), m2p, lim);
            if (elect()) bulk_mc(sb + O_MIMG + (s & 1) * 7168 + h * 448, gnear + s3 * 8192 + h * 448, 448, bar + 8 * B_M2);
            mbar_wait(bar + 8 * B_M2, m2p, lim);
            m2p ^= 1;
          }
        }
        sts32v(sb + O_REDO, redo);
        bar_sync(N_ZM, 160);
        if (redo) bar_sync(N_ZM, 160);
        if (s == NSEG - 1) break;
        {
          const uint32_t tz = clk();
          const uint8_t* gsrc = p_gsrc + (s & 1) * 1792;
          asm volatile("{\n.reg .pred e, p, q, x;\n.reg .u32 t, u, f0, f1, td, n;\n.reg .u64 c;\n"
                       "elect.sync _|e, 0xffffffff;\nmov.u32 td, %9;\n"
                       "@e mbarrier.expect_tx.relaxed.cta.shared::cta.b64 [%3], 2048;\n"
                       "@e cp.async.bulk.shared::cluster.global.mbarrier::complete_tx::bytes [%6], [%7], 2048, [%3];\n"
                       "setp.eq.u32 x, td, td;\n"
                       "REFRESH:\nmov.u64 c, %%clock64;\nmov.b64 {t, u}, c;\nsub.u32 t, t, %1;\nsetp.lt.u32 p, t, td;\n@p bra.uni REFRESH;\n"
                       "selp.u32 n, 3840, 1792, x;\nand.pred q, e, x;\n"
                       "@e mbarrier.expect_tx.relaxed.cta.shared::cta.b64 [%3], n;\n"
                       "@e cp.async.bulk.shared::cluster.global.mbarrier::complete_tx::bytes [%4], [%5], 1792, [%3];\n"
                       "@q cp.async.bulk.shared::cluster.global.mbarrier::complete_tx::bytes [%6], [%7], 2048, [%3];\n"
                       "ld.volatile.shared.v2.u32 {f0, f1}, [%8];\nadd.u32 td, td, %10;\nsub.s32 %0, %0, 1;\n"
                       "setp.le.s32 x, f1, %2;\nsetp.le.s32 p, f0, %2;\nsetp.gt.and.s32 p, %0, 0, p;\n@p bra.uni REFRESH;\n}"
                       : "+r"(lim)
                       : "r"(tz), "r"(s), "r"(bar + 8 * B_G), "r"(sb + O_GX + (s & 1) * 1792), "l"(gsrc), "r"(sb + O_GY), "l"(&g_xacc[s & 7][h][0]),
                         "r"(sb + O_DONE), "n"(D_S), "n"(D_SS)
                       : "memory");
        }
        while (__any_sync(0xffffffffu, (int)lds32v(sb + O_C3) < s - 2) && --lim > 0) {}
        const int s3n = s3 == 2 ? 0 : s3 + 1;
        uint32_t rb = rs0 + (s & 1) * 2048;
        uint8_t* gm = gm0 + s3n * 8192;
        const uint32_t mdst = sb + O_MIMG + ((s + 1) & 1) * 7168 + h * 448, mb = bar + 8 * (B_M + ((s + 1) & 1));
        const uint8_t* msrc = gnear + s3n * 8192 + h * 448;
        s3 = s3n;
        pin(rb); pinp(gm);
        mbar_wait(bar + 8 * (B_RS + (s & 1)), (s >> 1) & 1, lim);
        uint2 v[8];
#pragma unroll
        for (int k = 0; k < 8; k++) v[k] = lds_u2(rb + k * 128);
        float s0 = ((__uint_as_float(v[0].x) + __uint_as_float(v[1].x)) + (__uint_as_float(v[2].x) + __uint_as_float(v[3].x))) +
                   ((__uint_as_float(v[4].x) + __uint_as_float(v[5].x)) + (__uint_as_float(v[6].x) + __uint_as_float(v[7].x)));
        float s1 = ((__uint_as_float(v[0].y) + __uint_as_float(v[1].y)) + (__uint_as_float(v[2].y) + __uint_as_float(v[3].y))) +
                   ((__uint_as_float(v[4].y) + __uint_as_float(v[5].y)) + (__uint_as_float(v[6].y) + __uint_as_float(v[7].y)));
        s0 += __shfl_xor_sync(0xffffffffu, s0, 16);
        s1 += __shfl_xor_sync(0xffffffffu, s1, 16);
        const uint32_t mw = pack2(s0, s1);
        if (lane < 16) asm volatile("st.relaxed.gpu.global.u32 [%0], %1;" :: "l"(gm), "r"(mw) : "memory");
        const uint32_t tm = clk();
        sts32v(pc_st, mw);
        __syncwarp();
        const float4 pc = lds_f4(sb + O_PC + (lane & 3) * 16);
        if (s < NSEG - 2) {
          const uint32_t o = ((s + 1) & 1) * 1024, ob = ((s + 1) & 1) * 8;
          st_async4(mj_a + o, pc.x, pc.y, pc.z, pc.w, mj_b + ob);
          st_async4(mj_a + o + mj_st, pc.x, pc.y, pc.z, pc.w, mj_b + ob + mj_st);
        }
        const bool el = elect();
        if (el) mbar_expect(bar + 8 * (B_RS + (s & 1)), 2048);
        delay_until(tm, D_M);
        if (el) bulk_mc(mdst, msrc, 448, mb);
      }
      if (elect()) mbar_arrive(bar + 8 * B_G);
      mbar_wait(bar + 8 * B_G, 0, lim);
    } else if (warp < 11) {
      const int mt = warp - 9, q = lane & 3;
#pragma unroll
      for (int t = mt * 32 + lane; t < 448; t += 64) {
        const uint4 v = *reinterpret_cast<const uint4*>(mem0 + (t & 7) * DM + (t >> 3) * 8);
        sts_u4(sb + O_MIMG + t * 16, v.x, v.y, v.z, v.w);
      }
      asm volatile("fence.proxy.async.shared::cta;" ::: "memory");
      __syncwarp();
      cluster_wait();
      cluster_arrive();
      cluster_wait();
      uint8_t* gm0 = &g_mslot[0][(8 * j + 2 * (h >> 2) + (lane & 1)) * 128 + (2 * (h & 3) + ((lane >> 3) & 1)) * 16 + ((lane >> 1) & 3) * 4];
      int s3p = 2;
#pragma unroll 1
      for (int s = 0; s < NSEG; s++) {
        mbar_wait(bar + 8 * (B_T + (s & 1)), (s >> 1) & 1, lim);
        if (mt == 1 && s < NSEG - 1) {
          if (elect()) {
            mbar_expect(bar + 8 * (B_M + ((s + 1) & 1)), 7168);
            if (s < NSEG - 2) mbar_expect(bar + 8 * (B_MJ + ((s + 1) & 1)), 1024);
            if (s >= 1 && s + 2 < NSEG) {
              mbar_expect(bar + 8 * (B_X + ((s + 2) & 3)), XB);
              if (h < 7) tma2d_mc(sb + ((s + 2) & 3) * XB + h * 4096, &tmX, h * 64, (s + 2) * 32, bar + 8 * (B_X + ((s + 2) & 3)));
            }
          }
          asm volatile("st.relaxed.gpu.global.u32 [%0], 0xffffffff;" :: "l"(gm0 + s3p * 8192) : "memory");
          s3p = s3p == 2 ? 0 : s3p + 1;
        }
        const uint32_t t0 = clk();
        if (mt == 0 && elect()) {
          asm volatile("cp.reduce.async.bulk.global.shared::cta.bulk_group.add.f32 [%0], [%1], 5632;" :: "l"(&g_sacc[s & 7][h][0]), "r"(sb + O_ST + (s & 1) * 5632) : "memory");
          asm volatile("cp.async.bulk.commit_group;" ::: "memory");
          asm volatile("cp.async.bulk.wait_group.read 0;" ::: "memory");
        }
        __syncwarp();
        if (s < NSEG - 1) { mbar_wait(bar + 8 * (B_RS + (s & 1)), (s >> 1) & 1, lim); delay_until(t0, D_T); }
        else delay_until(t0, D_TL);
        const float4* sp = reinterpret_cast<const float4*>(&g_sacc[s & 7][h][mt * 512 + lane * 4]);
        float u[7][4];
        bool stale;
        do {
          stale = false;
#pragma unroll
          for (int c = 0; c < 7; c++) {
            u[c][0] = u[c][1] = u[c][2] = 0.f; u[c][3] = 7.f;
            if (c < 4 || mt)
              asm volatile("ld.relaxed.gpu.global.v4.f32 {%0,%1,%2,%3}, [%4];" : "=f"(u[c][0]), "=f"(u[c][1]), "=f"(u[c][2]), "=f"(u[c][3]) : "l"(sp + c * 32) : "memory");
          }
#pragma unroll
          for (int c = 0; c < 7; c++) stale |= u[c][3] != 7.f;
        } while (__any_sync(0xffffffffu, stale) && --lim > 0);
        uint32_t pk[2][5];
        float v[2][10];
#pragma unroll
        for (int e = 0; e < 10; e++) {
          const int i = 4 * (e >> 1) + (e & 1);
          v[0][e] = u[i / 3][i % 3];
          v[1][e] = u[(i + 2) / 3][(i + 2) % 3];
        }
#pragma unroll
        for (int rg = 0; rg < 2; rg++) {
          const int row = 16 * mt + 8 * rg + (lane >> 2);
#pragma unroll
          for (int e = 2; e < 10; e++)
            if (8 * ((e >> 1) - 1) + 2 * q + (e & 1) > row) v[rg][e] = MASKV;
          float mx = v[rg][0];
#pragma unroll
          for (int e = 1; e < 10; e++) mx = fmaxf(mx, v[rg][e]);
          mx = qmax(mx);
          const float nb = -mx * SC2;
          float l = 0.f;
#pragma unroll
          for (int e = 0; e < 10; e++) { v[rg][e] = ex2(fmaf(v[rg][e], SC2, nb)); l += v[rg][e]; }
          const float inv = rcp(qsum(l));
#pragma unroll
          for (int n = 0; n < 5; n++) pk[rg][n] = pack2(v[rg][2 * n] * inv, v[rg][2 * n + 1] * inv);
        }
        const uint32_t pb = sb + O_P + (s & 1) * 2560 + mt * 1280;
        sts_u4(pb + lane * 16, pk[0][1], pk[1][1], pk[0][3], pk[1][3]);
        sts_u4(pb + 512 + lane * 16, pk[0][2], pk[1][2], pk[0][4], pk[1][4]);
        sts_u2(pb + 1024 + lane * 8, pk[0][0], pk[1][0]);
        __syncwarp();
        if (lane == 0) mbar_arrive(bar + 8 * (B_P + (s & 1)));
        if (j + 7 * mt < 11) asm volatile("st.relaxed.gpu.global.v4.f32 [%0], {%1,%1,%1,%1};" :: "l"(&g_sacc[(s + 4) & 7][h][(j + 7 * mt) * 128 + lane * 4]), "f"(0.f) : "memory");
      }
    } else {
      const int t1 = lane >> 4, l16 = lane & 15;
      uint2 gw[7];
#pragma unroll
      for (int k = 0; k < 7; k++) gw[k] = *reinterpret_cast<const uint2*>(gate_w + (k * 16 + l16) * 4);
      const int col = j * 64 + ((lane >> 2) & 3) * 16 + (lane & 3) * 2;
      const uint32_t epoch = ldg1r(&g_ticket[0]) / 112 + 1;
      __syncwarp();
      cluster_wait();
      cluster_arrive();
      cluster_wait();
      const int trow = 16 * (h >> 3) + (h & 7) + 8 * t1;
      const uint32_t xg = sb + trow * 128 + (((l16 >> 1) ^ (trow & 7)) << 4) + (l16 & 1) * 8;
      auto gate = [&](int sg) {
        mbar_wait(bar + 8 * (B_X + (sg & 3)), (sg >> 2) & 1, lim);
        float z = 0.f, z2 = 0.f;
#pragma unroll
        for (int k = 0; k < 7; k++) {
          const uint2 xv = lds_u2(xg + (sg & 3) * XB + k * 4096);
          z = fmaf(bf_lo(xv.x), bf_lo(gw[k].x), z); z2 = fmaf(bf_hi(xv.x), bf_hi(gw[k].x), z2);
          z = fmaf(bf_lo(xv.y), bf_lo(gw[k].y), z); z2 = fmaf(bf_hi(xv.y), bf_hi(gw[k].y), z2);
        }
        z += z2;
#pragma unroll
        for (int o = 1; o < 16; o <<= 1) z += __shfl_xor_sync(0xffffffffu, z, o);
        return rcp(1.f + ex2(-1.4426950408889634f * z));
      };
      float4 pa4 = make_float4(0.f, 0.f, 0.f, 0.f);
      bool pend = false;
      auto finish = [&](int sg) {
        if (ldg1r(&g_bflag[sg >> 1][j >> 2][0]) == epoch) {
          const int o = (sg * 32 + trow) * DM + col;
          uint32_t b0, b1, b2, b3;
          ldg2r(b0, b1, g_b + o); ldg2r(b2, b3, g_b + o + 8);
          uint32_t* op = reinterpret_cast<uint32_t*>(out + o);
          op[0] = pack2(pa4.x + __uint_as_float(b0), pa4.y + __uint_as_float(b1));
          op[4] = pack2(pa4.z + __uint_as_float(b2), pa4.w + __uint_as_float(b3));
        }
      };
      float g1 = 0.f, g2 = 0.f;
#pragma unroll 1
      for (int s = -2; s < NSEG; s++) {
        if (s >= 0) {
        const int tok = s * 32 + trow;
        const bool have_b = ldg1r(&g_bflag[s >> 1][j >> 2][0]) == epoch;
        const float* bp = &g_b[tok * DM + col];
        uint32_t b0 = 0, b1 = 0, b2 = 0, b3 = 0;
        if (have_b) { ldg2r(b0, b1, bp); ldg2r(b2, b3, bp + 8); }
        const bool last = s >= NSEG - 2;
        mbar_wait(bar + 8 * ((last ? B_OL : B_O) + (s & 1)), last ? 0 : (s >> 1) & 1, lim);
        if (lane < 19 && j * 19 + lane < 128)
          asm volatile("st.relaxed.gpu.global.v4.f32 [%0], {%1,%1,%1,%1};" :: "l"(&g_xacc[s & 7][h][(j * 19 + lane) * 4]), "f"(0.f) : "memory");
        const float g = g1;
        const uint32_t ob = sb + O_ORS + ((last ? 2 : 0) + (s & 1)) * 4096 + t1 * 2048 + l16 * 16;
        float e[8] = {0.f, 0.f, 0.f, 0.f, 0.f, 0.f, 0.f, 0.f};
#pragma unroll 2
        for (int k = 0; k < 8; k++) {
          const uint4 c = lds_u4(ob + k * 256);
          e[0] += bf_lo(c.x); e[1] += bf_hi(c.x); e[2] += bf_lo(c.y); e[3] += bf_hi(c.y);
          e[4] += bf_lo(c.z); e[5] += bf_hi(c.z); e[6] += bf_lo(c.w); e[7] += bf_hi(c.w);
        }
        float4 a;
        a.x = g * ((t1 ? e[4] : e[0]) + __shfl_xor_sync(0xffffffffu, t1 ? e[0] : e[4], 16));
        a.y = g * ((t1 ? e[5] : e[1]) + __shfl_xor_sync(0xffffffffu, t1 ? e[1] : e[5], 16));
        a.z = g * ((t1 ? e[6] : e[2]) + __shfl_xor_sync(0xffffffffu, t1 ? e[2] : e[6], 16));
        a.w = g * ((t1 ? e[7] : e[3]) + __shfl_xor_sync(0xffffffffu, t1 ? e[3] : e[7], 16));
        __syncwarp();
        if (lane == 0 && s < NSEG - 4) mbar_expect(bar + 8 * (B_O + (s & 1)), 4096);
        float* sp = &g_stash[tok * DM + col];
        stg2r(sp, tagf(a.x, epoch & 3), tagf(a.y, epoch & 3));
        stg2r(sp + 8, tagf(a.z, epoch & 3), tagf(a.w, epoch & 3));
        if (have_b) {
          uint32_t* op = reinterpret_cast<uint32_t*>(out + tok * DM + col);
          op[0] = pack2(a.x + __uint_as_float(b0), a.y + __uint_as_float(b1));
          op[4] = pack2(a.z + __uint_as_float(b2), a.w + __uint_as_float(b3));
        }
        if (pend) { if (s >= NSEG - 2) __threadfence(); finish(s - 1); }
        pend = !have_b;
        pa4 = a;
        }
        g1 = g2;
        if (s + 2 < NSEG) g2 = gate(s + 2);
        if (lane == 0 && s >= 0) sts32v(sb + O_C3, s + 1);
      }
      if (pend) { __threadfence(); finish(NSEG - 1); }
      if (lane == 0) atomicAdd(&g_ticket[0], 1);
    }
    if (lim <= 0) g_err = 1;
    __syncwarp();
    cluster_arrive_relaxed();
    cluster_wait();
  }
}

constexpr uint32_t F_STAGE = 49152, F_BAR = 4 * F_STAGE, F_G = F_BAR + 128, F_STG = F_G + 512, F_SMEM = F_STG + 8 * 2304 + 1024;

DEVI void release_stage(uint32_t sb, int st, int lane) {
  if (lane < 2) asm volatile("mbarrier.arrive.relaxed.cluster.shared::cluster.b64 _, [%0];" :: "r"(mapa(sb + F_BAR + 32 + 8 * st, lane)) : "memory");
}
template <int N>
DEVI void ffn_tile(float (&d)[N / 2], uint32_t sb, int wg, int nk, int& it, int& dead, int lane) {
#pragma unroll 1
  for (int k = 0; k < nk; k++, it++) {
    const int st = it & 3;
    mbar_wait(sb + F_BAR + 8 * st, (it >> 2) & 1, dead);
    const uint64_t da = desc128(sb + st * F_STAGE + wg * 8192, 1), db = desc128(sb + st * F_STAGE + 16384, 512);
    wg_fence();
#pragma unroll
    for (int kk = 0; kk < 4; kk++) {
      if constexpr (N == 256) wgmma_n256_kn(d, da + kk * 2, db + kk * 128, (k | kk) != 0);
      else                    wgmma_n192_kn(d, da + kk * 2, db + kk * 128, (k | kk) != 0);
    }
    wg_commit();
    if (k) { wg_wait<1>(); release_stage(sb, (it - 1) & 3, lane); }
  }
  wg_wait<0>();
  release_stage(sb, (it - 1) & 3, lane);
  reg_fence(d);
}

template <int NJ>
DEVI void ffn_finish(float (&d)[NJ * 32], float g0, float g1, uint32_t sb, int r0, int row, int j0, uint32_t epoch,
                     __nv_bfloat16* __restrict__ out, int tid) {
  const int wg = tid >> 7, t = tid & 127, off = (r0 + row) * DM + j0 * 64 + 2 * (tid & 3);
#pragma unroll
  for (int n = 0; n < NJ * 8; n++) {
    d[4 * n] *= g0; d[4 * n + 1] *= g0; d[4 * n + 2] *= g1; d[4 * n + 3] *= g1;
    *reinterpret_cast<float2*>(g_b + off + n * 8) = make_float2(d[4 * n], d[4 * n + 1]);
    *reinterpret_cast<float2*>(g_b + off + 8 * DM + n * 8) = make_float2(d[4 * n + 2], d[4 * n + 3]);
  }
  asm volatile("fence.release.gpu;" ::: "memory");
  bar_sync(2 + wg, 128);
  if (t == 0) {
    asm volatile("st.relaxed.gpu.global.u32 [%0], %1;" :: "l"(&g_bflag[(r0 >> 6) + wg][j0 >> 2][0]), "r"(epoch) : "memory");
    __threadfence();
  }
  bar_sync(2 + wg, 128);
#pragma unroll
  for (int n0 = 0; n0 < NJ * 8; n0 += 8) {
    uint32_t a[8][4];
#pragma unroll
    for (int n = 0; n < 8; n++) { ldg2r(a[n][0], a[n][1], g_stash + off + (n0 + n) * 8); ldg2r(a[n][2], a[n][3], g_stash + off + 8 * DM + (n0 + n) * 8); }
#pragma unroll
    for (int n = 0; n < 8; n++)
#pragma unroll
      for (int half = 0; half < 2; half++)
        if (((a[n][2 * half] ^ epoch) & 3) == 0)
          *reinterpret_cast<uint32_t*>(out + off + half * 8 * DM + (n0 + n) * 8) =
              pack2(__uint_as_float(a[n][2 * half]) + d[4 * (n0 + n) + 2 * half], __uint_as_float(a[n][2 * half + 1]) + d[4 * (n0 + n) + 2 * half + 1]);
  }
}

__global__ void __launch_bounds__(384, 1)
ffn_kernel(const __grid_constant__ CUtensorMap tmX, const __grid_constant__ CUtensorMap tmW1,
           const __grid_constant__ CUtensorMap tmH, const __grid_constant__ CUtensorMap tmW2,
           const __nv_bfloat16* __restrict__ x, const __nv_bfloat16* __restrict__ gate_w, __nv_bfloat16* __restrict__ out) {
  extern __shared__ uint8_t smem_raw[];
  const uint32_t sb = (smem_u32(smem_raw) + 1023) & ~1023u;
  const uint32_t hbar = sb + F_BAR + 64;
  int dead = SPIN_LIMIT;
  const int tid = threadIdx.x, lane = tid & 31, warp = __shfl_sync(0xffffffffu, tid >> 5, 0), r0 = blockIdx.x * 128;
  if (tid == 0) {
    for (int i = 0; i < 4; i++) { mbar_init(sb + F_BAR + 8 * i, 1); mbar_init(sb + F_BAR + 32 + 8 * i, 16); }
    mbar_init(hbar, 256);
    asm volatile("fence.mbarrier_init.release.cluster;" ::: "memory");
    asm volatile("fence.proxy.async.shared::cta;" ::: "memory");
  }
  __syncthreads();
  cluster_arrive_relaxed();
  cluster_wait();
  if (warp >= 8) {
    asm volatile("setmaxnreg.dec.sync.aligned.u32 56;");
    if (tid == 256) {
      int it = 0;
#pragma unroll 1
      for (int t = 0; t < 9; t++) {
        const int nk = t < 7 ? 7 : 28, nb = t < 8 ? 4 : 3;
        if (t == 7) mbar_wait1(hbar, 0, dead);
#pragma unroll 1
        for (int k = 0; k < nk; k++, it++) {
          const int st = it & 3;
          const uint32_t fb = sb + F_BAR + 8 * st, a = sb + st * F_STAGE;
          if (it >= 4) mbar_wait1(fb + 32, ((it >> 2) - 1) & 1, dead);
          mbar_expect(fb, 16384 + nb * 8192);
          tma2d(a, t < 7 ? &tmX : &tmH, k * 64, r0, fb);
          for (int b = blockIdx.x & 1; b < nb; b += 2)
            asm volatile("cp.async.bulk.tensor.2d.shared::cluster.global.mbarrier::complete_tx::bytes.multicast::cluster [%0], [%1, {%2, %3}], [%4], %5;"
                         :: "r"(a + 16384 + b * 8192), "l"(t < 7 ? &tmW1 : &tmW2), "r"((t < 7 ? t : t - 7) * 256 + b * 64), "r"(k * 64), "r"(fb), "h"((uint16_t)3) : "memory");
        }
      }
    } else if (warp > 8) {
      const int l16 = lane & 15;
      for (int r = (warp - 9) * 2 + (lane >> 4); r < 132; r += 6) {
        const int rr = r < 128 ? r : 127;
        float z = 0.f;
#pragma unroll
        for (int k = 0; k < 7; k++) {
          const uint2 xv = *reinterpret_cast<const uint2*>(x + (r0 + rr) * DM + (k * 16 + l16) * 4);
          const uint2 gv = *reinterpret_cast<const uint2*>(gate_w + (k * 16 + l16) * 4);
          z = fmaf(bf_lo(xv.x), bf_lo(gv.x), z); z = fmaf(bf_hi(xv.x), bf_hi(gv.x), z);
          z = fmaf(bf_lo(xv.y), bf_lo(gv.y), z); z = fmaf(bf_hi(xv.y), bf_hi(gv.y), z);
        }
#pragma unroll
        for (int o = 1; o < 16; o <<= 1) z += __shfl_xor_sync(0xffffffffu, z, o);
        if (l16 == 0) sts32v(sb + F_G + rr * 4, __float_as_uint(1.f - rcp(1.f + ex2(-1.4426950408889634f * z))));
      }
      __syncwarp();
      bar_arrive(1, 352);
    }
    __syncwarp();
    cluster_arrive_relaxed();
    cluster_wait();
  } else {
    asm volatile("setmaxnreg.inc.sync.aligned.u32 224;");
    const int wg = warp >> 2, row = wg * 64 + (warp & 3) * 16 + (lane >> 2);
    const uint32_t epoch = (ldg1r(&g_ticket[1]) >> 4) + 1;
    int it = 0;
#pragma unroll 1
    for (int t = 0; t < 7; t++) {
      float d[128];
      ffn_tile<256>(d, sb, wg, 7, it, dead, lane);
      const uint32_t stg = sb + F_STG + warp * 2304;
      __nv_bfloat16* hp = g_h + (size_t)(r0 + warp * 16 + (lane >> 3)) * DFF + t * 256 + (lane & 7) * 8;
#pragma unroll
      for (int hf = 0; hf < 4; hf++) {
#pragma unroll
        for (int n = 0; n < 8; n += 2) {
          const float* e = d + 32 * hf + 4 * n;
          asm volatile("stmatrix.sync.aligned.m8n8.x4.shared.b16 [%0], {%1,%2,%3,%4};"
                       :: "r"(stg + (lane & 15) * 144 + (n + (lane >> 4)) * 16), "r"(pack2(fmaxf(e[0], 0.f), fmaxf(e[1], 0.f))), "r"(pack2(fmaxf(e[2], 0.f), fmaxf(e[3], 0.f))),
                          "r"(pack2(fmaxf(e[4], 0.f), fmaxf(e[5], 0.f))), "r"(pack2(fmaxf(e[6], 0.f), fmaxf(e[7], 0.f))) : "memory");
        }
        __syncwarp();
#pragma unroll
        for (int r = 0; r < 4; r++) {
          const uint4 v = lds_u4(stg + (4 * r + (lane >> 3)) * 144 + (lane & 7) * 16);
          *reinterpret_cast<uint4*>(hp + (size_t)4 * r * DFF + hf * 64) = v;
        }
        __syncwarp();
      }
    }
    __threadfence();
    asm volatile("fence.proxy.async;" ::: "memory");
    mbar_arrive(hbar);
    bar_sync(1, 352);
    const float g0 = __uint_as_float(lds32v(sb + F_G + row * 4)), g1 = __uint_as_float(lds32v(sb + F_G + row * 4 + 32));
    {
      float d[128];
      ffn_tile<256>(d, sb, wg, 28, it, dead, lane);
      ffn_finish<4>(d, g0, g1, sb, r0, row, 0, epoch, out, tid);
    }
    {
      float d[96];
      ffn_tile<192>(d, sb, wg, 28, it, dead, lane);
      ffn_finish<3>(d, g0, g1, sb, r0, row, 4, epoch, out, tid);
    }
    bar_sync(1, 256);
    if (tid == 0) atomicAdd(&g_ticket[1], 1);
    if (dead <= 0) g_err = 1;
    cluster_arrive_relaxed();
    cluster_wait();
  }
}

__device__ float g_fmem[8 * DM];
__global__ void fb_qkv(const __nv_bfloat16* x, const __nv_bfloat16* mem0, const __nv_bfloat16* wq, const __nv_bfloat16* wk,
                       const __nv_bfloat16* wv, int s) {
  __shared__ __nv_bfloat16 hs[40 * DM];
  for (int i = threadIdx.x; i < 40 * DM; i += 128)
    hs[i] = i >= 8 * DM ? x[s * 32 * DM + i - 8 * DM] : s ? __float2bfloat16(g_fmem[i]) : mem0[i];
  __syncthreads();
  const int col = blockIdx.x * 128 + threadIdx.x;
  const __nv_bfloat16* w = (blockIdx.y == 0 ? wq : blockIdx.y == 1 ? wk : wv) + col;
  float acc[40];
#pragma unroll
  for (int r = 0; r < 40; r++) acc[r] = 0.f;
  for (int d = 0; d < DM; d++) {
    const float wv_ = __bfloat162float(w[d * 4096]);
#pragma unroll
    for (int r = 0; r < 40; r++) acc[r] = fmaf(__bfloat162float(hs[r * DM + d]), wv_, acc[r]);
  }
#pragma unroll
  for (int r = 0; r < 40; r++) g_b[(blockIdx.y * 40 + r) * 4096 + col] = acc[r];
}
__global__ void fb_attn() {
  __shared__ float p[40];
  const int h = blockIdx.x, r = blockIdx.y, t = threadIdx.x;
  if (t < 40) {
    float a = 0.f;
    for (int e = 0; e < DH; e++) a = fmaf(g_b[r * 4096 + h * DH + e], g_b[(40 + t) * 4096 + h * DH + e], a);
    p[t] = (r < 8 || r >= t) ? a * 0.0625f : -1e9f;
  }
  __syncthreads();
  float mx = p[0], l = 0.f, o = 0.f;
  for (int k = 1; k < 40; k++) mx = fmaxf(mx, p[k]);
  for (int k = 0; k < 40; k++) { const float e = expf(p[k] - mx); l += e; o = fmaf(e, g_b[(80 + k) * 4096 + h * DH + t], o); }
  g_b[(120 + r) * 4096 + h * DH + t] = o / l;
}
__global__ void fb_out(const __nv_bfloat16* wo, int s) {
  const int r = blockIdx.x, c = threadIdx.x;
  float a = 0.f;
  for (int k = 0; k < 4096; k++) a = fmaf(g_b[(120 + r) * 4096 + k], __bfloat162float(wo[k * DM + c]), a);
  if (r < 8) g_fmem[r * DM + c] = a; else g_stash[(s * 32 + r - 8) * DM + c] = a;
}
__global__ void fb_ffn(const __nv_bfloat16* x, const __nv_bfloat16* w1, const __nv_bfloat16* w2, const __nv_bfloat16* gw, __nv_bfloat16* out) {
  __shared__ float xs[DM], hs[DFF];
  const int r = blockIdx.x, c = threadIdx.x;
  xs[c] = __bfloat162float(x[r * DM + c]);
  __syncthreads();
  float z = 0.f, b = 0.f;
  for (int d = 0; d < DM; d++) z = fmaf(xs[d], __bfloat162float(gw[d]), z);
  for (int f = c; f < DFF; f += DM) {
    float a = 0.f;
    for (int d = 0; d < DM; d++) a = fmaf(xs[d], __bfloat162float(w1[d * DFF + f]), a);
    hs[f] = fmaxf(a, 0.f);
  }
  __syncthreads();
  for (int f = 0; f < DFF; f++) b = fmaf(hs[f], __bfloat162float(w2[f * DM + c]), b);
  const float g = 1.f / (1.f + expf(-z));
  out[r * DM + c] = __float2bfloat16(g * g_stash[r * DM + c] + (1.f - g) * b);
}

typedef CUresult (*EncodeFn)(CUtensorMap*, CUtensorMapDataType, cuuint32_t, void*, const cuuint64_t*, const cuuint64_t*,
                             const cuuint32_t*, const cuuint32_t*, CUtensorMapInterleave, CUtensorMapSwizzle,
                             CUtensorMapL2promotion, CUtensorMapFloatOOBfill);

void make_map(EncodeFn fn, CUtensorMap* m, const void* p, uint64_t rows, uint64_t cols, uint32_t box_rows) {
  const cuuint64_t dims[2] = {cols, rows}, strides[1] = {cols * 2};
  const cuuint32_t box[2] = {64, box_rows}, es[2] = {1, 1};
  fn(m, CU_TENSOR_MAP_DATA_TYPE_BFLOAT16, 2, const_cast<void*>(p), dims, strides, box, es, CU_TENSOR_MAP_INTERLEAVE_NONE,
     CU_TENSOR_MAP_SWIZZLE_128B, CU_TENSOR_MAP_L2_PROMOTION_L2_256B, CU_TENSOR_MAP_FLOAT_OOB_FILL_NONE);
}

}

extern "C" void kernel_launch(void* const* d_in, const int* in_sizes, int n_in, void* d_out, int out_size) {
  (void)in_sizes; (void)n_in; (void)out_size;
  const __nv_bfloat16* x = (const __nv_bfloat16*)d_in[0];
  const __nv_bfloat16* mem0 = (const __nv_bfloat16*)d_in[1];
  const __nv_bfloat16* gate_w = (const __nv_bfloat16*)d_in[10];
  static EncodeFn fn = nullptr;
  static void* hptr = nullptr;
  static int mode = 0;
  cudaLaunchConfig_t cfg = {};
  cudaLaunchAttribute at[2];
  cfg.gridDim = dim3(112); cfg.blockDim = dim3(384); cfg.dynamicSmemBytes = T_SMEM; cfg.stream = cudaStreamPerThread;
  at[0].id = cudaLaunchAttributeClusterDimension;
  at[0].val.clusterDim.x = 16; at[0].val.clusterDim.y = 1; at[0].val.clusterDim.z = 1;
  cfg.attrs = at; cfg.numAttrs = 1;
  if (!mode) {
    cudaDriverEntryPointQueryResult qr;
    cudaGetDriverEntryPoint("cuTensorMapEncodeTiled", (void**)&fn, cudaEnableDefault, &qr);
    cudaGetSymbolAddress(&hptr, g_h);
    cudaFuncSetAttribute(rmt_kernel, cudaFuncAttributeMaxDynamicSharedMemorySize, T_SMEM);
    cudaFuncSetAttribute(rmt_kernel, cudaFuncAttributeNonPortableClusterSizeAllowed, 1);
    cudaFuncSetAttribute(ffn_kernel, cudaFuncAttributeMaxDynamicSharedMemorySize, F_SMEM);
    int ncl = 0;
    mode = fn && cudaOccupancyMaxActiveClusters(&ncl, rmt_kernel, &cfg) == cudaSuccess && ncl >= 7 ? 1 : 2;
    (void)cudaGetLastError();
  }
  if (mode == 2) {
    const __nv_bfloat16* const* in = (const __nv_bfloat16* const*)d_in;
    for (int s = 0; s < NSEG; s++) {
      fb_qkv<<<dim3(32, 3), 128, 0, cudaStreamPerThread>>>(x, mem0, in[2], in[3], in[4], s);
      fb_attn<<<dim3(NH, 40), DH, 0, cudaStreamPerThread>>>();
      fb_out<<<40, DM, 0, cudaStreamPerThread>>>(in[5], s);
    }
    fb_ffn<<<SEQ, DM, 0, cudaStreamPerThread>>>(x, in[8], in[9], gate_w, (__nv_bfloat16*)d_out);
    return;
  }
  CUtensorMap mWq, mWk, mWv, mWo, mX, mXf, mW1, mH, mW2;
  make_map(fn, &mWq, d_in[2], DM, NH * DH, 64);
  make_map(fn, &mWk, d_in[3], DM, NH * DH, 224);
  make_map(fn, &mWv, d_in[4], DM, NH * DH, 224);
  make_map(fn, &mWo, d_in[5], NH * DH, DM, 256);
  make_map(fn, &mX, x, SEQ, DM, 32);
  make_map(fn, &mXf, x, SEQ, DM, 128);
  make_map(fn, &mW1, d_in[8], DM, DFF, 64);
  make_map(fn, &mH, hptr, SEQ, DFF, 128);
  make_map(fn, &mW2, d_in[9], DFF, DM, 64);

  cudaLaunchKernelEx(&cfg, rmt_kernel, mWq, mWk, mWv, mWo, mX, x, mem0, gate_w, (__nv_bfloat16*)d_out);

  cfg.gridDim = dim3(16); cfg.dynamicSmemBytes = F_SMEM;
  at[0].val.clusterDim.x = 2;
  at[1].id = cudaLaunchAttributeProgrammaticStreamSerialization;
  at[1].val.programmaticStreamSerializationAllowed = 1;
  cfg.numAttrs = 2;
  cudaLaunchKernelEx(&cfg, ffn_kernel, mXf, mW1, mH, mW2, x, gate_w, (__nv_bfloat16*)d_out);
}
```

```cpp
#include <cuda_runtime.h>
#include <cuda_bf16.h>
#include <cuda.h>
#include <stdint.h>

namespace {

#define DEVI __device__ __forceinline__

constexpr int SEQ = 2048, DM = 448, NH = 16, DH = 256, NSEG = 64, DFF = 1792;
constexpr float SC2 = 1.4426950408889634f / 16.0f;
constexpr float MASKV = -1.6e10f;
constexpr int SPIN_LIMIT = 1 << 20;

#define D_M 460
#define D_T 700
#define D_SS 145
#define D_TL 750
#define FFN_AT 12
#define D_S 140

__device__ __align__(1024) uint8_t g_mslot[3][8192];
__device__ __align__(1024) float g_smm[NH][2][7][64];
__device__ __align__(1024) float g_xacc[8][NH][512];
__device__ __align__(1024) float g_sacc[8][NH][1408];
__device__ __align__(1024) float g_stash[SEQ * DM];
__device__ __align__(1024) float g_b[SEQ * DM];
__device__ __align__(1024) __nv_bfloat16 g_h[SEQ * DFF];
__device__ __align__(1024) uint32_t g_bflag[32][2][8];
__device__ uint32_t g_ticket[2];
__device__ int g_err;

DEVI uint32_t smem_u32(const void* p) { return (uint32_t)__cvta_generic_to_shared(p); }
DEVI uint32_t clk() { uint32_t c; asm volatile("mov.u32 %0, %%clock;" : "=r"(c) :: "memory"); return c; }
DEVI void mbar_init(uint32_t bar, uint32_t cnt) { asm volatile("mbarrier.init.shared::cta.b64 [%0], %1;" :: "r"(bar), "r"(cnt) : "memory"); }
DEVI void mbar_expect(uint32_t bar, uint32_t bytes) { asm volatile("mbarrier.arrive.expect_tx.shared::cta.b64 _, [%0], %1;" :: "r"(bar), "r"(bytes) : "memory"); }
DEVI void mbar_arrive(uint32_t bar) { asm volatile("mbarrier.arrive.shared::cta.b64 _, [%0];" :: "r"(bar) : "memory"); }
DEVI uint32_t lds32v(uint32_t a) { uint32_t v; asm volatile("ld.volatile.shared::cta.u32 %0, [%1];" : "=r"(v) : "r"(a) : "memory"); return v; }
DEVI void sts32v(uint32_t a, uint32_t v) { asm volatile("st.volatile.shared::cta.u32 [%0], %1;" :: "r"(a), "r"(v) : "memory"); }
DEVI void mbar_wait(uint32_t bar, uint32_t par, int& lim) {
  asm volatile("{\n.reg .pred p, q;\nWAIT_LOOP:\n"
               "mbarrier.try_wait.parity.shared::cta.b64 p, [%1], %2;\n"
               "sub.s32 %0, %0, 1;\nsetp.gt.and.s32 q, %0, 0, !p;\n@q bra.uni WAIT_LOOP;\n}"
               : "+r"(lim) : "r"(bar), "r"(par) : "memory");
}
DEVI void mbar_wait1(uint32_t bar, uint32_t par, int& lim) {
  asm volatile("{\n.reg .pred p, q;\nWAIT_LOOP:\n"
               "mbarrier.try_wait.parity.shared::cta.b64 p, [%1], %2;\n"
               "sub.s32 %0, %0, 1;\nsetp.gt.and.s32 q, %0, 0, !p;\n@q bra WAIT_LOOP;\n}"
               : "+r"(lim) : "r"(bar), "r"(par) : "memory");
}
DEVI bool elect() { uint32_t p; asm volatile("{\n.reg .pred p;\nelect.sync _|p, 0xffffffff;\nselp.u32 %0, 1, 0, p;\n}" : "=r"(p)); return p; }
DEVI void delay_until(uint32_t t0, uint32_t d) {
  asm volatile("{\n.reg .pred p;\n.reg .u32 t, u;\n.reg .u64 c;\nDELAY_LOOP:\nmov.u64 c, %%clock64;\nmov.b64 {t, u}, c;\nsub.u32 t, t, %0;\nsetp.lt.u32 p, t, %1;\n@p bra.uni DELAY_LOOP;\n}"
               :: "r"(t0), "r"(d) : "memory");
}
DEVI float rcp(float x) { float y; asm("rcp.approx.ftz.f32 %0, %1;" : "=f"(y) : "f"(x)); return y; }
DEVI uint32_t keep(uint32_t v, int lane) { return __shfl_sync(0xffffffffu, v, lane); }
template <class T> DEVI T* keepp(T* p, int lane) { return reinterpret_cast<T*>(__shfl_sync(0xffffffffu, reinterpret_cast<unsigned long long>(p), lane)); }
template <class T> DEVI void pin(T& v) { asm volatile("" : "+r"(v)); }
template <class T> DEVI void pinp(T*& v) { asm volatile("" : "+l"(v)); }
DEVI void bar_sync(int id, int n) { asm volatile("bar.sync %0, %1;" :: "r"(id), "r"(n) : "memory"); }
DEVI void bar_arrive(int id, int n) { asm volatile("bar.arrive %0, %1;" :: "r"(id), "r"(n) : "memory"); }
DEVI void cluster_arrive_relaxed() { asm volatile("barrier.cluster.arrive.relaxed.aligned;" ::: "memory"); }
DEVI void cluster_arrive() { asm volatile("barrier.cluster.arrive.release.aligned;" ::: "memory"); }
DEVI void cluster_wait() { asm volatile("barrier.cluster.wait.acquire.aligned;" ::: "memory"); }
DEVI uint32_t mapa(uint32_t a, uint32_t r) { uint32_t o; asm("mapa.shared::cluster.u32 %0, %1, %2;" : "=r"(o) : "r"(a), "r"(r)); return o; }
DEVI uint32_t pack2(float lo, float hi) { uint32_t r; asm("cvt.rn.bf16x2.f32 %0, %1, %2;" : "=r"(r) : "f"(hi), "f"(lo)); return r; }
DEVI float ex2(float x) { float y; asm("ex2.approx.ftz.f32 %0, %1;" : "=f"(y) : "f"(x)); return y; }
DEVI float bf_lo(uint32_t v) { return __uint_as_float(v << 16); }
DEVI float bf_hi(uint32_t v) { return __uint_as_float(v & 0xffff0000u); }
DEVI void ldsm4(uint32_t (&r)[4], uint32_t a) {
  asm volatile("ldmatrix.sync.aligned.m8n8.x4.shared.b16 {%0,%1,%2,%3}, [%4];" : "=r"(r[0]), "=r"(r[1]), "=r"(r[2]), "=r"(r[3]) : "r"(a) : "memory");
}
DEVI void stsm4t(uint32_t a, uint32_t r0, uint32_t r1, uint32_t r2, uint32_t r3) {
  asm volatile("stmatrix.sync.aligned.m8n8.x4.trans.shared.b16 [%0], {%1,%2,%3,%4};" :: "r"(a), "r"(r0), "r"(r1), "r"(r2), "r"(r3) : "memory");
}
DEVI void stsm2t(uint32_t a, uint32_t r0, uint32_t r1) {
  asm volatile("stmatrix.sync.aligned.m8n8.x2.trans.shared.b16 [%0], {%1,%2};" :: "r"(a), "r"(r0), "r"(r1) : "memory");
}
DEVI void mma16(float (&c)[4], uint32_t a0, uint32_t a1, uint32_t a2, uint32_t a3, uint32_t b0, uint32_t b1) {
  asm("mma.sync.aligned.m16n8k16.row.col.f32.bf16.bf16.f32 {%0,%1,%2,%3},{%4,%5,%6,%7},{%8,%9},{%0,%1,%2,%3};"
      : "+f"(c[0]), "+f"(c[1]), "+f"(c[2]), "+f"(c[3]) : "r"(a0), "r"(a1), "r"(a2), "r"(a3), "r"(b0), "r"(b1));
}
DEVI void mma8(float (&c)[4], uint32_t a0, uint32_t a1, uint32_t b0) {
  asm("mma.sync.aligned.m16n8k8.row.col.f32.bf16.bf16.f32 {%0,%1,%2,%3},{%4,%5},{%6},{%0,%1,%2,%3};"
      : "+f"(c[0]), "+f"(c[1]), "+f"(c[2]), "+f"(c[3]) : "r"(a0), "r"(a1), "r"(b0));
}
DEVI void mma16v(float (&c)[4], uint32_t a0, uint32_t a1, uint32_t a2, uint32_t a3, uint32_t b0, uint32_t b1) {
  asm volatile("mma.sync.aligned.m16n8k16.row.col.f32.bf16.bf16.f32 {%0,%1,%2,%3},{%4,%5,%6,%7},{%8,%9},{%0,%1,%2,%3};"
      : "+f"(c[0]), "+f"(c[1]), "+f"(c[2]), "+f"(c[3]) : "r"(a0), "r"(a1), "r"(a2), "r"(a3), "r"(b0), "r"(b1));
}
DEVI void mma8v(float (&c)[4], uint32_t a0, uint32_t a1, uint32_t b0) {
  asm volatile("mma.sync.aligned.m16n8k8.row.col.f32.bf16.bf16.f32 {%0,%1,%2,%3},{%4,%5},{%6},{%0,%1,%2,%3};"
      : "+f"(c[0]), "+f"(c[1]), "+f"(c[2]), "+f"(c[3]) : "r"(a0), "r"(a1), "r"(b0));
}
DEVI float2 mma_rows8(const uint32_t (&a0)[4], const uint32_t (&a1)[4], const uint32_t (&b0)[4], const uint32_t (&b1)[4]) {
  float e0[4] = {0.f, 0.f, 0.f, 0.f}, e1[4] = {0.f, 0.f, 0.f, 0.f}, e2[4] = {0.f, 0.f, 0.f, 0.f}, e3[4] = {0.f, 0.f, 0.f, 0.f};
  mma16v(e0, a0[0], a0[1], a0[2], a0[3], b0[0], b0[1]);
  mma16v(e1, a0[0], a0[1], a0[2], a0[3], b0[2], b0[3]);
  mma16v(e2, a1[0], a1[1], a1[2], a1[3], b1[0], b1[1]);
  mma16v(e3, a1[0], a1[1], a1[2], a1[3], b1[2], b1[3]);
  return make_float2((e0[0] + e1[2]) + (e2[0] + e3[2]), (e0[1] + e1[3]) + (e2[1] + e3[3]));
}
DEVI void wg_fence() { asm volatile("wgmma.fence.sync.aligned;" ::: "memory"); }
DEVI void wg_commit() { asm volatile("wgmma.commit_group.sync.aligned;" ::: "memory"); }
template <int N> DEVI void wg_wait() { asm volatile("wgmma.wait_group.sync.aligned %0;" :: "n"(N) : "memory"); }
template <int N> DEVI void reg_fence(float (&d)[N]) {
#pragma unroll
  for (int i = 0; i < N; i++) asm volatile("" : "+f"(d[i]) :: "memory");
}
DEVI uint64_t desc128(uint32_t addr, uint32_t lbo16) {
  return (uint64_t)((addr >> 4) & 0x3fff) | ((uint64_t)lbo16 << 16) | (64ull << 32) | (1ull << 62);
}
DEVI void tma2d(uint32_t dst, const CUtensorMap* tm, int c0, int c1, uint32_t bar) {
  asm volatile("cp.async.bulk.tensor.2d.shared::cluster.global.mbarrier::complete_tx::bytes [%0], [%1, {%2, %3}], [%4];"
               :: "r"(dst), "l"(tm), "r"(c0), "r"(c1), "r"(bar) : "memory");
}
DEVI void tma2d_mc(uint32_t dst, const CUtensorMap* tm, int c0, int c1, uint32_t bar) {
  asm volatile("cp.async.bulk.tensor.2d.shared::cluster.global.mbarrier::complete_tx::bytes.multicast::cluster [%0], [%1, {%2, %3}], [%4], %5;"
               :: "r"(dst), "l"(tm), "r"(c0), "r"(c1), "r"(bar), "h"((uint16_t)0xffff) : "memory");
}
DEVI void bulk_mc(uint32_t dst, const void* src, uint32_t bytes, uint32_t bar) {
  asm volatile("cp.async.bulk.shared::cluster.global.mbarrier::complete_tx::bytes.multicast::cluster [%0], [%1], %2, [%3], %4;"
               :: "r"(dst), "l"(src), "r"(bytes), "r"(bar), "h"((uint16_t)0xffff) : "memory");
}
DEVI void st_async4(uint32_t a, float x, float y, float z, float w, uint32_t bar) {
  asm volatile("st.async.weak.shared::cluster.mbarrier::complete_tx::bytes.v4.f32 [%0], {%1,%2,%3,%4}, [%5];"
               :: "r"(a), "f"(x), "f"(y), "f"(z), "f"(w), "r"(bar) : "memory");
}
DEVI void st_async4u(uint32_t a, uint32_t x, uint32_t y, uint32_t z, uint32_t w, uint32_t bar) {
  asm volatile("st.async.weak.shared::cluster.mbarrier::complete_tx::bytes.v4.b32 [%0], {%1,%2,%3,%4}, [%5];"
               :: "r"(a), "r"(x), "r"(y), "r"(z), "r"(w), "r"(bar) : "memory");
}
DEVI uint32_t ldg1r(const void* p) { uint32_t v; asm volatile("ld.relaxed.gpu.global.u32 %0, [%1];" : "=r"(v) : "l"(p) : "memory"); return v; }
DEVI void ldg2r(uint32_t& x, uint32_t& y, const void* p) { asm volatile("ld.relaxed.gpu.global.v2.u32 {%0,%1}, [%2];" : "=r"(x), "=r"(y) : "l"(p) : "memory"); }
DEVI void stg2r(void* p, uint32_t x, uint32_t y) { asm volatile("st.relaxed.gpu.global.v2.u32 [%0], {%1,%2};" :: "l"(p), "r"(x), "r"(y) : "memory"); }
DEVI float4 lds_f4(uint32_t a) { float4 v; asm volatile("ld.shared.v4.f32 {%0,%1,%2,%3}, [%4];" : "=f"(v.x), "=f"(v.y), "=f"(v.z), "=f"(v.w) : "r"(a) : "memory"); return v; }
DEVI uint2 lds_u2(uint32_t a) { uint2 v; asm volatile("ld.shared.v2.u32 {%0,%1}, [%2];" : "=r"(v.x), "=r"(v.y) : "r"(a) : "memory"); return v; }
DEVI uint4 lds_u4(uint32_t a) { uint4 v; asm volatile("ld.shared.v4.u32 {%0,%1,%2,%3}, [%4];" : "=r"(v.x), "=r"(v.y), "=r"(v.z), "=r"(v.w) : "r"(a) : "memory"); return v; }
DEVI void sts_f4(uint32_t a, float x, float y, float z, float w) { asm volatile("st.shared.v4.f32 [%0], {%1,%2,%3,%4};" :: "r"(a), "f"(x), "f"(y), "f"(z), "f"(w) : "memory"); }
DEVI void sts_u2(uint32_t a, uint32_t x, uint32_t y) { asm volatile("st.shared.v2.u32 [%0], {%1,%2};" :: "r"(a), "r"(x), "r"(y) : "memory"); }
DEVI void sts_u4(uint32_t a, uint32_t x, uint32_t y, uint32_t z, uint32_t w) { asm volatile("st.shared.v4.u32 [%0], {%1,%2,%3,%4};" :: "r"(a), "r"(x), "r"(y), "r"(z), "r"(w) : "memory"); }
DEVI uint32_t tagf(float v, uint32_t tag) { return (__float_as_uint(v) & ~3u) | tag; }
DEVI float qmax(float v) { v = fmaxf(v, __shfl_xor_sync(0xffffffffu, v, 1)); return fmaxf(v, __shfl_xor_sync(0xffffffffu, v, 2)); }
DEVI float qsum(float v) { v += __shfl_xor_sync(0xffffffffu, v, 1); return v + __shfl_xor_sync(0xffffffffu, v, 2); }

__device__ __forceinline__ void wgmma_n224_kk(float (&d)[112], uint64_t da, uint64_t db, int sc) {
  asm volatile("{\n.reg .pred p;\nsetp.ne.b32 p, %114, 0;\n"
    "wgmma.mma_async.sync.aligned.m64n224k16.f32.bf16.bf16 {%0,%1,%2,%3,%4,%5,%6,%7,%8,%9,%10,%11,%12,%13,%14,%15,%16,%17,%18,%19,%20,%21,%22,%23,%24,%25,%26,%27,%28,%29,%30,%31,%32,%33,%34,%35,%36,%37,%38,%39,%40,%41,%42,%43,%44,%45,%46,%47,%48,%49,%50,%51,%52,%53,%54,%55,%56,%57,%58,%59,%60,%61,%62,%63,%64,%65,%66,%67,%68,%69,%70,%71,%72,%73,%74,%75,%76,%77,%78,%79,%80,%81,%82,%83,%84,%85,%86,%87,%88,%89,%90,%91,%92,%93,%94,%95,%96,%97,%98,%99,%100,%101,%102,%103,%104,%105,%106,%107,%108,%109,%110,%111}, %112, %113, p, 1, 1, 0, 0;\n}"
    : "+f"(d[0]),"+f"(d[1]),"+f"(d[2]),"+f"(d[3]),"+f"(d[4]),"+f"(d[5]),"+f"(d[6]),"+f"(d[7]),"+f"(d[8]),"+f"(d[9]),"+f"(d[10]),"+f"(d[11]),"+f"(d[12]),"+f"(d[13]),"+f"(d[14]),"+f"(d[15]),"+f"(d[16]),"+f"(d[17]),"+f"(d[18]),"+f"(d[19]),"+f"(d[20]),"+f"(d[21]),"+f"(d[22]),"+f"(d[23]),"+f"(d[24]),"+f"(d[25]),"+f"(d[26]),"+f"(d[27]),"+f"(d[28]),"+f"(d[29]),"+f"(d[30]),"+f"(d[31]),"+f"(d[32]),"+f"(d[33]),"+f"(d[34]),"+f"(d[35]),"+f"(d[36]),"+f"(d[37]),"+f"(d[38]),"+f"(d[39]),"+f"(d[40]),"+f"(d[41]),"+f"(d[42]),"+f"(d[43]),"+f"(d[44]),"+f"(d[45]),"+f"(d[46]),"+f"(d[47]),"+f"(d[48]),"+f"(d[49]),"+f"(d[50]),"+f"(d[51]),"+f"(d[52]),"+f"(d[53]),"+f"(d[54]),"+f"(d[55]),"+f"(d[56]),"+f"(d[57]),"+f"(d[58]),"+f"(d[59]),"+f"(d[60]),"+f"(d[61]),"+f"(d[62]),"+f"(d[63]),"+f"(d[64]),"+f"(d[65]),"+f"(d[66]),"+f"(d[67]),"+f"(d[68]),"+f"(d[69]),"+f"(d[70]),"+f"(d[71]),"+f"(d[72]),"+f"(d[73]),"+f"(d[74]),"+f"(d[75]),"+f"(d[76]),"+f"(d[77]),"+f"(d[78]),"+f"(d[79]),"+f"(d[80]),"+f"(d[81]),"+f"(d[82]),"+f"(d[83]),"+f"(d[84]),"+f"(d[85]),"+f"(d[86]),"+f"(d[87]),"+f"(d[88]),"+f"(d[89]),"+f"(d[90]),"+f"(d[91]),"+f"(d[92]),"+f"(d[93]),"+f"(d[94]),"+f"(d[95]),"+f"(d[96]),"+f"(d[97]),"+f"(d[98]),"+f"(d[99]),"+f"(d[100]),"+f"(d[101]),"+f"(d[102]),"+f"(d[103]),"+f"(d[104]),"+f"(d[105]),"+f"(d[106]),"+f"(d[107]),"+f"(d[108]),"+f"(d[109]),"+f"(d[110]),"+f"(d[111])
    : "l"(da),"l"(db),"r"(sc));
}
__device__ __forceinline__ void wgmma_n224_mk(float (&d)[112], uint64_t da, uint64_t db, int sc) {
  asm volatile("{\n.reg .pred p;\nsetp.ne.b32 p, %114, 0;\n"
    "wgmma.mma_async.sync.aligned.m64n224k16.f32.bf16.bf16 {%0,%1,%2,%3,%4,%5,%6,%7,%8,%9,%10,%11,%12,%13,%14,%15,%16,%17,%18,%19,%20,%21,%22,%23,%24,%25,%26,%27,%28,%29,%30,%31,%32,%33,%34,%35,%36,%37,%38,%39,%40,%41,%42,%43,%44,%45,%46,%47,%48,%49,%50,%51,%52,%53,%54,%55,%56,%57,%58,%59,%60,%61,%62,%63,%64,%65,%66,%67,%68,%69,%70,%71,%72,%73,%74,%75,%76,%77,%78,%79,%80,%81,%82,%83,%84,%85,%86,%87,%88,%89,%90,%91,%92,%93,%94,%95,%96,%97,%98,%99,%100,%101,%102,%103,%104,%105,%106,%107,%108,%109,%110,%111}, %112, %113, p, 1, 1, 1, 0;\n}"
    : "+f"(d[0]),"+f"(d[1]),"+f"(d[2]),"+f"(d[3]),"+f"(d[4]),"+f"(d[5]),"+f"(d[6]),"+f"(d[7]),"+f"(d[8]),"+f"(d[9]),"+f"(d[10]),"+f"(d[11]),"+f"(d[12]),"+f"(d[13]),"+f"(d[14]),"+f"(d[15]),"+f"(d[16]),"+f"(d[17]),"+f"(d[18]),"+f"(d[19]),"+f"(d[20]),"+f"(d[21]),"+f"(d[22]),"+f"(d[23]),"+f"(d[24]),"+f"(d[25]),"+f"(d[26]),"+f"(d[27]),"+f"(d[28]),"+f"(d[29]),"+f"(d[30]),"+f"(d[31]),"+f"(d[32]),"+f"(d[33]),"+f"(d[34]),"+f"(d[35]),"+f"(d[36]),"+f"(d[37]),"+f"(d[38]),"+f"(d[39]),"+f"(d[40]),"+f"(d[41]),"+f"(d[42]),"+f"(d[43]),"+f"(d[44]),"+f"(d[45]),"+f"(d[46]),"+f"(d[47]),"+f"(d[48]),"+f"(d[49]),"+f"(d[50]),"+f"(d[51]),"+f"(d[52]),"+f"(d[53]),"+f"(d[54]),"+f"(d[55]),"+f"(d[56]),"+f"(d[57]),"+f"(d[58]),"+f"(d[59]),"+f"(d[60]),"+f"(d[61]),"+f"(d[62]),"+f"(d[63]),"+f"(d[64]),"+f"(d[65]),"+f"(d[66]),"+f"(d[67]),"+f"(d[68]),"+f"(d[69]),"+f"(d[70]),"+f"(d[71]),"+f"(d[72]),"+f"(d[73]),"+f"(d[74]),"+f"(d[75]),"+f"(d[76]),"+f"(d[77]),"+f"(d[78]),"+f"(d[79]),"+f"(d[80]),"+f"(d[81]),"+f"(d[82]),"+f"(d[83]),"+f"(d[84]),"+f"(d[85]),"+f"(d[86]),"+f"(d[87]),"+f"(d[88]),"+f"(d[89]),"+f"(d[90]),"+f"(d[91]),"+f"(d[92]),"+f"(d[93]),"+f"(d[94]),"+f"(d[95]),"+f"(d[96]),"+f"(d[97]),"+f"(d[98]),"+f"(d[99]),"+f"(d[100]),"+f"(d[101]),"+f"(d[102]),"+f"(d[103]),"+f"(d[104]),"+f"(d[105]),"+f"(d[106]),"+f"(d[107]),"+f"(d[108]),"+f"(d[109]),"+f"(d[110]),"+f"(d[111])
    : "l"(da),"l"(db),"r"(sc));
}
__device__ __forceinline__ void wgmma_n32_rs(float (&d)[16], const uint32_t (&a)[4], uint64_t db, int sc) {
  asm volatile("{\n.reg .pred p;\nsetp.ne.b32 p, %21, 0;\n"
    "wgmma.mma_async.sync.aligned.m64n32k16.f32.bf16.bf16 {%0,%1,%2,%3,%4,%5,%6,%7,%8,%9,%10,%11,%12,%13,%14,%15}, {%16,%17,%18,%19}, %20, p, 1, 1, 0;\n}"
    : "+f"(d[0]),"+f"(d[1]),"+f"(d[2]),"+f"(d[3]),"+f"(d[4]),"+f"(d[5]),"+f"(d[6]),"+f"(d[7]),"+f"(d[8]),"+f"(d[9]),"+f"(d[10]),"+f"(d[11]),"+f"(d[12]),"+f"(d[13]),"+f"(d[14]),"+f"(d[15])
    : "r"(a[0]),"r"(a[1]),"r"(a[2]),"r"(a[3]),"l"(db),"r"(sc));
}
__device__ __forceinline__ void wgmma_n8_rs(float (&d)[4], const uint32_t (&a)[4], uint64_t db, int sc) {
  asm volatile("{\n.reg .pred p;\nsetp.ne.b32 p, %9, 0;\n"
    "wgmma.mma_async.sync.aligned.m64n8k16.f32.bf16.bf16 {%0,%1,%2,%3}, {%4,%5,%6,%7}, %8, p, 1, 1, 0;\n}"
    : "+f"(d[0]),"+f"(d[1]),"+f"(d[2]),"+f"(d[3])
    : "r"(a[0]),"r"(a[1]),"r"(a[2]),"r"(a[3]),"l"(db),"r"(sc));
}
__device__ __forceinline__ void wgmma_n256_kn(float (&d)[128], uint64_t da, uint64_t db, int sc) {
  asm volatile("{\n.reg .pred p;\nsetp.ne.b32 p, %130, 0;\n"
    "wgmma.mma_async.sync.aligned.m64n256k16.f32.bf16.bf16 {%0,%1,%2,%3,%4,%5,%6,%7,%8,%9,%10,%11,%12,%13,%14,%15,%16,%17,%18,%19,%20,%21,%22,%23,%24,%25,%26,%27,%28,%29,%30,%31,%32,%33,%34,%35,%36,%37,%38,%39,%40,%41,%42,%43,%44,%45,%46,%47,%48,%49,%50,%51,%52,%53,%54,%55,%56,%57,%58,%59,%60,%61,%62,%63,%64,%65,%66,%67,%68,%69,%70,%71,%72,%73,%74,%75,%76,%77,%78,%79,%80,%81,%82,%83,%84,%85,%86,%87,%88,%89,%90,%91,%92,%93,%94,%95,%96,%97,%98,%99,%100,%101,%102,%103,%104,%105,%106,%107,%108,%109,%110,%111,%112,%113,%114,%115,%116,%117,%118,%119,%120,%121,%122,%123,%124,%125,%126,%127}, %128, %129, p, 1, 1, 0, 1;\n}"
    : "+f"(d[0]),"+f"(d[1]),"+f"(d[2]),"+f"(d[3]),"+f"(d[4]),"+f"(d[5]),"+f"(d[6]),"+f"(d[7]),"+f"(d[8]),"+f"(d[9]),"+f"(d[10]),"+f"(d[11]),"+f"(d[12]),"+f"(d[13]),"+f"(d[14]),"+f"(d[15]),"+f"(d[16]),"+f"(d[17]),"+f"(d[18]),"+f"(d[19]),"+f"(d[20]),"+f"(d[21]),"+f"(d[22]),"+f"(d[23]),"+f"(d[24]),"+f"(d[25]),"+f"(d[26]),"+f"(d[27]),"+f"(d[28]),"+f"(d[29]),"+f"(d[30]),"+f"(d[31]),"+f"(d[32]),"+f"(d[33]),"+f"(d[34]),"+f"(d[35]),"+f"(d[36]),"+f"(d[37]),"+f"(d[38]),"+f"(d[39]),"+f"(d[40]),"+f"(d[41]),"+f"(d[42]),"+f"(d[43]),"+f"(d[44]),"+f"(d[45]),"+f"(d[46]),"+f"(d[47]),"+f"(d[48]),"+f"(d[49]),"+f"(d[50]),"+f"(d[51]),"+f"(d[52]),"+f"(d[53]),"+f"(d[54]),"+f"(d[55]),"+f"(d[56]),"+f"(d[57]),"+f"(d[58]),"+f"(d[59]),"+f"(d[60]),"+f"(d[61]),"+f"(d[62]),"+f"(d[63]),"+f"(d[64]),"+f"(d[65]),"+f"(d[66]),"+f"(d[67]),"+f"(d[68]),"+f"(d[69]),"+f"(d[70]),"+f"(d[71]),"+f"(d[72]),"+f"(d[73]),"+f"(d[74]),"+f"(d[75]),"+f"(d[76]),"+f"(d[77]),"+f"(d[78]),"+f"(d[79]),"+f"(d[80]),"+f"(d[81]),"+f"(d[82]),"+f"(d[83]),"+f"(d[84]),"+f"(d[85]),"+f"(d[86]),"+f"(d[87]),"+f"(d[88]),"+f"(d[89]),"+f"(d[90]),"+f"(d[91]),"+f"(d[92]),"+f"(d[93]),"+f"(d[94]),"+f"(d[95]),"+f"(d[96]),"+f"(d[97]),"+f"(d[98]),"+f"(d[99]),"+f"(d[100]),"+f"(d[101]),"+f"(d[102]),"+f"(d[103]),"+f"(d[104]),"+f"(d[105]),"+f"(d[106]),"+f"(d[107]),"+f"(d[108]),"+f"(d[109]),"+f"(d[110]),"+f"(d[111]),"+f"(d[112]),"+f"(d[113]),"+f"(d[114]),"+f"(d[115]),"+f"(d[116]),"+f"(d[117]),"+f"(d[118]),"+f"(d[119]),"+f"(d[120]),"+f"(d[121]),"+f"(d[122]),"+f"(d[123]),"+f"(d[124]),"+f"(d[125]),"+f"(d[126]),"+f"(d[127])
    : "l"(da),"l"(db),"r"(sc));
}
__device__ __forceinline__ void wgmma_n192_kn(float (&d)[96], uint64_t da, uint64_t db, int sc) {
  asm volatile("{\n.reg .pred p;\nsetp.ne.b32 p, %98, 0;\n"
    "wgmma.mma_async.sync.aligned.m64n192k16.f32.bf16.bf16 {%0,%1,%2,%3,%4,%5,%6,%7,%8,%9,%10,%11,%12,%13,%14,%15,%16,%17,%18,%19,%20,%21,%22,%23,%24,%25,%26,%27,%28,%29,%30,%31,%32,%33,%34,%35,%36,%37,%38,%39,%40,%41,%42,%43,%44,%45,%46,%47,%48,%49,%50,%51,%52,%53,%54,%55,%56,%57,%58,%59,%60,%61,%62,%63,%64,%65,%66,%67,%68,%69,%70,%71,%72,%73,%74,%75,%76,%77,%78,%79,%80,%81,%82,%83,%84,%85,%86,%87,%88,%89,%90,%91,%92,%93,%94,%95}, %96, %97, p, 1, 1, 0, 1;\n}"
    : "+f"(d[0]),"+f"(d[1]),"+f"(d[2]),"+f"(d[3]),"+f"(d[4]),"+f"(d[5]),"+f"(d[6]),"+f"(d[7]),"+f"(d[8]),"+f"(d[9]),"+f"(d[10]),"+f"(d[11]),"+f"(d[12]),"+f"(d[13]),"+f"(d[14]),"+f"(d[15]),"+f"(d[16]),"+f"(d[17]),"+f"(d[18]),"+f"(d[19]),"+f"(d[20]),"+f"(d[21]),"+f"(d[22]),"+f"(d[23]),"+f"(d[24]),"+f"(d[25]),"+f"(d[26]),"+f"(d[27]),"+f"(d[28]),"+f"(d[29]),"+f"(d[30]),"+f"(d[31]),"+f"(d[32]),"+f"(d[33]),"+f"(d[34]),"+f"(d[35]),"+f"(d[36]),"+f"(d[37]),"+f"(d[38]),"+f"(d[39]),"+f"(d[40]),"+f"(d[41]),"+f"(d[42]),"+f"(d[43]),"+f"(d[44]),"+f"(d[45]),"+f"(d[46]),"+f"(d[47]),"+f"(d[48]),"+f"(d[49]),"+f"(d[50]),"+f"(d[51]),"+f"(d[52]),"+f"(d[53]),"+f"(d[54]),"+f"(d[55]),"+f"(d[56]),"+f"(d[57]),"+f"(d[58]),"+f"(d[59]),"+f"(d[60]),"+f"(d[61]),"+f"(d[62]),"+f"(d[63]),"+f"(d[64]),"+f"(d[65]),"+f"(d[66]),"+f"(d[67]),"+f"(d[68]),"+f"(d[69]),"+f"(d[70]),"+f"(d[71]),"+f"(d[72]),"+f"(d[73]),"+f"(d[74]),"+f"(d[75]),"+f"(d[76]),"+f"(d[77]),"+f"(d[78]),"+f"(d[79]),"+f"(d[80]),"+f"(d[81]),"+f"(d[82]),"+f"(d[83]),"+f"(d[84]),"+f"(d[85]),"+f"(d[86]),"+f"(d[87]),"+f"(d[88]),"+f"(d[89]),"+f"(d[90]),"+f"(d[91]),"+f"(d[92]),"+f"(d[93]),"+f"(d[94]),"+f"(d[95])
    : "l"(da),"l"(db),"r"(sc));
}

constexpr uint32_t XB = 28672;
constexpr uint32_t O_WQ = 5 * XB;
constexpr uint32_t O_WO = O_WQ + 32768;
constexpr uint32_t O_MIMG = O_WO + 32768;
constexpr uint32_t O_BAR = O_MIMG + 2 * 7168;
constexpr uint32_t O_TS = O_BAR + 384;
constexpr uint32_t T_SMEM = O_TS + 4096 + 128 + 1024;
constexpr uint32_t O_Z = 4 * XB;
constexpr uint32_t O_RS = O_Z + 2 * 5120;
constexpr uint32_t O_ORS = O_RS + 2 * 2048;
constexpr uint32_t O_P = O_ORS + 4 * 4096;
constexpr uint32_t O_MJ = O_P + 2 * 2560;
constexpr uint32_t O_ST = O_MJ + 2048;
constexpr uint32_t O_PC = O_ST + 2 * 5632;
constexpr uint32_t O_YB = O_PC + 128;
constexpr uint32_t O_GX = O_YB + 2 * 5120;
constexpr uint32_t O_GY = O_GX + 2 * 1792;
enum { B_X = 0, B_M = 4, B_RS = 6, B_O = 8, B_ZX = 10, B_P = 12, B_PF = 14, B_PE = 18, B_WQ = 22, B_WO = 23, B_T = 24, B_MJ = 26, B_OL = 28, B_G = 30, B_M2 = 31, B_YM = 33, B_N = 34 };
constexpr uint32_t O_DONE = O_BAR + 8 * B_N, O_C3 = O_DONE + 8, O_REDO = O_C3 + 4;
enum { N_ZM = 1, N_MOK = 2, N_W1 = 3, N_INIT = 4, N_ZX = 5, N_YX = 6, N_SS = 7, N_ST = 8 };

DEVI void gemm_m(const uint32_t (&w)[28][4], uint32_t img_lane, float (&c)[4]) {
  float acc[4][4];
#pragma unroll
  for (int i = 0; i < 4; i++) { acc[i][0] = acc[i][1] = acc[i][2] = acc[i][3] = 0.f; }
  uint32_t r[14][4];
#pragma unroll
  for (int u = 0; u < 14; u++) ldsm4(r[u], img_lane + u * 512);
#pragma unroll
  for (int u = 0; u < 14; u++) {
    mma16v(acc[(2 * u) & 3], w[2 * u][0], w[2 * u][1], w[2 * u][2], w[2 * u][3], r[u][0], r[u][1]);
    mma16v(acc[(2 * u + 1) & 3], w[2 * u + 1][0], w[2 * u + 1][1], w[2 * u + 1][2], w[2 * u + 1][3], r[u][2], r[u][3]);
  }
#pragma unroll
  for (int i = 0; i < 4; i++) c[i] = (acc[0][i] + acc[1][i]) + (acc[2][i] + acc[3][i]);
}

DEVI void gemm_x_issue(const uint32_t (&w)[28][4], uint32_t xbuf, float (&d)[16]) {
  const uint64_t b0 = desc128(xbuf, 1);
  wg_fence();
#pragma unroll
  for (int k = 0; k < 28; k++) wgmma_n32_rs(d, w[k], b0 + (uint64_t)((k >> 2) * 256 + (k & 3) * 2), k != 0);
  wg_commit();
}
DEVI void gemm_x(const uint32_t (&w)[28][4], uint32_t xbuf, float (&d)[16]) {
  gemm_x_issue(w, xbuf, d);
  wg_wait<0>();
  reg_fence(d);
}

template <int WHICH>
DEVI void build_weights(uint32_t (&w)[28][4], uint32_t sb, int& dead, int lane) {
  const uint32_t bar = sb + O_BAR;
  mbar_wait(bar + 8 * (WHICH ? B_WO : B_WQ), 0, dead);
#pragma unroll
  for (int half = 0; half < 2; half++) {
    float d[112];
#pragma unroll 1
    for (int fk = 0; fk < 4; fk++) {
      const int c = 2 * (4 * half + fk) + WHICH, st = c & 3;
      mbar_wait(bar + 8 * (B_PF + st), (c >> 2) & 1, dead);
      const uint64_t db = desc128(sb + (st + 1) * XB, 1);
      wg_fence();
#pragma unroll
      for (int kk = 0; kk < 4; kk++) {
        if (WHICH == 0) wgmma_n224_kk(d, desc128(sb + O_WQ + fk * 8192 + kk * 32, 1), db + kk * 2, (fk | kk) != 0);
        else            wgmma_n224_mk(d, desc128(sb + O_WO + (fk * 4 + kk) * 2048, 1), db + kk * 2, (fk | kk) != 0);
      }
      wg_commit();
      wg_wait<0>();
      if (lane == 0) mbar_arrive(bar + 8 * (B_PE + st));
    }
    reg_fence(d);
#pragma unroll
    for (int kk = 0; kk < 14; kk++) {
      w[14 * half + kk][0] = pack2(d[8 * kk + 0], d[8 * kk + 1]);
      w[14 * half + kk][1] = pack2(d[8 * kk + 2], d[8 * kk + 3]);
      w[14 * half + kk][2] = pack2(d[8 * kk + 4], d[8 * kk + 5]);
      w[14 * half + kk][3] = pack2(d[8 * kk + 6], d[8 * kk + 7]);
    }
  }
}

DEVI bool stale7(const uint32_t (&v)[14], uint32_t tag) {
  const uint32_t o = ((v[0] | v[1] | v[2]) | (v[3] | v[4] | v[5]) | (v[6] | v[7] | v[8])) | ((v[9] | v[10] | v[11]) | (v[12] | v[13]));
  const uint32_t a = ((v[0] & v[1] & v[2]) & (v[3] & v[4] & v[5]) & (v[6] & v[7] & v[8])) & ((v[9] & v[10] & v[11]) & (v[12] & v[13]));
  return (((o ^ tag) | (a ^ tag)) & 3u) != 0;
}
DEVI float2 add7(const uint32_t (&v)[14]) {
  float2 r;
  r.x = ((__uint_as_float(v[0]) + __uint_as_float(v[2])) + (__uint_as_float(v[4]) + __uint_as_float(v[6]))) +
        ((__uint_as_float(v[8]) + __uint_as_float(v[10])) + __uint_as_float(v[12]));
  r.y = ((__uint_as_float(v[1]) + __uint_as_float(v[3])) + (__uint_as_float(v[5]) + __uint_as_float(v[7]))) +
        ((__uint_as_float(v[9]) + __uint_as_float(v[11])) + __uint_as_float(v[13]));
  return r;
}

__global__ void __launch_bounds__(384, 1)
rmt_kernel(const __grid_constant__ CUtensorMap tmWq, const __grid_constant__ CUtensorMap tmWk,
           const __grid_constant__ CUtensorMap tmWv, const __grid_constant__ CUtensorMap tmWo,
           const __grid_constant__ CUtensorMap tmX, const __nv_bfloat16* __restrict__ x,
           const __nv_bfloat16* __restrict__ mem0, const __nv_bfloat16* __restrict__ gate_w, __nv_bfloat16* __restrict__ out) {
  extern __shared__ uint8_t smem_raw[];
  const uint32_t sb = (smem_u32(smem_raw) + 1023) & ~1023u;
  const uint32_t bar = sb + O_BAR;
  int lim = SPIN_LIMIT;
  int tid;
  uint32_t h, j;
  asm volatile("mov.u32 %0, %%tid.x;" : "=r"(tid));
  asm volatile("mov.u32 %0, %%cluster_ctarank;" : "=r"(h));
  asm volatile("mov.u32 %0, %%clusterid.x;" : "=r"(j));
  tid = __shfl_sync(0xffffffffu, tid, tid & 31);
  const int lane = tid & 31, warp = __shfl_sync(0xffffffffu, tid >> 5, 0);

  if (warp == 8) {
    if (elect()) {
#pragma unroll
      for (int i = 0; i < 4; i++) mbar_init(bar + 8 * (B_PF + i), 1);
      mbar_init(bar + 8 * B_WQ, 1);
      mbar_init(bar + 8 * B_WO, 1);
      asm volatile("fence.mbarrier_init.release.cluster;" ::: "memory");
      mbar_expect(bar + 8 * B_PF, XB);
      tma2d(sb + XB, &tmWk, h * DH, 0, bar + 8 * B_PF);
      mbar_expect(bar + 8 * B_WQ, 32768);
#pragma unroll
      for (int k = 0; k < 4; k++) tma2d(sb + O_WQ + k * 8192, &tmWq, h * DH + k * 64, j * 64, bar + 8 * B_WQ);
      mbar_expect(bar + 8 * B_WO, 32768);
      tma2d(sb + O_WO, &tmWo, j * 64, h * DH, bar + 8 * B_WO);
#pragma unroll
      for (int c = 1; c < 4; c++) {
        mbar_expect(bar + 8 * (B_PF + c), XB);
        tma2d(sb + (c + 1) * XB, (c & 1) ? &tmWv : &tmWk, h * DH + (c >> 1) * 64, 0, bar + 8 * (B_PF + c));
      }
    }
  } else if (warp == 9) {
    if (elect()) {
#pragma unroll
      for (int i = 0; i < B_N; i++)
        if (i < B_PF || (i >= B_PE && i < B_WQ) || i >= B_T) mbar_init(bar + 8 * i, i == B_M2 + 1 ? 16 : i >= B_MJ ? 1 : i >= B_T ? 3 : i >= B_PE ? 4 : i >= B_P ? 2 : i >= B_ZX ? 4 : 1);
      sts32v(sb + O_DONE, 0);
      sts32v(sb + O_C3, 0);
      sts32v(sb + O_REDO + 4, 0);
      sts32v(sb + O_DONE + 4, 0);
      mbar_expect(bar + 8 * B_X, XB);
      mbar_expect(bar + 8 * B_OL, 4096);
      mbar_expect(bar + 8 * (B_OL + 1), 4096);
#pragma unroll
      for (int i = 0; i < 2; i++) { mbar_expect(bar + 8 * (B_RS + i), 2048); mbar_expect(bar + 8 * (B_O + i), 4096); }
      asm volatile("fence.mbarrier_init.release.cluster;" ::: "memory");
    }
  }
  if (FFN_AT == 0) asm volatile("griddepcontrol.launch_dependents;");
  __syncthreads();
  cluster_arrive_relaxed();

  if (warp < 4) {
    asm volatile("setmaxnreg.inc.sync.aligned.u32 216;");
    uint32_t w[28][4];
    build_weights<0>(w, sb, lim, lane);
    cluster_wait();
    cluster_arrive_relaxed();
    uint32_t zst = sb + O_Z + ((2 * warp + ((lane >> 3) & 1)) * 40 + 8 * (lane >> 4) + (lane & 7)) * 16;
    const int mt = warp & 1, n0 = (warp >> 1) * 3;
    const int ch = lane >> 3, chp = (ch >> 1) | ((ch & 1) << 1);
    uint32_t zld = sb + O_Z + ((warp == 2 ? chp : ch) * 40 + (lane & 7)) * 16 + (warp == 2 ? 0 : n0 * 128);
    uint32_t zx = sb + O_Z + (chp * 40 + 8 + 8 * warp + (lane & 7)) * 16;
    float* p_smx = &g_xacc[0][h][warp * 128 + lane * 4];
    const int xrow = 16 * mt + (lane & 15);
    uint32_t xq = sb + j * 4096 + xrow * 128 + (((lane >> 4) ^ (xrow & 7)) << 4);
    uint32_t mimg = sb + O_MIMG + lane * 16, sta = sb + O_ST + (warp == 3 ? 4096 : mt * 2048) + lane * 16;
    float* p_smm = &g_smm[h][0][j][lane * 2];
    zst = keep(zst, lane); zld = keep(zld, lane); xq = keep(xq, lane); mimg = keep(mimg, lane); sta = keep(sta, lane); zx = keep(zx, lane);
    p_smm = keepp(p_smm, lane); p_smx = keepp(p_smx, lane);
    {
      float d[16];
      mbar_wait(bar + 8 * B_X, 0, lim);
      gemm_x(w, sb, d);
      cluster_wait();
      stsm4t(zst + 8 * 16, pack2(d[0], d[1]), pack2(d[2], d[3]), pack2(d[4], d[5]), pack2(d[6], d[7]));
      stsm4t(zst + 24 * 16, pack2(d[8], d[9]), pack2(d[10], d[11]), pack2(d[12], d[13]), pack2(d[14], d[15]));
    }
    const uint32_t rda0 = keep(sb + O_REDO, lane);
    const uint32_t o_a = keep(mapa(sb + O_ORS + h * 256 + warp * 64 + (lane & 3) * 16, lane >> 2), lane);
    const uint32_t o_b = keep(mapa(bar + 8 * B_O, lane >> 2), lane);
    const uint32_t o_st = mapa(sb, 8) - mapa(sb, 0);
    uint32_t oh[8];
    auto token_pv = [&](int sp) {
      const uint32_t p16 = mimg + (O_P - O_MIMG) + (sp & 1) * 2560, p8 = p16 + 1024 - lane * 8, yb = sb + O_YB + (sp & 1) * 5120 + tid * 16;
      const uint4 y0 = lds_u4(yb), y1 = lds_u4(yb + 2048);
      const uint2 ymp = lds_u2(yb + 4096 - tid * 8);
      mbar_wait(bar + 8 * (B_P + (sp & 1)), (sp >> 1) & 1, lim);
      const uint2 m0 = lds_u2(p8), m1 = lds_u2(p8 + 1280);
      const uint4 p0 = lds_u4(p16), p1 = lds_u4(p16 + 512), p2 = lds_u4(p16 + 1280), p3 = lds_u4(p16 + 1280 + 512);
      float o0[4] = {0.f, 0.f, 0.f, 0.f}, o1[4] = {0.f, 0.f, 0.f, 0.f}, o2[4] = {0.f, 0.f, 0.f, 0.f}, o3[4] = {0.f, 0.f, 0.f, 0.f};
      mma8(o0, m0.x, m0.y, ymp.x);
      mma8(o1, m0.x, m0.y, ymp.y);
      mma8(o2, m1.x, m1.y, ymp.x);
      mma8(o3, m1.x, m1.y, ymp.y);
      mma16(o0, p0.x, p0.y, p0.z, p0.w, y0.x, y0.y);
      mma16(o1, p0.x, p0.y, p0.z, p0.w, y0.z, y0.w);
      mma16(o2, p2.x, p2.y, p2.z, p2.w, y0.x, y0.y);
      mma16(o3, p2.x, p2.y, p2.z, p2.w, y0.z, y0.w);
      mma16(o0, p1.x, p1.y, p1.z, p1.w, y1.x, y1.y);
      mma16(o1, p1.x, p1.y, p1.z, p1.w, y1.z, y1.w);
      mma16(o2, p3.x, p3.y, p3.z, p3.w, y1.x, y1.y);
      mma16(o3, p3.x, p3.y, p3.z, p3.w, y1.z, y1.w);
      oh[0] = pack2(o0[0], o0[1]); oh[1] = pack2(o1[0], o1[1]); oh[2] = pack2(o0[2], o0[3]); oh[3] = pack2(o1[2], o1[3]);
      oh[4] = pack2(o2[0], o2[1]); oh[5] = pack2(o3[0], o3[1]); oh[6] = pack2(o2[2], o2[3]); oh[7] = pack2(o3[2], o3[3]);
    };
    auto token_send = [&](int sp) {
      const bool last = sp >= NSEG - 2;
      const uint32_t oa = o_a + ((last ? 2 : 0) + (sp & 1)) * 4096, ob = o_b + ((last ? B_OL - B_O : 0) + (sp & 1)) * 8;
      st_async4u(oa, oh[0], oh[1], oh[2], oh[3], ob);
      st_async4u(oa + o_st, oh[4], oh[5], oh[6], oh[7], ob + o_st);
    };
#pragma unroll 1
    for (int s = 0; s < NSEG; s++) {
      const bool rec = s < NSEG - 1;
      uint32_t img = mimg + (s & 1) * 7168, zs = zst + (s & 1) * 5120, zl = zld + (s & 1) * 5120;
      uint32_t tag = ((s >> 1) + 1) & 3;
      float* smm = p_smm + (s & 1) * 448;
      pin(img); pin(zs); pin(zl); pin(tag); pinp(smm);
      uint32_t a[4][4];
      if (rec) {
        uint32_t zb0[4], zb1[4];
        bar_sync(N_W1, 128);
        ldsm4(zb0, zx + (s & 1) * 5120);
        ldsm4(zb1, zx + (s & 1) * 5120 + 4 * 640);
        const uint32_t mj = s ? mimg + (O_MJ - O_MIMG) + (s & 1) * 1024 : img + j * 1024;
        if (s) mbar_wait(bar + 8 * (B_MJ + (s & 1)), ((s - 1) >> 1) & 1, lim);
        ldsm4(a[0], mj);
        ldsm4(a[1], mj + 512);
        const float2 e = mma_rows8(a[0], a[1], zb0, zb1);
        asm volatile("red.relaxed.gpu.global.add.v4.f32 [%0], {%1,%2,%3,%4};" :: "l"(p_smx + (s & 7) * (NH * 512)), "f"(e.x), "f"(e.y), "f"((float)(s + 1)), "f"(0.f) : "memory");
      }
      if (s) mbar_wait(bar + 8 * (B_M + (s & 1)), ((s - 1) >> 1) & 1, lim);
      float c[4];
      uint32_t b0[4], b1[4], rda = rda0;
      while (true) {
        gemm_m(w, img, c);
        stsm2t(zs, pack2(c[0], c[1]), pack2(c[2], c[3]));
        bar_sync(N_ZM, 160);
        if (warp == 2) { ldsm4(b0, zl); ldsm4(b1, zl + 4 * 640); }
        const uint32_t redo = lds32v(rda);
        rda += 4;
        if (warp == 2) {
          const float2 e = mma_rows8(a[0], a[1], b0, b1);
          if (rec && !redo) stg2r(smm, tagf(e.x, tag), tagf(e.y, tag));
          if (lane == 0 && !redo && rec) mbar_arrive(bar + 8 * B_YM);
        }
        if (__builtin_expect(!__any_sync(0xffffffffu, redo), 1)) break;
        bar_sync(N_MOK, 128);
      }
      bar_sync(N_SS, 128);
      if (s >= 2 && rec) token_send(s - 2);
      if (warp != 2) {
        const uint32_t st = sta + (s & 1) * 5632, aq = xq + (s & 3) * XB;
        uint32_t b2[4], b3[4], b4[4], b5[4];
        ldsm4(a[0], aq); ldsm4(b0, zl); ldsm4(b2, zl + 128); ldsm4(b4, zl + 256); ldsm4(a[1], aq ^ 32);
        ldsm4(a[2], aq ^ 64); ldsm4(b1, zl + 2560); ldsm4(b3, zl + 2560 + 128); ldsm4(b5, zl + 2560 + 256); ldsm4(a[3], aq ^ 96);
        float e0[4] = {0.f, 0.f, 0.f, 0.f}, e1[4] = {0.f, 0.f, 0.f, 0.f}, e2[4] = {0.f, 0.f, 0.f, 0.f};
        mma16(e0, a[0][0], a[0][1], a[0][2], a[0][3], b0[0], b0[1]);
        mma16(e1, a[0][0], a[0][1], a[0][2], a[0][3], b2[0], b2[1]);
        mma16(e2, a[0][0], a[0][1], a[0][2], a[0][3], b4[0], b4[1]);
        mma16(e0, a[1][0], a[1][1], a[1][2], a[1][3], b0[2], b0[3]);
        mma16(e1, a[1][0], a[1][1], a[1][2], a[1][3], b2[2], b2[3]);
        mma16(e2, a[1][0], a[1][1], a[1][2], a[1][3], b4[2], b4[3]);
        mma16(e0, a[2][0], a[2][1], a[2][2], a[2][3], b1[0], b1[1]);
        mma16(e1, a[2][0], a[2][1], a[2][2], a[2][3], b3[0], b3[1]);
        mma16(e2, a[2][0], a[2][1], a[2][2], a[2][3], b5[0], b5[1]);
        mma16(e0, a[3][0], a[3][1], a[3][2], a[3][3], b1[2], b1[3]);
        mma16(e1, a[3][0], a[3][1], a[3][2], a[3][3], b3[2], b3[3]);
        mma16(e2, a[3][0], a[3][1], a[3][2], a[3][3], b5[2], b5[3]);
        sts_f4(st, e0[0], e0[1], e0[2], 1.f);
        sts_f4(st + 512, e0[3], e1[0], e1[1], 1.f);
        sts_f4(st + 1024, e1[2], e1[3], n0 ? 0.f : e2[0], 1.f);
        if (n0 == 0) sts_f4(st + 1536, e2[1], e2[2], e2[3], 1.f);
        asm volatile("fence.proxy.async.shared::cta;" ::: "memory");
        __syncwarp();
        if (lane == 0) mbar_arrive(bar + 8 * (B_T + (s & 1)));
      }
      if (!rec) {
        if (tid == 32) mbar_arrive(bar + 8 * B_YM);
        token_send(s - 2);
      }
      if (s) token_pv(s - 1);
      if (rec) bar_arrive(N_YX, 256);
      if (rec) {
        float d[16];
        mbar_wait(bar + 8 * (B_X + ((s + 1) & 3)), ((s + 1) >> 2) & 1, lim);
        bar_sync(N_ZX, 256);
        gemm_x_issue(w, sb + ((s + 1) & 3) * XB, d);
        wg_wait<0>();
        reg_fence(d);
        const uint32_t zn = zst + ((s + 1) & 1) * 5120;
        stsm4t(zn + 8 * 16, pack2(d[0], d[1]), pack2(d[2], d[3]), pack2(d[4], d[5]), pack2(d[6], d[7]));
        stsm4t(zn + 24 * 16, pack2(d[8], d[9]), pack2(d[10], d[11]), pack2(d[12], d[13]), pack2(d[14], d[15]));
      }
    }
    token_send(NSEG - 2);
    bar_sync(N_ST, 256);
    token_pv(NSEG - 1);
    token_send(NSEG - 1);
    if (lim <= 0) g_err = 1;
    __syncwarp();
    cluster_arrive_relaxed();
    cluster_wait();
  } else if (warp < 8) {
    asm volatile("setmaxnreg.inc.sync.aligned.u32 216;");
    const int wq = warp - 4;
    uint32_t w[28][4];
    build_weights<1>(w, sb, lim, lane);
    cluster_wait();
    cluster_arrive_relaxed();
    uint32_t yx[8], ym[2];
    {
      float d[16];
      mbar_wait(bar + 8 * B_X, 0, lim);
      gemm_x(w, sb, d);
#pragma unroll
      for (int i = 0; i < 8; i++) yx[i] = pack2(d[2 * i], d[2 * i + 1]);
      cluster_wait();
    }
    const int ri = lane >> 2, q = lane & 3;
    uint32_t rs_a = mapa(sb + O_RS + h * 128 + ((ri & 1) * 4 + q) * 16, 4 * wq + (ri >> 1));
    uint32_t rs_b = mapa(bar + 8 * B_RS, 4 * wq + (ri >> 1));
    uint32_t mimg = sb + O_MIMG + lane * 16, l8 = sb + lane * 8;
    for (int k = wq; k < 22; k += 4) sts_u2(sb + O_GX + k * 256 + lane * 8, 0, 0);
    asm volatile("fence.proxy.async.shared::cta;" ::: "memory");
    bar_sync(N_INIT, 160);
    const uint32_t yb = sb + O_YB + (tid & 127) * 16;
    sts_u4(yb, yx[0], yx[4], yx[1], yx[5]);
    sts_u4(yb + 2048, yx[2], yx[6], yx[3], yx[7]);
    rs_a = keep(rs_a, lane); rs_b = keep(rs_b, lane); mimg = keep(mimg, lane); l8 = keep(l8, lane);

#pragma unroll 1
    for (int s = 0; s < NSEG; s++) {
      const bool rec = s < NSEG - 1;
      uint32_t img = mimg + (s & 1) * 7168, tag = ((s >> 1) + 1) & 3;
      uint32_t ra = rs_a + (s & 1) * 2048, rb = rs_b + (s & 1) * 8;
      pin(img); pin(tag); pin(ra); pin(rb);
      mbar_wait(bar + 8 * B_YM, s & 1, lim);
      float c[4];
      {
        const uint64_t dm = (uint64_t)(((sb + O_MIMG + (s & 1) * 7168) >> 4) & 0x3fff) | (8ull << 16) | (8ull << 32);
        wg_fence();
#pragma unroll
        for (int k = 0; k < 28; k++) wgmma_n8_rs(c, w[k], dm + k * 16, k != 0);
        wg_commit();
      }
      float v[4][4], mxl = 0.f;
      if (rec) {
        const float full = 7.f * (s + 1);
        do {
#pragma unroll
          for (int n = 0; n < 4; n++)
            asm volatile("ld.volatile.shared.v4.f32 {%0,%1,%2,%3}, [%4];" : "=f"(v[n][0]), "=f"(v[n][1]), "=f"(v[n][2]), "=f"(v[n][3]) : "r"(mimg + (O_GY - O_MIMG) + n * 512) : "memory");
        } while (__any_sync(0xffffffffu, (v[0][2] + v[0][3] != full) | (v[1][2] + v[1][3] != full) | (v[2][2] + v[2][3] != full) | (v[3][2] + v[3][3] != full)) && --lim > 0);
        sts32v(sb + O_DONE + 4, s + 1);
        mxl = fmaxf(fmaxf(fmaxf(v[0][0], v[0][1]), fmaxf(v[1][0], v[1][1])), fmaxf(fmaxf(v[2][0], v[2][1]), fmaxf(v[3][0], v[3][1])));
      }
      wg_wait<0>();
      reg_fence(c);
      ym[0] = pack2(c[0], c[1]);
      ym[1] = pack2(c[2], c[3]);
      if (rec) {
        uint32_t vm[14];
        const uint32_t gx = l8 + O_GX + (s & 1) * 1792;
        do {
#pragma unroll
          for (int k = 0; k < 7; k++) asm volatile("ld.volatile.shared.v2.u32 {%0,%1}, [%2];" : "=r"(vm[2 * k]), "=r"(vm[2 * k + 1]) : "r"(gx + k * 256) : "memory");
        } while (__any_sync(0xffffffffu, stale7(vm, tag)) && --lim > 0);
        sts32v(sb + O_DONE, s + 1);
        const float2 sm = add7(vm);
        const float mx = qmax(fmaxf(mxl, fmaxf(sm.x, sm.y)));
        const float nb = -mx * SC2;
        uint32_t pa[4];
        float l = 0.f;
#pragma unroll
        for (int n = 0; n < 4; n++) {
          const float p0 = ex2(fmaf(v[n][0], SC2, nb)), p1 = ex2(fmaf(v[n][1], SC2, nb));
          l += p0 + p1;
          pa[n] = pack2(p0, p1);
        }
        float o0[4] = {0.f, 0.f, 0.f, 0.f}, o1[4] = {0.f, 0.f, 0.f, 0.f}, u0[4] = {0.f, 0.f, 0.f, 0.f}, u1[4] = {0.f, 0.f, 0.f, 0.f};
        mma16v(o0, pa[0], pa[1], pa[2], pa[3], yx[0], yx[4]);
        mma16v(o1, pa[0], pa[1], pa[2], pa[3], yx[1], yx[5]);
        mma16v(u0, pa[0], pa[1], pa[2], pa[3], yx[2], yx[6]);
        mma16v(u1, pa[0], pa[1], pa[2], pa[3], yx[3], yx[7]);
        const float p0 = ex2(fmaf(sm.x, SC2, nb)), p1 = ex2(fmaf(sm.y, SC2, nb));
        const uint32_t pp = pack2(p0, p1);
        mma8v(o0, pp, pp, ym[0]);
        mma8v(o1, pp, pp, ym[1]);
        const float inv = rcp(qsum(l + (p0 + p1)));
        st_async4(ra, (o0[0] + u0[2]) * inv, (o0[1] + u0[3]) * inv, (o1[0] + u1[2]) * inv, (o1[1] + u1[3]) * inv, rb);
      }
      sts_u2(yb + 4096 - (tid & 127) * 8 + (s & 1) * 5120, ym[0], ym[1]);
      if (!rec) bar_arrive(N_ST, 256);
      if (rec) {
        bar_arrive(N_ZX, 256);
      }
      if (rec) {
        float d[16];
        mbar_wait(bar + 8 * (B_X + ((s + 1) & 3)), ((s + 1) >> 2) & 1, lim);
        gemm_x(w, sb + ((s + 1) & 3) * XB, d);
#pragma unroll
        for (int i = 0; i < 8; i++) yx[i] = pack2(d[2 * i], d[2 * i + 1]);
        bar_sync(N_YX, 256);
        sts_u4(yb + ((s + 1) & 1) * 5120, yx[0], yx[4], yx[1], yx[5]);
        sts_u4(yb + ((s + 1) & 1) * 5120 + 2048, yx[2], yx[6], yx[3], yx[7]);
      }
    }
    if (lim <= 0) g_err = 1;
    __syncwarp();
    cluster_arrive_relaxed();
    cluster_wait();
  } else {
    asm volatile("setmaxnreg.dec.sync.aligned.u32 72;");
    if (warp == 8) {
      const int u = (lane & 15) >> 1, nt = lane & 1;
      uint8_t* gm0 = &g_mslot[0][(8 * j + 2 * (h >> 2) + nt) * 128 + (2 * (h & 3) + (u >> 2)) * 16 + (u & 3) * 4];
#pragma unroll
      for (int k = 0; k < 3; k++) asm volatile("st.relaxed.gpu.global.u32 [%0], 0xffffffff;" :: "l"(gm0 + k * 8192) : "memory");
      cluster_wait();
      if (lane == 0) {
        int lim1 = SPIN_LIMIT;
        if (h < 7) tma2d_mc(sb + h * 4096, &tmX, h * 64, 0, bar + 8 * B_X);
#pragma unroll 1
        for (int c = 4; c < 16; c++) {
          const int st = c & 3;
          mbar_wait1(bar + 8 * (B_PE + st), ((c >> 2) - 1) & 1, lim1);
          if (c == FFN_AT) asm volatile("griddepcontrol.launch_dependents;");
          mbar_expect(bar + 8 * (B_PF + st), XB);
          tma2d(sb + (st + 1) * XB, (c & 1) ? &tmWv : &tmWk, h * DH + ((c >> 1) & 3) * 64, (c >> 3) * 224, bar + 8 * (B_PF + st));
        }
      }
      __syncwarp();
      cluster_arrive();
      cluster_wait();
      if (lane == 0) {
        for (int k = 1; k < 3; k++) {
          mbar_expect(bar + 8 * (B_X + k), XB);
          if (h < 7) tma2d_mc(sb + k * XB + h * 4096, &tmX, h * 64, k * 32, bar + 8 * (B_X + k));
        }
      }
      uint32_t chk = sb + O_MIMG + lane * 32 + (lane >> 2) * 4, rs0 = sb + O_RS + (lane >> 4) * 1024 + (lane & 15) * 8;
      const uint8_t* gnear = &g_mslot[0][0];
      const uint32_t pc_st = keep(sb + O_PC + (nt * 2 + (u >> 2)) * 16 + (u & 3) * 4, lane);
      const uint32_t mj_a = keep(mapa(sb + O_MJ + (2 * (h >> 2) + ((lane >> 1) & 1)) * 128 + (2 * (h & 3) + (lane & 1)) * 16, lane >> 2), lane);
      const uint32_t mj_b = keep(mapa(bar + 8 * B_MJ, lane >> 2), lane), mj_st = mapa(sb, 8) - mapa(sb, 0);
      chk = keep(chk, lane); rs0 = keep(rs0, lane); gm0 = keepp(gm0, lane);
      const uint32_t m2r = mapa(bar + 8 * (B_M2 + 1), lane & 15);
      auto cl_sync_arrive = [&](uint32_t a) { if (lane < 16) asm volatile("mbarrier.arrive.relaxed.cluster.shared::cluster.b64 _, [%0];" :: "r"(a) : "memory"); __syncwarp(); };
      const uint8_t* p_gsrc = reinterpret_cast<const uint8_t*>(&g_smm[h][0][0][0]);
      bar_sync(N_INIT, 160);
      uint32_t m2p = 0;
      int s3 = 0;
#pragma unroll 1
      for (int s = 0; s < NSEG; s++) {
        uint32_t ck = chk + (s & 1) * 7168;
        pin(ck);
        bool redo = false;
        if (s) {
          mbar_wait(bar + 8 * (B_M + (s & 1)), ((s - 1) >> 1) & 1, lim);
          while (true) {
            uint32_t v[7];
#pragma unroll
            for (int k = 0; k < 7; k++) v[k] = lds32v(ck + k * 1024);
            const uint32_t mx = __vimax3_u32(__vimax3_u32(v[0], v[1], v[2]), __vimax3_u32(v[3], v[4], v[5]), v[6]);
            if (__builtin_expect(!__any_sync(0xffffffffu, mx == 0xffffffffu) || lim <= 0, 1)) break;
            redo = true;
            cl_sync_arrive(m2r);
            if (elect()) mbar_expect(bar + 8 * B_M2, 7168);
            mbar_wait(bar + 8 * (B_M2 + 1), m2p, lim);
            if (elect()) bulk_mc(sb + O_MIMG + (s & 1) * 7168 + h * 448, gnear + s3 * 8192 + h * 448, 448, bar + 8 * B_M2);
            mbar_wait(bar + 8 * B_M2, m2p, lim);
            m2p ^= 1;
          }
        }
        sts32v(sb + O_REDO, redo);
        bar_sync(N_ZM, 160);
        if (redo) bar_sync(N_ZM, 160);
        if (s == NSEG - 1) break;
        {
          const uint32_t tz = clk();
          const uint8_t* gsrc = p_gsrc + (s & 1) * 1792;
          asm volatile("{\n.reg .pred e, p, q, x;\n.reg .u32 t, u, f0, f1, td, n;\n.reg .u64 c;\n"
                       "elect.sync _|e, 0xffffffff;\nmov.u32 td, %9;\n"
                       "@e mbarrier.expect_tx.relaxed.cta.shared::cta.b64 [%3], 2048;\n"
                       "@e cp.async.bulk.shared::cluster.global.mbarrier::complete_tx::bytes [%6], [%7], 2048, [%3];\n"
                       "setp.eq.u32 x, td, td;\n"
                       "REFRESH:\nmov.u64 c, %%clock64;\nmov.b64 {t, u}, c;\nsub.u32 t, t, %1;\nsetp.lt.u32 p, t, td;\n@p bra.uni REFRESH;\n"
                       "selp.u32 n, 3840, 1792, x;\nand.pred q, e, x;\n"
                       "@e mbarrier.expect_tx.relaxed.cta.shared::cta.b64 [%3], n;\n"
                       "@e cp.async.bulk.shared::cluster.global.mbarrier::complete_tx::bytes [%4], [%5], 1792, [%3];\n"
                       "@q cp.async.bulk.shared::cluster.global.mbarrier::complete_tx::bytes [%6], [%7], 2048, [%3];\n"
                       "ld.volatile.shared.v2.u32 {f0, f1}, [%8];\nadd.u32 td, td, %10;\nsub.s32 %0, %0, 1;\n"
                       "setp.le.s32 x, f1, %2;\nsetp.le.s32 p, f0, %2;\nsetp.gt.and.s32 p, %0, 0, p;\n@p bra.uni REFRESH;\n}"
                       : "+r"(lim)
                       : "r"(tz), "r"(s), "r"(bar + 8 * B_G), "r"(sb + O_GX + (s & 1) * 1792), "l"(gsrc), "r"(sb + O_GY), "l"(&g_xacc[s & 7][h][0]),
                         "r"(sb + O_DONE), "n"(D_S), "n"(D_SS)
                       : "memory");
        }
        while (__any_sync(0xffffffffu, (int)lds32v(sb + O_C3) < s - 2) && --lim > 0) {}
        const int s3n = s3 == 2 ? 0 : s3 + 1;
        uint32_t rb = rs0 + (s & 1) * 2048;
        uint8_t* gm = gm0 + s3n * 8192;
        const uint32_t mdst = sb + O_MIMG + ((s + 1) & 1) * 7168 + h * 448, mb = bar + 8 * (B_M + ((s + 1) & 1));
        const uint8_t* msrc = gnear + s3n * 8192 + h * 448;
        s3 = s3n;
        pin(rb); pinp(gm);
        mbar_wait(bar + 8 * (B_RS + (s & 1)), (s >> 1) & 1, lim);
        uint2 v[8];
#pragma unroll
        for (int k = 0; k < 8; k++) v[k] = lds_u2(rb + k * 128);
        float s0 = ((__uint_as_float(v[0].x) + __uint_as_float(v[1].x)) + (__uint_as_float(v[2].x) + __uint_as_float(v[3].x))) +
                   ((__uint_as_float(v[4].x) + __uint_as_float(v[5].x)) + (__uint_as_float(v[6].x) + __uint_as_float(v[7].x)));
        float s1 = ((__uint_as_float(v[0].y) + __uint_as_float(v[1].y)) + (__uint_as_float(v[2].y) + __uint_as_float(v[3].y))) +
                   ((__uint_as_float(v[4].y) + __uint_as_float(v[5].y)) + (__uint_as_float(v[6].y) + __uint_as_float(v[7].y)));
        s0 += __shfl_xor_sync(0xffffffffu, s0, 16);
        s1 += __shfl_xor_sync(0xffffffffu, s1, 16);
        const uint32_t mw = pack2(s0, s1);
        if (lane < 16) asm volatile("st.relaxed.gpu.global.u32 [%0], %1;" :: "l"(gm), "r"(mw) : "memory");
        const uint32_t tm = clk();
        sts32v(pc_st, mw);
        __syncwarp();
        const float4 pc = lds_f4(sb + O_PC + (lane & 3) * 16);
        if (s < NSEG - 2) {
          const uint32_t o = ((s + 1) & 1) * 1024, ob = ((s + 1) & 1) * 8;
          st_async4(mj_a + o, pc.x, pc.y, pc.z, pc.w, mj_b + ob);
          st_async4(mj_a + o + mj_st, pc.x, pc.y, pc.z, pc.w, mj_b + ob + mj_st);
        }
        const bool el = elect();
        if (el) mbar_expect(bar + 8 * (B_RS + (s & 1)), 2048);
        delay_until(tm, D_M);
        if (el) bulk_mc(mdst, msrc, 448, mb);
      }
      if (elect()) mbar_arrive(bar + 8 * B_G);
      mbar_wait(bar + 8 * B_G, 0, lim);
    } else if (warp < 11) {
      const int mt = warp - 9, q = lane & 3;
#pragma unroll
      for (int t = mt * 32 + lane; t < 448; t += 64) {
        const uint4 v = *reinterpret_cast<const uint4*>(mem0 + (t & 7) * DM + (t >> 3) * 8);
        sts_u4(sb + O_MIMG + t * 16, v.x, v.y, v.z, v.w);
      }
      asm volatile("fence.proxy.async.shared::cta;" ::: "memory");
      __syncwarp();
      cluster_wait();
      cluster_arrive();
      cluster_wait();
      uint8_t* gm0 = &g_mslot[0][(8 * j + 2 * (h >> 2) + (lane & 1)) * 128 + (2 * (h & 3) + ((lane >> 3) & 1)) * 16 + ((lane >> 1) & 3) * 4];
      int s3p = 2;
#pragma unroll 1
      for (int s = 0; s < NSEG; s++) {
        mbar_wait(bar + 8 * (B_T + (s & 1)), (s >> 1) & 1, lim);
        if (mt == 1 && s < NSEG - 1) {
          if (elect()) {
            mbar_expect(bar + 8 * (B_M + ((s + 1) & 1)), 7168);
            if (s < NSEG - 2) mbar_expect(bar + 8 * (B_MJ + ((s + 1) & 1)), 1024);
            if (s >= 1 && s + 2 < NSEG) {
              mbar_expect(bar + 8 * (B_X + ((s + 2) & 3)), XB);
              if (h < 7) tma2d_mc(sb + ((s + 2) & 3) * XB + h * 4096, &tmX, h * 64, (s + 2) * 32, bar + 8 * (B_X + ((s + 2) & 3)));
            }
          }
          asm volatile("st.relaxed.gpu.global.u32 [%0], 0xffffffff;" :: "l"(gm0 + s3p * 8192) : "memory");
          s3p = s3p == 2 ? 0 : s3p + 1;
        }
        const uint32_t t0 = clk();
        if (mt == 0 && elect()) {
          asm volatile("cp.reduce.async.bulk.global.shared::cta.bulk_group.add.f32 [%0], [%1], 5632;" :: "l"(&g_sacc[s & 7][h][0]), "r"(sb + O_ST + (s & 1) * 5632) : "memory");
          asm volatile("cp.async.bulk.commit_group;" ::: "memory");
          asm volatile("cp.async.bulk.wait_group.read 0;" ::: "memory");
        }
        __syncwarp();
        if (s < NSEG - 1) { mbar_wait(bar + 8 * (B_RS + (s & 1)), (s >> 1) & 1, lim); delay_until(t0, D_T); }
        else delay_until(t0, D_TL);
        const float4* sp = reinterpret_cast<const float4*>(&g_sacc[s & 7][h][mt * 512 + lane * 4]);
        float u[7][4];
        bool stale;
        do {
          stale = false;
#pragma unroll
          for (int c = 0; c < 7; c++) {
            u[c][0] = u[c][1] = u[c][2] = 0.f; u[c][3] = 7.f;
            if (c < 4 || mt)
              asm volatile("ld.relaxed.gpu.global.v4.f32 {%0,%1,%2,%3}, [%4];" : "=f"(u[c][0]), "=f"(u[c][1]), "=f"(u[c][2]), "=f"(u[c][3]) : "l"(sp + c * 32) : "memory");
          }
#pragma unroll
          for (int c = 0; c < 7; c++) stale |= u[c][3] != 7.f;
        } while (__any_sync(0xffffffffu, stale) && --lim > 0);
        uint32_t pk[2][5];
        float v[2][10];
#pragma unroll
        for (int e = 0; e < 10; e++) {
          const int i = 4 * (e >> 1) + (e & 1);
          v[0][e] = u[i / 3][i % 3];
          v[1][e] = u[(i + 2) / 3][(i + 2) % 3];
        }
#pragma unroll
        for (int rg = 0; rg < 2; rg++) {
          const int row = 16 * mt + 8 * rg + (lane >> 2);
#pragma unroll
          for (int e = 2; e < 10; e++)
            if (8 * ((e >> 1) - 1) + 2 * q + (e & 1) > row) v[rg][e] = MASKV;
          float mx = v[rg][0];
#pragma unroll
          for (int e = 1; e < 10; e++) mx = fmaxf(mx, v[rg][e]);
          mx = qmax(mx);
          const float nb = -mx * SC2;
          float l = 0.f;
#pragma unroll
          for (int e = 0; e < 10; e++) { v[rg][e] = ex2(fmaf(v[rg][e], SC2, nb)); l += v[rg][e]; }
          const float inv = rcp(qsum(l));
#pragma unroll
          for (int n = 0; n < 5; n++) pk[rg][n] = pack2(v[rg][2 * n] * inv, v[rg][2 * n + 1] * inv);
        }
        const uint32_t pb = sb + O_P + (s & 1) * 2560 + mt * 1280;
        sts_u4(pb + lane * 16, pk[0][1], pk[1][1], pk[0][3], pk[1][3]);
        sts_u4(pb + 512 + lane * 16, pk[0][2], pk[1][2], pk[0][4], pk[1][4]);
        sts_u2(pb + 1024 + lane * 8, pk[0][0], pk[1][0]);
        __syncwarp();
        if (lane == 0) mbar_arrive(bar + 8 * (B_P + (s & 1)));
        if (j + 7 * mt < 11) asm volatile("st.relaxed.gpu.global.v4.f32 [%0], {%1,%1,%1,%1};" :: "l"(&g_sacc[(s + 4) & 7][h][(j + 7 * mt) * 128 + lane * 4]), "f"(0.f) : "memory");
      }
    } else {
      const int t1 = lane >> 4, l16 = lane & 15;
      uint2 gw[7];
#pragma unroll
      for (int k = 0; k < 7; k++) gw[k] = *reinterpret_cast<const uint2*>(gate_w + (k * 16 + l16) * 4);
      const int col = j * 64 + ((lane >> 2) & 3) * 16 + (lane & 3) * 2;
      const uint32_t epoch = ldg1r(&g_ticket[0]) / 112 + 1;
      __syncwarp();
      cluster_wait();
      cluster_arrive();
      cluster_wait();
      const int trow = 16 * (h >> 3) + (h & 7) + 8 * t1;
      const uint32_t xg = sb + trow * 128 + (((l16 >> 1) ^ (trow & 7)) << 4) + (l16 & 1) * 8;
      auto gate = [&](int sg) {
        mbar_wait(bar + 8 * (B_X + (sg & 3)), (sg >> 2) & 1, lim);
        float z = 0.f, z2 = 0.f;
#pragma unroll
        for (int k = 0; k < 7; k++) {
          const uint2 xv = lds_u2(xg + (sg & 3) * XB + k * 4096);
          z = fmaf(bf_lo(xv.x), bf_lo(gw[k].x), z); z2 = fmaf(bf_hi(xv.x), bf_hi(gw[k].x), z2);
          z = fmaf(bf_lo(xv.y), bf_lo(gw[k].y), z); z2 = fmaf(bf_hi(xv.y), bf_hi(gw[k].y), z2);
        }
        z += z2;
#pragma unroll
        for (int o = 1; o < 16; o <<= 1) z += __shfl_xor_sync(0xffffffffu, z, o);
        return rcp(1.f + ex2(-1.4426950408889634f * z));
      };
      float4 pa4 = make_float4(0.f, 0.f, 0.f, 0.f);
      bool pend = false;
      auto finish = [&](int sg) {
        if (ldg1r(&g_bflag[sg >> 1][j >> 2][0]) == epoch) {
          const int o = (sg * 32 + trow) * DM + col;
          uint32_t b0, b1, b2, b3;
          ldg2r(b0, b1, g_b + o); ldg2r(b2, b3, g_b + o + 8);
          uint32_t* op = reinterpret_cast<uint32_t*>(out + o);
          op[0] = pack2(pa4.x + __uint_as_float(b0), pa4.y + __uint_as_float(b1));
          op[4] = pack2(pa4.z + __uint_as_float(b2), pa4.w + __uint_as_float(b3));
        }
      };
      const uint32_t* fl0 = keepp(&g_bflag[0][j >> 2][0], lane);
      uint32_t fnext = 0;
      float g1 = 0.f, g2 = 0.f;
#pragma unroll 1
      for (int s = -2; s < NSEG; s++) {
        if (s >= 0) {
        const int tok = s * 32 + trow;
        const bool have_b = fnext == epoch;
        fnext = ldg1r(fl0 + (min(s + 1, NSEG - 1) >> 1) * 16);
        const float* bp = &g_b[tok * DM + col];
        uint32_t b0 = 0, b1 = 0, b2 = 0, b3 = 0;
        if (have_b) { ldg2r(b0, b1, bp); ldg2r(b2, b3, bp + 8); }
        const bool last = s >= NSEG - 2;
        mbar_wait(bar + 8 * ((last ? B_OL : B_O) + (s & 1)), last ? 0 : (s >> 1) & 1, lim);
        if (lane < 19 && j * 19 + lane < 128)
          asm volatile("st.relaxed.gpu.global.v4.f32 [%0], {%1,%1,%1,%1};" :: "l"(&g_xacc[s & 7][h][(j * 19 + lane) * 4]), "f"(0.f) : "memory");
        const float g = g1;
        const uint32_t ob = sb + O_ORS + ((last ? 2 : 0) + (s & 1)) * 4096 + t1 * 2048 + l16 * 16;
        float e[8] = {0.f, 0.f, 0.f, 0.f, 0.f, 0.f, 0.f, 0.f};
#pragma unroll 2
        for (int k = 0; k < 8; k++) {
          const uint4 c = lds_u4(ob + k * 256);
          e[0] += bf_lo(c.x); e[1] += bf_hi(c.x); e[2] += bf_lo(c.y); e[3] += bf_hi(c.y);
          e[4] += bf_lo(c.z); e[5] += bf_hi(c.z); e[6] += bf_lo(c.w); e[7] += bf_hi(c.w);
        }
        float4 a;
        a.x = g * ((t1 ? e[4] : e[0]) + __shfl_xor_sync(0xffffffffu, t1 ? e[0] : e[4], 16));
        a.y = g * ((t1 ? e[5] : e[1]) + __shfl_xor_sync(0xffffffffu, t1 ? e[1] : e[5], 16));
        a.z = g * ((t1 ? e[6] : e[2]) + __shfl_xor_sync(0xffffffffu, t1 ? e[2] : e[6], 16));
        a.w = g * ((t1 ? e[7] : e[3]) + __shfl_xor_sync(0xffffffffu, t1 ? e[3] : e[7], 16));
        __syncwarp();
        if (lane == 0 && s < NSEG - 4) mbar_expect(bar + 8 * (B_O + (s & 1)), 4096);
        float* sp = &g_stash[tok * DM + col];
        stg2r(sp, tagf(a.x, epoch & 3), tagf(a.y, epoch & 3));
        stg2r(sp + 8, tagf(a.z, epoch & 3), tagf(a.w, epoch & 3));
        if (have_b) {
          uint32_t* op = reinterpret_cast<uint32_t*>(out + tok * DM + col);
          op[0] = pack2(a.x + __uint_as_float(b0), a.y + __uint_as_float(b1));
          op[4] = pack2(a.z + __uint_as_float(b2), a.w + __uint_as_float(b3));
        }
        if (pend) { if (s >= NSEG - 2) __threadfence(); finish(s - 1); }
        pend = !have_b;
        pa4 = a;
        }
        g1 = g2;
        if (s + 2 < NSEG) g2 = gate(s + 2);
        if (lane == 0 && s >= 0) sts32v(sb + O_C3, s + 1);
      }
      if (pend) { __threadfence(); finish(NSEG - 1); }
      if (lane == 0) atomicAdd(&g_ticket[0], 1);
    }
    if (lim <= 0) g_err = 1;
    __syncwarp();
    cluster_arrive_relaxed();
    cluster_wait();
  }
}

constexpr uint32_t F_STAGE = 49152, F_BAR = 4 * F_STAGE, F_G = F_BAR + 128, F_STG = F_G + 512, F_SMEM = F_STG + 8 * 2304 + 1024;

DEVI void release_stage(uint32_t sb, int st, int lane) {
  if (lane < 2) asm volatile("mbarrier.arrive.relaxed.cluster.shared::cluster.b64 _, [%0];" :: "r"(mapa(sb + F_BAR + 32 + 8 * st, lane)) : "memory");
}
template <int N>
DEVI void ffn_tile(float (&d)[N / 2], uint32_t sb, int wg, int nk, int& it, int& dead, int lane) {
#pragma unroll 1
  for (int k = 0; k < nk; k++, it++) {
    const int st = it & 3;
    mbar_wait(sb + F_BAR + 8 * st, (it >> 2) & 1, dead);
    const uint64_t da = desc128(sb + st * F_STAGE + wg * 8192, 1), db = desc128(sb + st * F_STAGE + 16384, 512);
    wg_fence();
#pragma unroll
    for (int kk = 0; kk < 4; kk++) {
      if constexpr (N == 256) wgmma_n256_kn(d, da + kk * 2, db + kk * 128, (k | kk) != 0);
      else                    wgmma_n192_kn(d, da + kk * 2, db + kk * 128, (k | kk) != 0);
    }
    wg_commit();
    if (k) { wg_wait<1>(); release_stage(sb, (it - 1) & 3, lane); }
  }
  wg_wait<0>();
  release_stage(sb, (it - 1) & 3, lane);
  reg_fence(d);
}

template <int NJ>
DEVI void ffn_finish(float (&d)[NJ * 32], float g0, float g1, uint32_t sb, int r0, int row, int j0, uint32_t epoch,
                     __nv_bfloat16* __restrict__ out, int tid) {
  const int wg = tid >> 7, t = tid & 127, off = (r0 + row) * DM + j0 * 64 + 2 * (tid & 3);
#pragma unroll
  for (int n = 0; n < NJ * 8; n++) {
    d[4 * n] *= g0; d[4 * n + 1] *= g0; d[4 * n + 2] *= g1; d[4 * n + 3] *= g1;
    *reinterpret_cast<float2*>(g_b + off + n * 8) = make_float2(d[4 * n], d[4 * n + 1]);
    *reinterpret_cast<float2*>(g_b + off + 8 * DM + n * 8) = make_float2(d[4 * n + 2], d[4 * n + 3]);
  }
  asm volatile("fence.release.gpu;" ::: "memory");
  bar_sync(2 + wg, 128);
  if (t == 0) {
    asm volatile("st.relaxed.gpu.global.u32 [%0], %1;" :: "l"(&g_bflag[(r0 >> 6) + wg][j0 >> 2][0]), "r"(epoch) : "memory");
    __threadfence();
  }
  bar_sync(2 + wg, 128);
#pragma unroll
  for (int n0 = 0; n0 < NJ * 8; n0 += 8) {
    uint32_t a[8][4];
#pragma unroll
    for (int n = 0; n < 8; n++) { ldg2r(a[n][0], a[n][1], g_stash + off + (n0 + n) * 8); ldg2r(a[n][2], a[n][3], g_stash + off + 8 * DM + (n0 + n) * 8); }
#pragma unroll
    for (int n = 0; n < 8; n++)
#pragma unroll
      for (int half = 0; half < 2; half++)
        if (((a[n][2 * half] ^ epoch) & 3) == 0)
          *reinterpret_cast<uint32_t*>(out + off + half * 8 * DM + (n0 + n) * 8) =
              pack2(__uint_as_float(a[n][2 * half]) + d[4 * (n0 + n) + 2 * half], __uint_as_float(a[n][2 * half + 1]) + d[4 * (n0 + n) + 2 * half + 1]);
  }
}

__global__ void __launch_bounds__(384, 1)
ffn_kernel(const __grid_constant__ CUtensorMap tmX, const __grid_constant__ CUtensorMap tmW1,
           const __grid_constant__ CUtensorMap tmH, const __grid_constant__ CUtensorMap tmW2,
           const __nv_bfloat16* __restrict__ x, const __nv_bfloat16* __restrict__ gate_w, __nv_bfloat16* __restrict__ out) {
  extern __shared__ uint8_t smem_raw[];
  const uint32_t sb = (smem_u32(smem_raw) + 1023) & ~1023u;
  const uint32_t hbar = sb + F_BAR + 64;
  int dead = SPIN_LIMIT;
  const int tid = threadIdx.x, lane = tid & 31, warp = __shfl_sync(0xffffffffu, tid >> 5, 0), r0 = blockIdx.x * 128;
  if (tid == 0) {
    for (int i = 0; i < 4; i++) { mbar_init(sb + F_BAR + 8 * i, 1); mbar_init(sb + F_BAR + 32 + 8 * i, 16); }
    mbar_init(hbar, 256);
    asm volatile("fence.mbarrier_init.release.cluster;" ::: "memory");
    asm volatile("fence.proxy.async.shared::cta;" ::: "memory");
  }
  __syncthreads();
  cluster_arrive_relaxed();
  cluster_wait();
  if (warp >= 8) {
    asm volatile("setmaxnreg.dec.sync.aligned.u32 56;");
    if (tid == 256) {
      int it = 0;
#pragma unroll 1
      for (int t = 0; t < 9; t++) {
        const int nk = t < 7 ? 7 : 28, nb = t < 8 ? 4 : 3;
        if (t == 7) mbar_wait1(hbar, 0, dead);
#pragma unroll 1
        for (int k = 0; k < nk; k++, it++) {
          const int st = it & 3;
          const uint32_t fb = sb + F_BAR + 8 * st, a = sb + st * F_STAGE;
          if (it >= 4) mbar_wait1(fb + 32, ((it >> 2) - 1) & 1, dead);
          mbar_expect(fb, 16384 + nb * 8192);
          tma2d(a, t < 7 ? &tmX : &tmH, k * 64, r0, fb);
          for (int b = blockIdx.x & 1; b < nb; b += 2)
            asm volatile("cp.async.bulk.tensor.2d.shared::cluster.global.mbarrier::complete_tx::bytes.multicast::cluster [%0], [%1, {%2, %3}], [%4], %5;"
                         :: "r"(a + 16384 + b * 8192), "l"(t < 7 ? &tmW1 : &tmW2), "r"((t < 7 ? t : t - 7) * 256 + b * 64), "r"(k * 64), "r"(fb), "h"((uint16_t)3) : "memory");
        }
      }
    } else if (warp > 8) {
      const int l16 = lane & 15;
      for (int r = (warp - 9) * 2 + (lane >> 4); r < 132; r += 6) {
        const int rr = r < 128 ? r : 127;
        float z = 0.f;
#pragma unroll
        for (int k = 0; k < 7; k++) {
          const uint2 xv = *reinterpret_cast<const uint2*>(x + (r0 + rr) * DM + (k * 16 + l16) * 4);
          const uint2 gv = *reinterpret_cast<const uint2*>(gate_w + (k * 16 + l16) * 4);
          z = fmaf(bf_lo(xv.x), bf_lo(gv.x), z); z = fmaf(bf_hi(xv.x), bf_hi(gv.x), z);
          z = fmaf(bf_lo(xv.y), bf_lo(gv.y), z); z = fmaf(bf_hi(xv.y), bf_hi(gv.y), z);
        }
#pragma unroll
        for (int o = 1; o < 16; o <<= 1) z += __shfl_xor_sync(0xffffffffu, z, o);
        if (l16 == 0) sts32v(sb + F_G + rr * 4, __float_as_uint(1.f - rcp(1.f + ex2(-1.4426950408889634f * z))));
      }
      __syncwarp();
      bar_arrive(1, 352);
    }
    __syncwarp();
    cluster_arrive_relaxed();
    cluster_wait();
  } else {
    asm volatile("setmaxnreg.inc.sync.aligned.u32 224;");
    const int wg = warp >> 2, row = wg * 64 + (warp & 3) * 16 + (lane >> 2);
    const uint32_t epoch = (ldg1r(&g_ticket[1]) >> 4) + 1;
    int it = 0;
#pragma unroll 1
    for (int t = 0; t < 7; t++) {
      float d[128];
      ffn_tile<256>(d, sb, wg, 7, it, dead, lane);
      const uint32_t stg = sb + F_STG + warp * 2304;
      __nv_bfloat16* hp = g_h + (size_t)(r0 + warp * 16 + (lane >> 3)) * DFF + t * 256 + (lane & 7) * 8;
#pragma unroll
      for (int hf = 0; hf < 4; hf++) {
#pragma unroll
        for (int n = 0; n < 8; n += 2) {
          const float* e = d + 32 * hf + 4 * n;
          asm volatile("stmatrix.sync.aligned.m8n8.x4.shared.b16 [%0], {%1,%2,%3,%4};"
                       :: "r"(stg + (lane & 15) * 144 + (n + (lane >> 4)) * 16), "r"(pack2(fmaxf(e[0], 0.f), fmaxf(e[1], 0.f))), "r"(pack2(fmaxf(e[2], 0.f), fmaxf(e[3], 0.f))),
                          "r"(pack2(fmaxf(e[4], 0.f), fmaxf(e[5], 0.f))), "r"(pack2(fmaxf(e[6], 0.f), fmaxf(e[7], 0.f))) : "memory");
        }
        __syncwarp();
#pragma unroll
        for (int r = 0; r < 4; r++) {
          const uint4 v = lds_u4(stg + (4 * r + (lane >> 3)) * 144 + (lane & 7) * 16);
          *reinterpret_cast<uint4*>(hp + (size_t)4 * r * DFF + hf * 64) = v;
        }
        __syncwarp();
      }
    }
    __threadfence();
    asm volatile("fence.proxy.async;" ::: "memory");
    mbar_arrive(hbar);
    bar_sync(1, 352);
    const float g0 = __uint_as_float(lds32v(sb + F_G + row * 4)), g1 = __uint_as_float(lds32v(sb + F_G + row * 4 + 32));
    {
      float d[128];
      ffn_tile<256>(d, sb, wg, 28, it, dead, lane);
      ffn_finish<4>(d, g0, g1, sb, r0, row, 0, epoch, out, tid);
    }
    {
      float d[96];
      ffn_tile<192>(d, sb, wg, 28, it, dead, lane);
      ffn_finish<3>(d, g0, g1, sb, r0, row, 4, epoch, out, tid);
    }
    bar_sync(1, 256);
    if (tid == 0) atomicAdd(&g_ticket[1], 1);
    if (dead <= 0) g_err = 1;
    cluster_arrive_relaxed();
    cluster_wait();
  }
}

__device__ float g_fmem[8 * DM];
__global__ void fb_qkv(const __nv_bfloat16* x, const __nv_bfloat16* mem0, const __nv_bfloat16* wq, const __nv_bfloat16* wk,
                       const __nv_bfloat16* wv, int s) {
  __shared__ __nv_bfloat16 hs[40 * DM];
  for (int i = threadIdx.x; i < 40 * DM; i += 128)
    hs[i] = i >= 8 * DM ? x[s * 32 * DM + i - 8 * DM] : s ? __float2bfloat16(g_fmem[i]) : mem0[i];
  __syncthreads();
  const int col = blockIdx.x * 128 + threadIdx.x;
  const __nv_bfloat16* w = (blockIdx.y == 0 ? wq : blockIdx.y == 1 ? wk : wv) + col;
  float acc[40];
#pragma unroll
  for (int r = 0; r < 40; r++) acc[r] = 0.f;
  for (int d = 0; d < DM; d++) {
    const float wv_ = __bfloat162float(w[d * 4096]);
#pragma unroll
    for (int r = 0; r < 40; r++) acc[r] = fmaf(__bfloat162float(hs[r * DM + d]), wv_, acc[r]);
  }
#pragma unroll
  for (int r = 0; r < 40; r++) g_b[(blockIdx.y * 40 + r) * 4096 + col] = acc[r];
}
__global__ void fb_attn() {
  __shared__ float p[40];
  const int h = blockIdx.x, r = blockIdx.y, t = threadIdx.x;
  if (t < 40) {
    float a = 0.f;
    for (int e = 0; e < DH; e++) a = fmaf(g_b[r * 4096 + h * DH + e], g_b[(40 + t) * 4096 + h * DH + e], a);
    p[t] = (r < 8 || r >= t) ? a * 0.0625f : -1e9f;
  }
  __syncthreads();
  float mx = p[0], l = 0.f, o = 0.f;
  for (int k = 1; k < 40; k++) mx = fmaxf(mx, p[k]);
  for (int k = 0; k < 40; k++) { const float e = expf(p[k] - mx); l += e; o = fmaf(e, g_b[(80 + k) * 4096 + h * DH + t], o); }
  g_b[(120 + r) * 4096 + h * DH + t] = o / l;
}
__global__ void fb_out(const __nv_bfloat16* wo, int s) {
  const int r = blockIdx.x, c = threadIdx.x;
  float a = 0.f;
  for (int k = 0; k < 4096; k++) a = fmaf(g_b[(120 + r) * 4096 + k], __bfloat162float(wo[k * DM + c]), a);
  if (r < 8) g_fmem[r * DM + c] = a; else g_stash[(s * 32 + r - 8) * DM + c] = a;
}
__global__ void fb_ffn(const __nv_bfloat16* x, const __nv_bfloat16* w1, const __nv_bfloat16* w2, const __nv_bfloat16* gw, __nv_bfloat16* out) {
  __shared__ float xs[DM], hs[DFF];
  const int r = blockIdx.x, c = threadIdx.x;
  xs[c] = __bfloat162float(x[r * DM + c]);
  __syncthreads();
  float z = 0.f, b = 0.f;
  for (int d = 0; d < DM; d++) z = fmaf(xs[d], __bfloat162float(gw[d]), z);
  for (int f = c; f < DFF; f += DM) {
    float a = 0.f;
    for (int d = 0; d < DM; d++) a = fmaf(xs[d], __bfloat162float(w1[d * DFF + f]), a);
    hs[f] = fmaxf(a, 0.f);
  }
  __syncthreads();
  for (int f = 0; f < DFF; f++) b = fmaf(hs[f], __bfloat162float(w2[f * DM + c]), b);
  const float g = 1.f / (1.f + expf(-z));
  out[r * DM + c] = __float2bfloat16(g * g_stash[r * DM + c] + (1.f - g) * b);
}

typedef CUresult (*EncodeFn)(CUtensorMap*, CUtensorMapDataType, cuuint32_t, void*, const cuuint64_t*, const cuuint64_t*,
                             const cuuint32_t*, const cuuint32_t*, CUtensorMapInterleave, CUtensorMapSwizzle,
                             CUtensorMapL2promotion, CUtensorMapFloatOOBfill);

void make_map(EncodeFn fn, CUtensorMap* m, const void* p, uint64_t rows, uint64_t cols, uint32_t box_rows) {
  const cuuint64_t dims[2] = {cols, rows}, strides[1] = {cols * 2};
  const cuuint32_t box[2] = {64, box_rows}, es[2] = {1, 1};
  fn(m, CU_TENSOR_MAP_DATA_TYPE_BFLOAT16, 2, const_cast<void*>(p), dims, strides, box, es, CU_TENSOR_MAP_INTERLEAVE_NONE,
     CU_TENSOR_MAP_SWIZZLE_128B, CU_TENSOR_MAP_L2_PROMOTION_L2_256B, CU_TENSOR_MAP_FLOAT_OOB_FILL_NONE);
}

}

extern "C" void kernel_launch(void* const* d_in, const int* in_sizes, int n_in, void* d_out, int out_size) {
  (void)in_sizes; (void)n_in; (void)out_size;
  const __nv_bfloat16* x = (const __nv_bfloat16*)d_in[0];
  const __nv_bfloat16* mem0 = (const __nv_bfloat16*)d_in[1];
  const __nv_bfloat16* gate_w = (const __nv_bfloat16*)d_in[10];
  static EncodeFn fn = nullptr;
  static void* hptr = nullptr;
  static int mode = 0;
  cudaLaunchConfig_t cfg = {};
  cudaLaunchAttribute at[2];
  cfg.gridDim = dim3(112); cfg.blockDim = dim3(384); cfg.dynamicSmemBytes = T_SMEM; cfg.stream = cudaStreamPerThread;
  at[0].id = cudaLaunchAttributeClusterDimension;
  at[0].val.clusterDim.x = 16; at[0].val.clusterDim.y = 1; at[0].val.clusterDim.z = 1;
  cfg.attrs = at; cfg.numAttrs = 1;
  if (!mode) {
    cudaDriverEntryPointQueryResult qr;
    cudaGetDriverEntryPoint("cuTensorMapEncodeTiled", (void**)&fn, cudaEnableDefault, &qr);
    cudaGetSymbolAddress(&hptr, g_h);
    cudaFuncSetAttribute(rmt_kernel, cudaFuncAttributeMaxDynamicSharedMemorySize, T_SMEM);
    cudaFuncSetAttribute(rmt_kernel, cudaFuncAttributeNonPortableClusterSizeAllowed, 1);
    cudaFuncSetAttribute(ffn_kernel, cudaFuncAttributeMaxDynamicSharedMemorySize, F_SMEM);
    int ncl = 0;
    mode = fn && cudaOccupancyMaxActiveClusters(&ncl, rmt_kernel, &cfg) == cudaSuccess && ncl >= 7 ? 1 : 2;
    (void)cudaGetLastError();
  }
  if (mode == 2) {
    const __nv_bfloat16* const* in = (const __nv_bfloat16* const*)d_in;
    for (int s = 0; s < NSEG; s++) {
      fb_qkv<<<dim3(32, 3), 128, 0, cudaStreamPerThread>>>(x, mem0, in[2], in[3], in[4], s);
      fb_attn<<<dim3(NH, 40), DH, 0, cudaStreamPerThread>>>();
      fb_out<<<40, DM, 0, cudaStreamPerThread>>>(in[5], s);
    }
    fb_ffn<<<SEQ, DM, 0, cudaStreamPerThread>>>(x, in[8], in[9], gate_w, (__nv_bfloat16*)d_out);
    return;
  }
  CUtensorMap mWq, mWk, mWv, mWo, mX, mXf, mW1, mH, mW2;
  make_map(fn, &mWq, d_in[2], DM, NH * DH, 64);
  make_map(fn, &mWk, d_in[3], DM, NH * DH, 224);
  make_map(fn, &mWv, d_in[4], DM, NH * DH, 224);
  make_map(fn, &mWo, d_in[5], NH * DH, DM, 256);
  make_map(fn, &mX, x, SEQ, DM, 32);
  make_map(fn, &mXf, x, SEQ, DM, 128);
  make_map(fn, &mW1, d_in[8], DM, DFF, 64);
  make_map(fn, &mH, hptr, SEQ, DFF, 128);
  make_map(fn, &mW2, d_in[9], DFF, DM, 64);

  cudaLaunchKernelEx(&cfg, rmt_kernel, mWq, mWk, mWv, mWo, mX, x, mem0, gate_w, (__nv_bfloat16*)d_out);

  cfg.gridDim = dim3(16); cfg.dynamicSmemBytes = F_SMEM;
  at[0].val.clusterDim.x = 2;
  at[1].id = cudaLaunchAttributeProgrammaticStreamSerialization;
  at[1].val.programmaticStreamSerializationAllowed = 1;
  cfg.numAttrs = 2;
  cudaLaunchKernelEx(&cfg, ffn_kernel, mXf, mW1, mH, mW2, x, gate_w, (__nv_bfloat16*)d_out);
}
```

```cpp
#include <cuda_runtime.h>
#include <cuda_bf16.h>
#include <cuda.h>
#include <stdint.h>

namespace {

#define DEVI __device__ __forceinline__

constexpr int SEQ = 2048, DM = 448, NH = 16, DH = 256, NSEG = 64, DFF = 1792;
constexpr float SC2 = 1.4426950408889634f / 16.0f;
constexpr float MASKV = -1.6e10f;
constexpr int SPIN_LIMIT = 1 << 20;

#define D_M 420
#define D_T 700
#define D_SS 230
#define D_TL 750
#define FFN_AT 12
#define D_S 150

__device__ __align__(1024) uint8_t g_mslot[3][8192];
__device__ __align__(1024) float g_smm[NH][2][7][64];
__device__ __align__(1024) float g_xacc[8][NH][512];
__device__ __align__(1024) float g_sacc[8][NH][1408];
__device__ __align__(1024) float g_stash[SEQ * DM];
__device__ __align__(1024) float g_b[SEQ * DM];
__device__ __align__(1024) __nv_bfloat16 g_h[SEQ * DFF];
__device__ __align__(1024) uint32_t g_bflag[32][2][8];
__device__ uint32_t g_ticket[2];
__device__ int g_err;

DEVI uint32_t smem_u32(const void* p) { return (uint32_t)__cvta_generic_to_shared(p); }
DEVI uint32_t clk() { uint32_t c; asm volatile("mov.u32 %0, %%clock;" : "=r"(c) :: "memory"); return c; }
DEVI void mbar_init(uint32_t bar, uint32_t cnt) { asm volatile("mbarrier.init.shared::cta.b64 [%0], %1;" :: "r"(bar), "r"(cnt) : "memory"); }
DEVI void mbar_expect(uint32_t bar, uint32_t bytes) { asm volatile("mbarrier.arrive.expect_tx.shared::cta.b64 _, [%0], %1;" :: "r"(bar), "r"(bytes) : "memory"); }
DEVI void mbar_arrive(uint32_t bar) { asm volatile("mbarrier.arrive.shared::cta.b64 _, [%0];" :: "r"(bar) : "memory"); }
DEVI uint32_t lds32v(uint32_t a) { uint32_t v; asm volatile("ld.volatile.shared::cta.u32 %0, [%1];" : "=r"(v) : "r"(a) : "memory"); return v; }
DEVI void sts32v(uint32_t a, uint32_t v) { asm volatile("st.volatile.shared::cta.u32 [%0], %1;" :: "r"(a), "r"(v) : "memory"); }
DEVI void mbar_wait(uint32_t bar, uint32_t par, int& lim) {
  asm volatile("{\n.reg .pred p, q;\nWAIT_LOOP:\n"
               "mbarrier.try_wait.parity.shared::cta.b64 p, [%1], %2;\n"
               "sub.s32 %0, %0, 1;\nsetp.gt.and.s32 q, %0, 0, !p;\n@q bra.uni WAIT_LOOP;\n}"
               : "+r"(lim) : "r"(bar), "r"(par) : "memory");
}
DEVI void mbar_wait1(uint32_t bar, uint32_t par, int& lim) {
  asm volatile("{\n.reg .pred p, q;\nWAIT_LOOP:\n"
               "mbarrier.try_wait.parity.shared::cta.b64 p, [%1], %2;\n"
               "sub.s32 %0, %0, 1;\nsetp.gt.and.s32 q, %0, 0, !p;\n@q bra WAIT_LOOP;\n}"
               : "+r"(lim) : "r"(bar), "r"(par) : "memory");
}
DEVI bool elect() { uint32_t p; asm volatile("{\n.reg .pred p;\nelect.sync _|p, 0xffffffff;\nselp.u32 %0, 1, 0, p;\n}" : "=r"(p)); return p; }
DEVI void delay_until(uint32_t t0, uint32_t d) {
  asm volatile("{\n.reg .pred p;\n.reg .u32 t, u;\n.reg .u64 c;\nDELAY_LOOP:\nmov.u64 c, %%clock64;\nmov.b64 {t, u}, c;\nsub.u32 t, t, %0;\nsetp.lt.u32 p, t, %1;\n@p bra.uni DELAY_LOOP;\n}"
               :: "r"(t0), "r"(d) : "memory");
}
DEVI float rcp(float x) { float y; asm("rcp.approx.ftz.f32 %0, %1;" : "=f"(y) : "f"(x)); return y; }
DEVI uint32_t keep(uint32_t v, int lane) { return __shfl_sync(0xffffffffu, v, lane); }
template <class T> DEVI T* keepp(T* p, int lane) { return reinterpret_cast<T*>(__shfl_sync(0xffffffffu, reinterpret_cast<unsigned long long>(p), lane)); }
template <class T> DEVI void pin(T& v) { asm volatile("" : "+r"(v)); }
template <class T> DEVI void pinp(T*& v) { asm volatile("" : "+l"(v)); }
DEVI void bar_sync(int id, int n) { asm volatile("bar.sync %0, %1;" :: "r"(id), "r"(n) : "memory"); }
DEVI void bar_arrive(int id, int n) { asm volatile("bar.arrive %0, %1;" :: "r"(id), "r"(n) : "memory"); }
DEVI void cluster_arrive_relaxed() { asm volatile("barrier.cluster.arrive.relaxed.aligned;" ::: "memory"); }
DEVI void cluster_arrive() { asm volatile("barrier.cluster.arrive.release.aligned;" ::: "memory"); }
DEVI void cluster_wait() { asm volatile("barrier.cluster.wait.acquire.aligned;" ::: "memory"); }
DEVI uint32_t mapa(uint32_t a, uint32_t r) { uint32_t o; asm("mapa.shared::cluster.u32 %0, %1, %2;" : "=r"(o) : "r"(a), "r"(r)); return o; }
DEVI uint32_t pack2(float lo, float hi) { uint32_t r; asm("cvt.rn.bf16x2.f32 %0, %1, %2;" : "=r"(r) : "f"(hi), "f"(lo)); return r; }
DEVI float ex2(float x) { float y; asm("ex2.approx.ftz.f32 %0, %1;" : "=f"(y) : "f"(x)); return y; }
DEVI float bf_lo(uint32_t v) { return __uint_as_float(v << 16); }
DEVI float bf_hi(uint32_t v) { return __uint_as_float(v & 0xffff0000u); }
DEVI void ldsm4(uint32_t (&r)[4], uint32_t a) {
  asm volatile("ldmatrix.sync.aligned.m8n8.x4.shared.b16 {%0,%1,%2,%3}, [%4];" : "=r"(r[0]), "=r"(r[1]), "=r"(r[2]), "=r"(r[3]) : "r"(a) : "memory");
}
DEVI void stsm4t(uint32_t a, uint32_t r0, uint32_t r1, uint32_t r2, uint32_t r3) {
  asm volatile("stmatrix.sync.aligned.m8n8.x4.trans.shared.b16 [%0], {%1,%2,%3,%4};" :: "r"(a), "r"(r0), "r"(r1), "r"(r2), "r"(r3) : "memory");
}
DEVI void stsm2t(uint32_t a, uint32_t r0, uint32_t r1) {
  asm volatile("stmatrix.sync.aligned.m8n8.x2.trans.shared.b16 [%0], {%1,%2};" :: "r"(a), "r"(r0), "r"(r1) : "memory");
}
DEVI void mma16(float (&c)[4], uint32_t a0, uint32_t a1, uint32_t a2, uint32_t a3, uint32_t b0, uint32_t b1) {
  asm("mma.sync.aligned.m16n8k16.row.col.f32.bf16.bf16.f32 {%0,%1,%2,%3},{%4,%5,%6,%7},{%8,%9},{%0,%1,%2,%3};"
      : "+f"(c[0]), "+f"(c[1]), "+f"(c[2]), "+f"(c[3]) : "r"(a0), "r"(a1), "r"(a2), "r"(a3), "r"(b0), "r"(b1));
}
DEVI void mma8(float (&c)[4], uint32_t a0, uint32_t a1, uint32_t b0) {
  asm("mma.sync.aligned.m16n8k8.row.col.f32.bf16.bf16.f32 {%0,%1,%2,%3},{%4,%5},{%6},{%0,%1,%2,%3};"
      : "+f"(c[0]), "+f"(c[1]), "+f"(c[2]), "+f"(c[3]) : "r"(a0), "r"(a1), "r"(b0));
}
DEVI void mma16v(float (&c)[4], uint32_t a0, uint32_t a1, uint32_t a2, uint32_t a3, uint32_t b0, uint32_t b1) {
  asm volatile("mma.sync.aligned.m16n8k16.row.col.f32.bf16.bf16.f32 {%0,%1,%2,%3},{%4,%5,%6,%7},{%8,%9},{%0,%1,%2,%3};"
      : "+f"(c[0]), "+f"(c[1]), "+f"(c[2]), "+f"(c[3]) : "r"(a0), "r"(a1), "r"(a2), "r"(a3), "r"(b0), "r"(b1));
}
DEVI void mma8v(float (&c)[4], uint32_t a0, uint32_t a1, uint32_t b0) {
  asm volatile("mma.sync.aligned.m16n8k8.row.col.f32.bf16.bf16.f32 {%0,%1,%2,%3},{%4,%5},{%6},{%0,%1,%2,%3};"
      : "+f"(c[0]), "+f"(c[1]), "+f"(c[2]), "+f"(c[3]) : "r"(a0), "r"(a1), "r"(b0));
}
DEVI float2 mma_rows8(const uint32_t (&a0)[4], const uint32_t (&a1)[4], const uint32_t (&b0)[4], const uint32_t (&b1)[4]) {
  float e0[4] = {0.f, 0.f, 0.f, 0.f}, e1[4] = {0.f, 0.f, 0.f, 0.f}, e2[4] = {0.f, 0.f, 0.f, 0.f}, e3[4] = {0.f, 0.f, 0.f, 0.f};
  mma16v(e0, a0[0], a0[1], a0[2], a0[3], b0[0], b0[1]);
  mma16v(e1, a0[0], a0[1], a0[2], a0[3], b0[2], b0[3]);
  mma16v(e2, a1[0], a1[1], a1[2], a1[3], b1[0], b1[1]);
  mma16v(e3, a1[0], a1[1], a1[2], a1[3], b1[2], b1[3]);
  return make_float2((e0[0] + e1[2]) + (e2[0] + e3[2]), (e0[1] + e1[3]) + (e2[1] + e3[3]));
}
DEVI void wg_fence() { asm volatile("wgmma.fence.sync.aligned;" ::: "memory"); }
DEVI void wg_commit() { asm volatile("wgmma.commit_group.sync.aligned;" ::: "memory"); }
template <int N> DEVI void wg_wait() { asm volatile("wgmma.wait_group.sync.aligned %0;" :: "n"(N) : "memory"); }
template <int N> DEVI void reg_fence(float (&d)[N]) {
#pragma unroll
  for (int i = 0; i < N; i++) asm volatile("" : "+f"(d[i]) :: "memory");
}
DEVI uint64_t desc128(uint32_t addr, uint32_t lbo16) {
  return (uint64_t)((addr >> 4) & 0x3fff) | ((uint64_t)lbo16 << 16) | (64ull << 32) | (1ull << 62);
}
DEVI void tma2d(uint32_t dst, const CUtensorMap* tm, int c0, int c1, uint32_t bar) {
  asm volatile("cp.async.bulk.tensor.2d.shared::cluster.global.mbarrier::complete_tx::bytes [%0], [%1, {%2, %3}], [%4];"
               :: "r"(dst), "l"(tm), "r"(c0), "r"(c1), "r"(bar) : "memory");
}
DEVI void tma2d_mc(uint32_t dst, const CUtensorMap* tm, int c0, int c1, uint32_t bar) {
  asm volatile("cp.async.bulk.tensor.2d.shared::cluster.global.mbarrier::complete_tx::bytes.multicast::cluster [%0], [%1, {%2, %3}], [%4], %5;"
               :: "r"(dst), "l"(tm), "r"(c0), "r"(c1), "r"(bar), "h"((uint16_t)0xffff) : "memory");
}
DEVI void bulk_mc(uint32_t dst, const void* src, uint32_t bytes, uint32_t bar) {
  asm volatile("cp.async.bulk.shared::cluster.global.mbarrier::complete_tx::bytes.multicast::cluster [%0], [%1], %2, [%3], %4;"
               :: "r"(dst), "l"(src), "r"(bytes), "r"(bar), "h"((uint16_t)0xffff) : "memory");
}
DEVI void st_async4(uint32_t a, float x, float y, float z, float w, uint32_t bar) {
  asm volatile("st.async.weak.shared::cluster.mbarrier::complete_tx::bytes.v4.f32 [%0], {%1,%2,%3,%4}, [%5];"
               :: "r"(a), "f"(x), "f"(y), "f"(z), "f"(w), "r"(bar) : "memory");
}
DEVI void st_async4u(uint32_t a, uint32_t x, uint32_t y, uint32_t z, uint32_t w, uint32_t bar) {
  asm volatile("st.async.weak.shared::cluster.mbarrier::complete_tx::bytes.v4.b32 [%0], {%1,%2,%3,%4}, [%5];"
               :: "r"(a), "r"(x), "r"(y), "r"(z), "r"(w), "r"(bar) : "memory");
}
DEVI uint32_t ldg1r(const void* p) { uint32_t v; asm volatile("ld.relaxed.gpu.global.u32 %0, [%1];" : "=r"(v) : "l"(p) : "memory"); return v; }
DEVI void ldg2r(uint32_t& x, uint32_t& y, const void* p) { asm volatile("ld.relaxed.gpu.global.v2.u32 {%0,%1}, [%2];" : "=r"(x), "=r"(y) : "l"(p) : "memory"); }
DEVI void stg2r(void* p, uint32_t x, uint32_t y) { asm volatile("st.relaxed.gpu.global.v2.u32 [%0], {%1,%2};" :: "l"(p), "r"(x), "r"(y) : "memory"); }
DEVI float4 lds_f4(uint32_t a) { float4 v; asm volatile("ld.shared.v4.f32 {%0,%1,%2,%3}, [%4];" : "=f"(v.x), "=f"(v.y), "=f"(v.z), "=f"(v.w) : "r"(a) : "memory"); return v; }
DEVI uint2 lds_u2(uint32_t a) { uint2 v; asm volatile("ld.shared.v2.u32 {%0,%1}, [%2];" : "=r"(v.x), "=r"(v.y) : "r"(a) : "memory"); return v; }
DEVI uint4 lds_u4(uint32_t a) { uint4 v; asm volatile("ld.shared.v4.u32 {%0,%1,%2,%3}, [%4];" : "=r"(v.x), "=r"(v.y), "=r"(v.z), "=r"(v.w) : "r"(a) : "memory"); return v; }
DEVI void sts_f4(uint32_t a, float x, float y, float z, float w) { asm volatile("st.shared.v4.f32 [%0], {%1,%2,%3,%4};" :: "r"(a), "f"(x), "f"(y), "f"(z), "f"(w) : "memory"); }
DEVI void sts_u2(uint32_t a, uint32_t x, uint32_t y) { asm volatile("st.shared.v2.u32 [%0], {%1,%2};" :: "r"(a), "r"(x), "r"(y) : "memory"); }
DEVI void sts_u4(uint32_t a, uint32_t x, uint32_t y, uint32_t z, uint32_t w) { asm volatile("st.shared.v4.u32 [%0], {%1,%2,%3,%4};" :: "r"(a), "r"(x), "r"(y), "r"(z), "r"(w) : "memory"); }
DEVI uint32_t tagf(float v, uint32_t tag) { return (__float_as_uint(v) & ~3u) | tag; }
DEVI float qmax(float v) { v = fmaxf(v, __shfl_xor_sync(0xffffffffu, v, 1)); return fmaxf(v, __shfl_xor_sync(0xffffffffu, v, 2)); }
DEVI float qsum(float v) { v += __shfl_xor_sync(0xffffffffu, v, 1); return v + __shfl_xor_sync(0xffffffffu, v, 2); }

__device__ __forceinline__ void wgmma_n224_kk(float (&d)[112], uint64_t da, uint64_t db, int sc) {
  asm volatile("{\n.reg .pred p;\nsetp.ne.b32 p, %114, 0;\n"
    "wgmma.mma_async.sync.aligned.m64n224k16.f32.bf16.bf16 {%0,%1,%2,%3,%4,%5,%6,%7,%8,%9,%10,%11,%12,%13,%14,%15,%16,%17,%18,%19,%20,%21,%22,%23,%24,%25,%26,%27,%28,%29,%30,%31,%32,%33,%34,%35,%36,%37,%38,%39,%40,%41,%42,%43,%44,%45,%46,%47,%48,%49,%50,%51,%52,%53,%54,%55,%56,%57,%58,%59,%60,%61,%62,%63,%64,%65,%66,%67,%68,%69,%70,%71,%72,%73,%74,%75,%76,%77,%78,%79,%80,%81,%82,%83,%84,%85,%86,%87,%88,%89,%90,%91,%92,%93,%94,%95,%96,%97,%98,%99,%100,%101,%102,%103,%104,%105,%106,%107,%108,%109,%110,%111}, %112, %113, p, 1, 1, 0, 0;\n}"
    : "+f"(d[0]),"+f"(d[1]),"+f"(d[2]),"+f"(d[3]),"+f"(d[4]),"+f"(d[5]),"+f"(d[6]),"+f"(d[7]),"+f"(d[8]),"+f"(d[9]),"+f"(d[10]),"+f"(d[11]),"+f"(d[12]),"+f"(d[13]),"+f"(d[14]),"+f"(d[15]),"+f"(d[16]),"+f"(d[17]),"+f"(d[18]),"+f"(d[19]),"+f"(d[20]),"+f"(d[21]),"+f"(d[22]),"+f"(d[23]),"+f"(d[24]),"+f"(d[25]),"+f"(d[26]),"+f"(d[27]),"+f"(d[28]),"+f"(d[29]),"+f"(d[30]),"+f"(d[31]),"+f"(d[32]),"+f"(d[33]),"+f"(d[34]),"+f"(d[35]),"+f"(d[36]),"+f"(d[37]),"+f"(d[38]),"+f"(d[39]),"+f"(d[40]),"+f"(d[41]),"+f"(d[42]),"+f"(d[43]),"+f"(d[44]),"+f"(d[45]),"+f"(d[46]),"+f"(d[47]),"+f"(d[48]),"+f"(d[49]),"+f"(d[50]),"+f"(d[51]),"+f"(d[52]),"+f"(d[53]),"+f"(d[54]),"+f"(d[55]),"+f"(d[56]),"+f"(d[57]),"+f"(d[58]),"+f"(d[59]),"+f"(d[60]),"+f"(d[61]),"+f"(d[62]),"+f"(d[63]),"+f"(d[64]),"+f"(d[65]),"+f"(d[66]),"+f"(d[67]),"+f"(d[68]),"+f"(d[69]),"+f"(d[70]),"+f"(d[71]),"+f"(d[72]),"+f"(d[73]),"+f"(d[74]),"+f"(d[75]),"+f"(d[76]),"+f"(d[77]),"+f"(d[78]),"+f"(d[79]),"+f"(d[80]),"+f"(d[81]),"+f"(d[82]),"+f"(d[83]),"+f"(d[84]),"+f"(d[85]),"+f"(d[86]),"+f"(d[87]),"+f"(d[88]),"+f"(d[89]),"+f"(d[90]),"+f"(d[91]),"+f"(d[92]),"+f"(d[93]),"+f"(d[94]),"+f"(d[95]),"+f"(d[96]),"+f"(d[97]),"+f"(d[98]),"+f"(d[99]),"+f"(d[100]),"+f"(d[101]),"+f"(d[102]),"+f"(d[103]),"+f"(d[104]),"+f"(d[105]),"+f"(d[106]),"+f"(d[107]),"+f"(d[108]),"+f"(d[109]),"+f"(d[110]),"+f"(d[111])
    : "l"(da),"l"(db),"r"(sc));
}
__device__ __forceinline__ void wgmma_n224_mk(float (&d)[112], uint64_t da, uint64_t db, int sc) {
  asm volatile("{\n.reg .pred p;\nsetp.ne.b32 p, %114, 0;\n"
    "wgmma.mma_async.sync.aligned.m64n224k16.f32.bf16.bf16 {%0,%1,%2,%3,%4,%5,%6,%7,%8,%9,%10,%11,%12,%13,%14,%15,%16,%17,%18,%19,%20,%21,%22,%23,%24,%25,%26,%27,%28,%29,%30,%31,%32,%33,%34,%35,%36,%37,%38,%39,%40,%41,%42,%43,%44,%45,%46,%47,%48,%49,%50,%51,%52,%53,%54,%55,%56,%57,%58,%59,%60,%61,%62,%63,%64,%65,%66,%67,%68,%69,%70,%71,%72,%73,%74,%75,%76,%77,%78,%79,%80,%81,%82,%83,%84,%85,%86,%87,%88,%89,%90,%91,%92,%93,%94,%95,%96,%97,%98,%99,%100,%101,%102,%103,%104,%105,%106,%107,%108,%109,%110,%111}, %112, %113, p, 1, 1, 1, 0;\n}"
    : "+f"(d[0]),"+f"(d[1]),"+f"(d[2]),"+f"(d[3]),"+f"(d[4]),"+f"(d[5]),"+f"(d[6]),"+f"(d[7]),"+f"(d[8]),"+f"(d[9]),"+f"(d[10]),"+f"(d[11]),"+f"(d[12]),"+f"(d[13]),"+f"(d[14]),"+f"(d[15]),"+f"(d[16]),"+f"(d[17]),"+f"(d[18]),"+f"(d[19]),"+f"(d[20]),"+f"(d[21]),"+f"(d[22]),"+f"(d[23]),"+f"(d[24]),"+f"(d[25]),"+f"(d[26]),"+f"(d[27]),"+f"(d[28]),"+f"(d[29]),"+f"(d[30]),"+f"(d[31]),"+f"(d[32]),"+f"(d[33]),"+f"(d[34]),"+f"(d[35]),"+f"(d[36]),"+f"(d[37]),"+f"(d[38]),"+f"(d[39]),"+f"(d[40]),"+f"(d[41]),"+f"(d[42]),"+f"(d[43]),"+f"(d[44]),"+f"(d[45]),"+f"(d[46]),"+f"(d[47]),"+f"(d[48]),"+f"(d[49]),"+f"(d[50]),"+f"(d[51]),"+f"(d[52]),"+f"(d[53]),"+f"(d[54]),"+f"(d[55]),"+f"(d[56]),"+f"(d[57]),"+f"(d[58]),"+f"(d[59]),"+f"(d[60]),"+f"(d[61]),"+f"(d[62]),"+f"(d[63]),"+f"(d[64]),"+f"(d[65]),"+f"(d[66]),"+f"(d[67]),"+f"(d[68]),"+f"(d[69]),"+f"(d[70]),"+f"(d[71]),"+f"(d[72]),"+f"(d[73]),"+f"(d[74]),"+f"(d[75]),"+f"(d[76]),"+f"(d[77]),"+f"(d[78]),"+f"(d[79]),"+f"(d[80]),"+f"(d[81]),"+f"(d[82]),"+f"(d[83]),"+f"(d[84]),"+f"(d[85]),"+f"(d[86]),"+f"(d[87]),"+f"(d[88]),"+f"(d[89]),"+f"(d[90]),"+f"(d[91]),"+f"(d[92]),"+f"(d[93]),"+f"(d[94]),"+f"(d[95]),"+f"(d[96]),"+f"(d[97]),"+f"(d[98]),"+f"(d[99]),"+f"(d[100]),"+f"(d[101]),"+f"(d[102]),"+f"(d[103]),"+f"(d[104]),"+f"(d[105]),"+f"(d[106]),"+f"(d[107]),"+f"(d[108]),"+f"(d[109]),"+f"(d[110]),"+f"(d[111])
    : "l"(da),"l"(db),"r"(sc));
}
__device__ __forceinline__ void wgmma_n32_rs(float (&d)[16], const uint32_t (&a)[4], uint64_t db, int sc) {
  asm volatile("{\n.reg .pred p;\nsetp.ne.b32 p, %21, 0;\n"
    "wgmma.mma_async.sync.aligned.m64n32k16.f32.bf16.bf16 {%0,%1,%2,%3,%4,%5,%6,%7,%8,%9,%10,%11,%12,%13,%14,%15}, {%16,%17,%18,%19}, %20, p, 1, 1, 0;\n}"
    : "+f"(d[0]),"+f"(d[1]),"+f"(d[2]),"+f"(d[3]),"+f"(d[4]),"+f"(d[5]),"+f"(d[6]),"+f"(d[7]),"+f"(d[8]),"+f"(d[9]),"+f"(d[10]),"+f"(d[11]),"+f"(d[12]),"+f"(d[13]),"+f"(d[14]),"+f"(d[15])
    : "r"(a[0]),"r"(a[1]),"r"(a[2]),"r"(a[3]),"l"(db),"r"(sc));
}
__device__ __forceinline__ void wgmma_n8_rs(float (&d)[4], const uint32_t (&a)[4], uint64_t db, int sc) {
  asm volatile("{\n.reg .pred p;\nsetp.ne.b32 p, %9, 0;\n"
    "wgmma.mma_async.sync.aligned.m64n8k16.f32.bf16.bf16 {%0,%1,%2,%3}, {%4,%5,%6,%7}, %8, p, 1, 1, 0;\n}"
    : "+f"(d[0]),"+f"(d[1]),"+f"(d[2]),"+f"(d[3])
    : "r"(a[0]),"r"(a[1]),"r"(a[2]),"r"(a[3]),"l"(db),"r"(sc));
}
__device__ __forceinline__ void wgmma_n256_kn(float (&d)[128], uint64_t da, uint64_t db, int sc) {
  asm volatile("{\n.reg .pred p;\nsetp.ne.b32 p, %130, 0;\n"
    "wgmma.mma_async.sync.aligned.m64n256k16.f32.bf16.bf16 {%0,%1,%2,%3,%4,%5,%6,%7,%8,%9,%10,%11,%12,%13,%14,%15,%16,%17,%18,%19,%20,%21,%22,%23,%24,%25,%26,%27,%28,%29,%30,%31,%32,%33,%34,%35,%36,%37,%38,%39,%40,%41,%42,%43,%44,%45,%46,%47,%48,%49,%50,%51,%52,%53,%54,%55,%56,%57,%58,%59,%60,%61,%62,%63,%64,%65,%66,%67,%68,%69,%70,%71,%72,%73,%74,%75,%76,%77,%78,%79,%80,%81,%82,%83,%84,%85,%86,%87,%88,%89,%90,%91,%92,%93,%94,%95,%96,%97,%98,%99,%100,%101,%102,%103,%104,%105,%106,%107,%108,%109,%110,%111,%112,%113,%114,%115,%116,%117,%118,%119,%120,%121,%122,%123,%124,%125,%126,%127}, %128, %129, p, 1, 1, 0, 1;\n}"
    : "+f"(d[0]),"+f"(d[1]),"+f"(d[2]),"+f"(d[3]),"+f"(d[4]),"+f"(d[5]),"+f"(d[6]),"+f"(d[7]),"+f"(d[8]),"+f"(d[9]),"+f"(d[10]),"+f"(d[11]),"+f"(d[12]),"+f"(d[13]),"+f"(d[14]),"+f"(d[15]),"+f"(d[16]),"+f"(d[17]),"+f"(d[18]),"+f"(d[19]),"+f"(d[20]),"+f"(d[21]),"+f"(d[22]),"+f"(d[23]),"+f"(d[24]),"+f"(d[25]),"+f"(d[26]),"+f"(d[27]),"+f"(d[28]),"+f"(d[29]),"+f"(d[30]),"+f"(d[31]),"+f"(d[32]),"+f"(d[33]),"+f"(d[34]),"+f"(d[35]),"+f"(d[36]),"+f"(d[37]),"+f"(d[38]),"+f"(d[39]),"+f"(d[40]),"+f"(d[41]),"+f"(d[42]),"+f"(d[43]),"+f"(d[44]),"+f"(d[45]),"+f"(d[46]),"+f"(d[47]),"+f"(d[48]),"+f"(d[49]),"+f"(d[50]),"+f"(d[51]),"+f"(d[52]),"+f"(d[53]),"+f"(d[54]),"+f"(d[55]),"+f"(d[56]),"+f"(d[57]),"+f"(d[58]),"+f"(d[59]),"+f"(d[60]),"+f"(d[61]),"+f"(d[62]),"+f"(d[63]),"+f"(d[64]),"+f"(d[65]),"+f"(d[66]),"+f"(d[67]),"+f"(d[68]),"+f"(d[69]),"+f"(d[70]),"+f"(d[71]),"+f"(d[72]),"+f"(d[73]),"+f"(d[74]),"+f"(d[75]),"+f"(d[76]),"+f"(d[77]),"+f"(d[78]),"+f"(d[79]),"+f"(d[80]),"+f"(d[81]),"+f"(d[82]),"+f"(d[83]),"+f"(d[84]),"+f"(d[85]),"+f"(d[86]),"+f"(d[87]),"+f"(d[88]),"+f"(d[89]),"+f"(d[90]),"+f"(d[91]),"+f"(d[92]),"+f"(d[93]),"+f"(d[94]),"+f"(d[95]),"+f"(d[96]),"+f"(d[97]),"+f"(d[98]),"+f"(d[99]),"+f"(d[100]),"+f"(d[101]),"+f"(d[102]),"+f"(d[103]),"+f"(d[104]),"+f"(d[105]),"+f"(d[106]),"+f"(d[107]),"+f"(d[108]),"+f"(d[109]),"+f"(d[110]),"+f"(d[111]),"+f"(d[112]),"+f"(d[113]),"+f"(d[114]),"+f"(d[115]),"+f"(d[116]),"+f"(d[117]),"+f"(d[118]),"+f"(d[119]),"+f"(d[120]),"+f"(d[121]),"+f"(d[122]),"+f"(d[123]),"+f"(d[124]),"+f"(d[125]),"+f"(d[126]),"+f"(d[127])
    : "l"(da),"l"(db),"r"(sc));
}
__device__ __forceinline__ void wgmma_n192_kn(float (&d)[96], uint64_t da, uint64_t db, int sc) {
  asm volatile("{\n.reg .pred p;\nsetp.ne.b32 p, %98, 0;\n"
    "wgmma.mma_async.sync.aligned.m64n192k16.f32.bf16.bf16 {%0,%1,%2,%3,%4,%5,%6,%7,%8,%9,%10,%11,%12,%13,%14,%15,%16,%17,%18,%19,%20,%21,%22,%23,%24,%25,%26,%27,%28,%29,%30,%31,%32,%33,%34,%35,%36,%37,%38,%39,%40,%41,%42,%43,%44,%45,%46,%47,%48,%49,%50,%51,%52,%53,%54,%55,%56,%57,%58,%59,%60,%61,%62,%63,%64,%65,%66,%67,%68,%69,%70,%71,%72,%73,%74,%75,%76,%77,%78,%79,%80,%81,%82,%83,%84,%85,%86,%87,%88,%89,%90,%91,%92,%93,%94,%95}, %96, %97, p, 1, 1, 0, 1;\n}"
    : "+f"(d[0]),"+f"(d[1]),"+f"(d[2]),"+f"(d[3]),"+f"(d[4]),"+f"(d[5]),"+f"(d[6]),"+f"(d[7]),"+f"(d[8]),"+f"(d[9]),"+f"(d[10]),"+f"(d[11]),"+f"(d[12]),"+f"(d[13]),"+f"(d[14]),"+f"(d[15]),"+f"(d[16]),"+f"(d[17]),"+f"(d[18]),"+f"(d[19]),"+f"(d[20]),"+f"(d[21]),"+f"(d[22]),"+f"(d[23]),"+f"(d[24]),"+f"(d[25]),"+f"(d[26]),"+f"(d[27]),"+f"(d[28]),"+f"(d[29]),"+f"(d[30]),"+f"(d[31]),"+f"(d[32]),"+f"(d[33]),"+f"(d[34]),"+f"(d[35]),"+f"(d[36]),"+f"(d[37]),"+f"(d[38]),"+f"(d[39]),"+f"(d[40]),"+f"(d[41]),"+f"(d[42]),"+f"(d[43]),"+f"(d[44]),"+f"(d[45]),"+f"(d[46]),"+f"(d[47]),"+f"(d[48]),"+f"(d[49]),"+f"(d[50]),"+f"(d[51]),"+f"(d[52]),"+f"(d[53]),"+f"(d[54]),"+f"(d[55]),"+f"(d[56]),"+f"(d[57]),"+f"(d[58]),"+f"(d[59]),"+f"(d[60]),"+f"(d[61]),"+f"(d[62]),"+f"(d[63]),"+f"(d[64]),"+f"(d[65]),"+f"(d[66]),"+f"(d[67]),"+f"(d[68]),"+f"(d[69]),"+f"(d[70]),"+f"(d[71]),"+f"(d[72]),"+f"(d[73]),"+f"(d[74]),"+f"(d[75]),"+f"(d[76]),"+f"(d[77]),"+f"(d[78]),"+f"(d[79]),"+f"(d[80]),"+f"(d[81]),"+f"(d[82]),"+f"(d[83]),"+f"(d[84]),"+f"(d[85]),"+f"(d[86]),"+f"(d[87]),"+f"(d[88]),"+f"(d[89]),"+f"(d[90]),"+f"(d[91]),"+f"(d[92]),"+f"(d[93]),"+f"(d[94]),"+f"(d[95])
    : "l"(da),"l"(db),"r"(sc));
}

constexpr uint32_t XB = 28672;
constexpr uint32_t O_WQ = 5 * XB;
constexpr uint32_t O_WO = O_WQ + 32768;
constexpr uint32_t O_MIMG = O_WO + 32768;
constexpr uint32_t O_BAR = O_MIMG + 2 * 7168;
constexpr uint32_t O_TS = O_BAR + 384;
constexpr uint32_t T_SMEM = O_TS + 4096 + 128 + 1024;
constexpr uint32_t O_Z = 4 * XB;
constexpr uint32_t O_RS = O_Z + 2 * 5120;
constexpr uint32_t O_ORS = O_RS + 2 * 2048;
constexpr uint32_t O_P = O_ORS + 4 * 4096;
constexpr uint32_t O_MJ = O_P + 2 * 2560;
constexpr uint32_t O_ST = O_MJ + 2048;
constexpr uint32_t O_PC = O_ST + 2 * 5632;
constexpr uint32_t O_YB = O_PC + 128;
constexpr uint32_t O_GX = O_YB + 2 * 5120;
constexpr uint32_t O_GY = O_GX + 2 * 1792;
enum { B_X = 0, B_M = 4, B_RS = 6, B_O = 8, B_ZX = 10, B_P = 12, B_PF = 14, B_PE = 18, B_WQ = 22, B_WO = 23, B_T = 24, B_MJ = 26, B_OL = 28, B_G = 30, B_M2 = 31, B_YM = 33, B_N = 34 };
constexpr uint32_t O_DONE = O_BAR + 8 * B_N, O_C3 = O_DONE + 8, O_REDO = O_C3 + 4;
enum { N_ZM = 1, N_MOK = 2, N_W1 = 3, N_INIT = 4, N_ZX = 5, N_YX = 6, N_SS = 7, N_ST = 8 };

DEVI void gemm_m(const uint32_t (&w)[28][4], uint32_t img_lane, float (&c)[4]) {
  float acc[4][4];
#pragma unroll
  for (int i = 0; i < 4; i++) { acc[i][0] = acc[i][1] = acc[i][2] = acc[i][3] = 0.f; }
  uint32_t r[14][4];
#pragma unroll
  for (int u = 0; u < 14; u++) ldsm4(r[u], img_lane + u * 512);
#pragma unroll
  for (int u = 0; u < 14; u++) {
    mma16v(acc[(2 * u) & 3], w[2 * u][0], w[2 * u][1], w[2 * u][2], w[2 * u][3], r[u][0], r[u][1]);
    mma16v(acc[(2 * u + 1) & 3], w[2 * u + 1][0], w[2 * u + 1][1], w[2 * u + 1][2], w[2 * u + 1][3], r[u][2], r[u][3]);
  }
#pragma unroll
  for (int i = 0; i < 4; i++) c[i] = (acc[0][i] + acc[1][i]) + (acc[2][i] + acc[3][i]);
}

DEVI void gemm_x_issue(const uint32_t (&w)[28][4], uint32_t xbuf, float (&d)[16]) {
  const uint64_t b0 = desc128(xbuf, 1);
  wg_fence();
#pragma unroll
  for (int k = 0; k < 28; k++) wgmma_n32_rs(d, w[k], b0 + (uint64_t)((k >> 2) * 256 + (k & 3) * 2), k != 0);
  wg_commit();
}
DEVI void gemm_x(const uint32_t (&w)[28][4], uint32_t xbuf, float (&d)[16]) {
  gemm_x_issue(w, xbuf, d);
  wg_wait<0>();
  reg_fence(d);
}

template <int WHICH>
DEVI void build_weights(uint32_t (&w)[28][4], uint32_t sb, int& dead, int lane) {
  const uint32_t bar = sb + O_BAR;
  mbar_wait(bar + 8 * (WHICH ? B_WO : B_WQ), 0, dead);
#pragma unroll
  for (int half = 0; half < 2; half++) {
    float d[112];
#pragma unroll 1
    for (int fk = 0; fk < 4; fk++) {
      const int c = 2 * (4 * half + fk) + WHICH, st = c & 3;
      mbar_wait(bar + 8 * (B_PF + st), (c >> 2) & 1, dead);
      const uint64_t db = desc128(sb + (st + 1) * XB, 1);
      wg_fence();
#pragma unroll
      for (int kk = 0; kk < 4; kk++) {
        if (WHICH == 0) wgmma_n224_kk(d, desc128(sb + O_WQ + fk * 8192 + kk * 32, 1), db + kk * 2, (fk | kk) != 0);
        else            wgmma_n224_mk(d, desc128(sb + O_WO + (fk * 4 + kk) * 2048, 1), db + kk * 2, (fk | kk) != 0);
      }
      wg_commit();
      wg_wait<0>();
      if (lane == 0) mbar_arrive(bar + 8 * (B_PE + st));
    }
    reg_fence(d);
#pragma unroll
    for (int kk = 0; kk < 14; kk++) {
      w[14 * half + kk][0] = pack2(d[8 * kk + 0], d[8 * kk + 1]);
      w[14 * half + kk][1] = pack2(d[8 * kk + 2], d[8 * kk + 3]);
      w[14 * half + kk][2] = pack2(d[8 * kk + 4], d[8 * kk + 5]);
      w[14 * half + kk][3] = pack2(d[8 * kk + 6], d[8 * kk + 7]);
    }
  }
}

DEVI bool stale7(const uint32_t (&v)[14], uint32_t tag) {
  const uint32_t o = ((v[0] | v[1] | v[2]) | (v[3] | v[4] | v[5]) | (v[6] | v[7] | v[8])) | ((v[9] | v[10] | v[11]) | (v[12] | v[13]));
  const uint32_t a = ((v[0] & v[1] & v[2]) & (v[3] & v[4] & v[5]) & (v[6] & v[7] & v[8])) & ((v[9] & v[10] & v[11]) & (v[12] & v[13]));
  return (((o ^ tag) | (a ^ tag)) & 3u) != 0;
}
DEVI float2 add7(const uint32_t (&v)[14]) {
  float2 r;
  r.x = ((__uint_as_float(v[0]) + __uint_as_float(v[2])) + (__uint_as_float(v[4]) + __uint_as_float(v[6]))) +
        ((__uint_as_float(v[8]) + __uint_as_float(v[10])) + __uint_as_float(v[12]));
  r.y = ((__uint_as_float(v[1]) + __uint_as_float(v[3])) + (__uint_as_float(v[5]) + __uint_as_float(v[7]))) +
        ((__uint_as_float(v[9]) + __uint_as_float(v[11])) + __uint_as_float(v[13]));
  return r;
}

__global__ void __launch_bounds__(384, 1)
rmt_kernel(const __grid_constant__ CUtensorMap tmWq, const __grid_constant__ CUtensorMap tmWk,
           const __grid_constant__ CUtensorMap tmWv, const __grid_constant__ CUtensorMap tmWo,
           const __grid_constant__ CUtensorMap tmX, const __nv_bfloat16* __restrict__ x,
           const __nv_bfloat16* __restrict__ mem0, const __nv_bfloat16* __restrict__ gate_w, __nv_bfloat16* __restrict__ out) {
  extern __shared__ uint8_t smem_raw[];
  const uint32_t sb = (smem_u32(smem_raw) + 1023) & ~1023u;
  const uint32_t bar = sb + O_BAR;
  int lim = SPIN_LIMIT;
  int tid;
  uint32_t h, j;
  asm volatile("mov.u32 %0, %%tid.x;" : "=r"(tid));
  asm volatile("mov.u32 %0, %%cluster_ctarank;" : "=r"(h));
  asm volatile("mov.u32 %0, %%clusterid.x;" : "=r"(j));
  tid = __shfl_sync(0xffffffffu, tid, tid & 31);
  const int lane = tid & 31, warp = __shfl_sync(0xffffffffu, tid >> 5, 0);

  if (warp == 8) {
    if (elect()) {
#pragma unroll
      for (int i = 0; i < 4; i++) mbar_init(bar + 8 * (B_PF + i), 1);
      mbar_init(bar + 8 * B_WQ, 1);
      mbar_init(bar + 8 * B_WO, 1);
      asm volatile("fence.mbarrier_init.release.cluster;" ::: "memory");
      mbar_expect(bar + 8 * B_PF, XB);
      tma2d(sb + XB, &tmWk, h * DH, 0, bar + 8 * B_PF);
      mbar_expect(bar + 8 * B_WQ, 32768);
#pragma unroll
      for (int k = 0; k < 4; k++) tma2d(sb + O_WQ + k * 8192, &tmWq, h * DH + k * 64, j * 64, bar + 8 * B_WQ);
      mbar_expect(bar + 8 * B_WO, 32768);
      tma2d(sb + O_WO, &tmWo, j * 64, h * DH, bar + 8 * B_WO);
#pragma unroll
      for (int c = 1; c < 4; c++) {
        mbar_expect(bar + 8 * (B_PF + c), XB);
        tma2d(sb + (c + 1) * XB, (c & 1) ? &tmWv : &tmWk, h * DH + (c >> 1) * 64, 0, bar + 8 * (B_PF + c));
      }
    }
  } else if (warp == 9) {
    if (elect()) {
#pragma unroll
      for (int i = 0; i < B_N; i++)
        if (i < B_PF || (i >= B_PE && i < B_WQ) || i >= B_T) mbar_init(bar + 8 * i, i == B_M2 + 1 ? 16 : i >= B_MJ ? 1 : i >= B_T ? 3 : i >= B_PE ? 4 : i >= B_P ? 2 : i >= B_ZX ? 4 : 1);
      sts32v(sb + O_DONE, 0);
      sts32v(sb + O_C3, 0);
      sts32v(sb + O_REDO + 4, 0);
      sts32v(sb + O_DONE + 4, 0);
      mbar_expect(bar + 8 * B_X, XB);
      mbar_expect(bar + 8 * B_OL, 4096);
      mbar_expect(bar + 8 * (B_OL + 1), 4096);
#pragma unroll
      for (int i = 0; i < 2; i++) { mbar_expect(bar + 8 * (B_RS + i), 2048); mbar_expect(bar + 8 * (B_O + i), 4096); }
      asm volatile("fence.mbarrier_init.release.cluster;" ::: "memory");
    }
  }
  if (FFN_AT == 0) asm volatile("griddepcontrol.launch_dependents;");
  __syncthreads();
  cluster_arrive_relaxed();

  if (warp < 4) {
    asm volatile("setmaxnreg.inc.sync.aligned.u32 216;");
    uint32_t w[28][4];
    build_weights<0>(w, sb, lim, lane);
    cluster_wait();
    cluster_arrive_relaxed();
    uint32_t zst = sb + O_Z + ((2 * warp + ((lane >> 3) & 1)) * 40 + 8 * (lane >> 4) + (lane & 7)) * 16;
    const int mt = warp & 1, n0 = (warp >> 1) * 3;
    const int ch = lane >> 3, chp = (ch >> 1) | ((ch & 1) << 1);
    uint32_t zld = sb + O_Z + ((warp == 2 ? chp : ch) * 40 + (lane & 7)) * 16 + (warp == 2 ? 0 : n0 * 128);
    const int xrow = 16 * mt + (lane & 15);
    uint32_t xq = sb + j * 4096 + xrow * 128 + (((lane >> 4) ^ (xrow & 7)) << 4);
    uint32_t mimg = sb + O_MIMG + lane * 16, sta = sb + O_ST + (warp == 3 ? 4096 : mt * 2048) + lane * 16;
    float* p_smm = &g_smm[h][0][j][lane * 2];
    zst = keep(zst, lane); zld = keep(zld, lane); xq = keep(xq, lane); mimg = keep(mimg, lane); sta = keep(sta, lane);
    p_smm = keepp(p_smm, lane);
    {
      float d[16];
      mbar_wait(bar + 8 * B_X, 0, lim);
      gemm_x(w, sb, d);
      cluster_wait();
      stsm4t(zst + 8 * 16, pack2(d[0], d[1]), pack2(d[2], d[3]), pack2(d[4], d[5]), pack2(d[6], d[7]));
      stsm4t(zst + 24 * 16, pack2(d[8], d[9]), pack2(d[10], d[11]), pack2(d[12], d[13]), pack2(d[14], d[15]));
    }
    const uint32_t rda0 = keep(sb + O_REDO, lane);
    const uint32_t o_a = keep(mapa(sb + O_ORS + h * 256 + warp * 64 + (lane & 3) * 16, lane >> 2), lane);
    const uint32_t o_b = keep(mapa(bar + 8 * B_O, lane >> 2), lane);
    const uint32_t o_st = mapa(sb, 8) - mapa(sb, 0);
    uint32_t oh[8];
    auto token_pv = [&](int sp) {
      const uint32_t p16 = mimg + (O_P - O_MIMG) + (sp & 1) * 2560, p8 = p16 + 1024 - lane * 8, yb = sb + O_YB + (sp & 1) * 5120 + tid * 16;
      const uint4 y0 = lds_u4(yb), y1 = lds_u4(yb + 2048);
      const uint2 ymp = lds_u2(yb + 4096 - tid * 8);
      mbar_wait(bar + 8 * (B_P + (sp & 1)), (sp >> 1) & 1, lim);
      const uint2 m0 = lds_u2(p8), m1 = lds_u2(p8 + 1280);
      const uint4 p0 = lds_u4(p16), p1 = lds_u4(p16 + 512), p2 = lds_u4(p16 + 1280), p3 = lds_u4(p16 + 1280 + 512);
      float o0[4] = {0.f, 0.f, 0.f, 0.f}, o1[4] = {0.f, 0.f, 0.f, 0.f}, o2[4] = {0.f, 0.f, 0.f, 0.f}, o3[4] = {0.f, 0.f, 0.f, 0.f};
      mma8(o0, m0.x, m0.y, ymp.x);
      mma8(o1, m0.x, m0.y, ymp.y);
      mma8(o2, m1.x, m1.y, ymp.x);
      mma8(o3, m1.x, m1.y, ymp.y);
      mma16(o0, p0.x, p0.y, p0.z, p0.w, y0.x, y0.y);
      mma16(o1, p0.x, p0.y, p0.z, p0.w, y0.z, y0.w);
      mma16(o2, p2.x, p2.y, p2.z, p2.w, y0.x, y0.y);
      mma16(o3, p2.x, p2.y, p2.z, p2.w, y0.z, y0.w);
      mma16(o0, p1.x, p1.y, p1.z, p1.w, y1.x, y1.y);
      mma16(o1, p1.x, p1.y, p1.z, p1.w, y1.z, y1.w);
      mma16(o2, p3.x, p3.y, p3.z, p3.w, y1.x, y1.y);
      mma16(o3, p3.x, p3.y, p3.z, p3.w, y1.z, y1.w);
      oh[0] = pack2(o0[0], o0[1]); oh[1] = pack2(o1[0], o1[1]); oh[2] = pack2(o0[2], o0[3]); oh[3] = pack2(o1[2], o1[3]);
      oh[4] = pack2(o2[0], o2[1]); oh[5] = pack2(o3[0], o3[1]); oh[6] = pack2(o2[2], o2[3]); oh[7] = pack2(o3[2], o3[3]);
    };
    auto token_send = [&](int sp) {
      const bool last = sp >= NSEG - 2;
      const uint32_t oa = o_a + ((last ? 2 : 0) + (sp & 1)) * 4096, ob = o_b + ((last ? B_OL - B_O : 0) + (sp & 1)) * 8;
      st_async4u(oa, oh[0], oh[1], oh[2], oh[3], ob);
      st_async4u(oa + o_st, oh[4], oh[5], oh[6], oh[7], ob + o_st);
    };
#pragma unroll 1
    for (int s = 0; s < NSEG; s++) {
      const bool rec = s < NSEG - 1;
      uint32_t img = mimg + (s & 1) * 7168, zs = zst + (s & 1) * 5120, zl = zld + (s & 1) * 5120;
      uint32_t tag = ((s >> 1) + 1) & 3;
      float* smm = p_smm + (s & 1) * 448;
      pin(img); pin(zs); pin(zl); pin(tag); pinp(smm);
      uint32_t a[4][4];
      if (rec) {
        bar_arrive(N_W1, 256);
        if (warp == 2) {
          const uint32_t mj = s ? mimg + (O_MJ - O_MIMG) + (s & 1) * 1024 : img + j * 1024;
          if (s) mbar_wait(bar + 8 * (B_MJ + (s & 1)), ((s - 1) >> 1) & 1, lim);
          ldsm4(a[0], mj);
          ldsm4(a[1], mj + 512);
        }
      }
      if (s) mbar_wait(bar + 8 * (B_M + (s & 1)), ((s - 1) >> 1) & 1, lim);
      float c[4];
      uint32_t b0[4], b1[4], rda = rda0;
      while (true) {
        gemm_m(w, img, c);
        stsm2t(zs, pack2(c[0], c[1]), pack2(c[2], c[3]));
        bar_sync(N_ZM, 160);
        if (warp == 2) { ldsm4(b0, zl); ldsm4(b1, zl + 4 * 640); }
        const uint32_t redo = lds32v(rda);
        rda += 4;
        if (warp == 2) {
          const float2 e = mma_rows8(a[0], a[1], b0, b1);
          if (rec && !redo) stg2r(smm, tagf(e.x, tag), tagf(e.y, tag));
          if (lane == 0 && !redo && rec) mbar_arrive(bar + 8 * B_YM);
        }
        if (__builtin_expect(!__any_sync(0xffffffffu, redo), 1)) break;
        bar_sync(N_MOK, 128);
      }
      bar_sync(N_SS, 128);
      if (s >= 2 && rec) token_send(s - 2);
      if (warp != 2) {
        const uint32_t st = sta + (s & 1) * 5632, aq = xq + (s & 3) * XB;
        uint32_t b2[4], b3[4], b4[4], b5[4];
        ldsm4(a[0], aq); ldsm4(b0, zl); ldsm4(b2, zl + 128); ldsm4(b4, zl + 256); ldsm4(a[1], aq ^ 32);
        ldsm4(a[2], aq ^ 64); ldsm4(b1, zl + 2560); ldsm4(b3, zl + 2560 + 128); ldsm4(b5, zl + 2560 + 256); ldsm4(a[3], aq ^ 96);
        float e0[4] = {0.f, 0.f, 0.f, 0.f}, e1[4] = {0.f, 0.f, 0.f, 0.f}, e2[4] = {0.f, 0.f, 0.f, 0.f};
        mma16(e0, a[0][0], a[0][1], a[0][2], a[0][3], b0[0], b0[1]);
        mma16(e1, a[0][0], a[0][1], a[0][2], a[0][3], b2[0], b2[1]);
        mma16(e2, a[0][0], a[0][1], a[0][2], a[0][3], b4[0], b4[1]);
        mma16(e0, a[1][0], a[1][1], a[1][2], a[1][3], b0[2], b0[3]);
        mma16(e1, a[1][0], a[1][1], a[1][2], a[1][3], b2[2], b2[3]);
        mma16(e2, a[1][0], a[1][1], a[1][2], a[1][3], b4[2], b4[3]);
        mma16(e0, a[2][0], a[2][1], a[2][2], a[2][3], b1[0], b1[1]);
        mma16(e1, a[2][0], a[2][1], a[2][2], a[2][3], b3[0], b3[1]);
        mma16(e2, a[2][0], a[2][1], a[2][2], a[2][3], b5[0], b5[1]);
        mma16(e0, a[3][0], a[3][1], a[3][2], a[3][3], b1[2], b1[3]);
        mma16(e1, a[3][0], a[3][1], a[3][2], a[3][3], b3[2], b3[3]);
        mma16(e2, a[3][0], a[3][1], a[3][2], a[3][3], b5[2], b5[3]);
        sts_f4(st, e0[0], e0[1], e0[2], 1.f);
        sts_f4(st + 512, e0[3], e1[0], e1[1], 1.f);
        sts_f4(st + 1024, e1[2], e1[3], n0 ? 0.f : e2[0], 1.f);
        if (n0 == 0) sts_f4(st + 1536, e2[1], e2[2], e2[3], 1.f);
        asm volatile("fence.proxy.async.shared::cta;" ::: "memory");
        __syncwarp();
        if (lane == 0) mbar_arrive(bar + 8 * (B_T + (s & 1)));
      }
      if (!rec) {
        if (tid == 32) mbar_arrive(bar + 8 * B_YM);
        token_send(s - 2);
      }
      if (s) token_pv(s - 1);
      if (rec) bar_arrive(N_YX, 256);
      if (rec) {
        float d[16];
        mbar_wait(bar + 8 * (B_X + ((s + 1) & 3)), ((s + 1) >> 2) & 1, lim);
        bar_sync(N_ZX, 256);
        gemm_x_issue(w, sb + ((s + 1) & 3) * XB, d);
        wg_wait<0>();
        reg_fence(d);
        const uint32_t zn = zst + ((s + 1) & 1) * 5120;
        stsm4t(zn + 8 * 16, pack2(d[0], d[1]), pack2(d[2], d[3]), pack2(d[4], d[5]), pack2(d[6], d[7]));
        stsm4t(zn + 24 * 16, pack2(d[8], d[9]), pack2(d[10], d[11]), pack2(d[12], d[13]), pack2(d[14], d[15]));
      }
    }
    token_send(NSEG - 2);
    bar_sync(N_ST, 256);
    token_pv(NSEG - 1);
    token_send(NSEG - 1);
    if (lim <= 0) g_err = 1;
    __syncwarp();
    cluster_arrive_relaxed();
    cluster_wait();
  } else if (warp < 8) {
    asm volatile("setmaxnreg.inc.sync.aligned.u32 216;");
    const int wq = warp - 4;
    uint32_t w[28][4];
    build_weights<1>(w, sb, lim, lane);
    cluster_wait();
    cluster_arrive_relaxed();
    uint32_t yx[8], ym[2];
    {
      float d[16];
      mbar_wait(bar + 8 * B_X, 0, lim);
      gemm_x(w, sb, d);
#pragma unroll
      for (int i = 0; i < 8; i++) yx[i] = pack2(d[2 * i], d[2 * i + 1]);
      cluster_wait();
    }
    const int ri = lane >> 2, q = lane & 3;
    uint32_t rs_a = mapa(sb + O_RS + h * 128 + ((ri & 1) * 4 + q) * 16, 4 * wq + (ri >> 1));
    uint32_t rs_b = mapa(bar + 8 * B_RS, 4 * wq + (ri >> 1));
    uint32_t mimg = sb + O_MIMG + lane * 16, l8 = sb + lane * 8;
    for (int k = wq; k < 22; k += 4) sts_u2(sb + O_GX + k * 256 + lane * 8, 0, 0);
    asm volatile("fence.proxy.async.shared::cta;" ::: "memory");
    bar_sync(N_INIT, 160);
    const uint32_t zx = keep(sb + O_Z + (((lane >> 4) | ((lane >> 2) & 2)) * 40 + 8 + 8 * wq + (lane & 7)) * 16, lane);
    float* p_smx = keepp(&g_xacc[0][h][wq * 128 + lane * 4], lane);
    const uint32_t yb = sb + O_YB + (tid & 127) * 16;
    sts_u4(yb, yx[0], yx[4], yx[1], yx[5]);
    sts_u4(yb + 2048, yx[2], yx[6], yx[3], yx[7]);
    rs_a = keep(rs_a, lane); rs_b = keep(rs_b, lane); mimg = keep(mimg, lane); l8 = keep(l8, lane);

#pragma unroll 1
    for (int s = 0; s < NSEG; s++) {
      const bool rec = s < NSEG - 1;
      uint32_t img = mimg + (s & 1) * 7168, tag = ((s >> 1) + 1) & 3;
      uint32_t ra = rs_a + (s & 1) * 2048, rb = rs_b + (s & 1) * 8;
      pin(img); pin(tag); pin(ra); pin(rb);
      if (rec) {
        uint32_t zb0[4], zb1[4], a[2][4];
        bar_sync(N_W1, 256);
        ldsm4(zb0, zx + (s & 1) * 5120);
        ldsm4(zb1, zx + (s & 1) * 5120 + 4 * 640);
        const uint32_t mj = s ? mimg + (O_MJ - O_MIMG) + (s & 1) * 1024 : img + j * 1024;
        if (s) mbar_wait(bar + 8 * (B_MJ + (s & 1)), ((s - 1) >> 1) & 1, lim);
        ldsm4(a[0], mj);
        ldsm4(a[1], mj + 512);
        const float2 e = mma_rows8(a[0], a[1], zb0, zb1);
        asm volatile("red.relaxed.gpu.global.add.v4.f32 [%0], {%1,%2,%3,%4};" :: "l"(p_smx + (s & 7) * (NH * 512)), "f"(e.x), "f"(e.y), "f"((float)(s + 1)), "f"(0.f) : "memory");
      }
      mbar_wait(bar + 8 * B_YM, s & 1, lim);
      float c[4];
      {
        const uint64_t dm = (uint64_t)(((sb + O_MIMG + (s & 1) * 7168) >> 4) & 0x3fff) | (8ull << 16) | (8ull << 32);
        wg_fence();
#pragma unroll
        for (int k = 0; k < 28; k++) wgmma_n8_rs(c, w[k], dm + k * 16, k != 0);
        wg_commit();
      }
      float v[4][4], mxl = 0.f;
      if (rec) {
        const float full = 7.f * (s + 1);
        do {
#pragma unroll
          for (int n = 0; n < 4; n++)
            asm volatile("ld.volatile.shared.v4.f32 {%0,%1,%2,%3}, [%4];" : "=f"(v[n][0]), "=f"(v[n][1]), "=f"(v[n][2]), "=f"(v[n][3]) : "r"(mimg + (O_GY - O_MIMG) + n * 512) : "memory");
        } while (__any_sync(0xffffffffu, (v[0][2] + v[0][3] != full) | (v[1][2] + v[1][3] != full) | (v[2][2] + v[2][3] != full) | (v[3][2] + v[3][3] != full)) && --lim > 0);
        sts32v(sb + O_DONE + 4, s + 1);
        mxl = fmaxf(fmaxf(fmaxf(v[0][0], v[0][1]), fmaxf(v[1][0], v[1][1])), fmaxf(fmaxf(v[2][0], v[2][1]), fmaxf(v[3][0], v[3][1])));
      }
      wg_wait<0>();
      reg_fence(c);
      ym[0] = pack2(c[0], c[1]);
      ym[1] = pack2(c[2], c[3]);
      if (rec) {
        uint32_t vm[14];
        const uint32_t gx = l8 + O_GX + (s & 1) * 1792;
        do {
#pragma unroll
          for (int k = 0; k < 7; k++) asm volatile("ld.volatile.shared.v2.u32 {%0,%1}, [%2];" : "=r"(vm[2 * k]), "=r"(vm[2 * k + 1]) : "r"(gx + k * 256) : "memory");
        } while (__any_sync(0xffffffffu, stale7(vm, tag)) && --lim > 0);
        sts32v(sb + O_DONE, s + 1);
        const float2 sm = add7(vm);
        const float mx = qmax(fmaxf(mxl, fmaxf(sm.x, sm.y)));
        const float nb = -mx * SC2;
        uint32_t pa[4];
        float l = 0.f;
#pragma unroll
        for (int n = 0; n < 4; n++) {
          const float p0 = ex2(fmaf(v[n][0], SC2, nb)), p1 = ex2(fmaf(v[n][1], SC2, nb));
          l += p0 + p1;
          pa[n] = pack2(p0, p1);
        }
        float o0[4] = {0.f, 0.f, 0.f, 0.f}, o1[4] = {0.f, 0.f, 0.f, 0.f}, u0[4] = {0.f, 0.f, 0.f, 0.f}, u1[4] = {0.f, 0.f, 0.f, 0.f};
        mma16v(o0, pa[0], pa[1], pa[2], pa[3], yx[0], yx[4]);
        mma16v(o1, pa[0], pa[1], pa[2], pa[3], yx[1], yx[5]);
        mma16v(u0, pa[0], pa[1], pa[2], pa[3], yx[2], yx[6]);
        mma16v(u1, pa[0], pa[1], pa[2], pa[3], yx[3], yx[7]);
        const float p0 = ex2(fmaf(sm.x, SC2, nb)), p1 = ex2(fmaf(sm.y, SC2, nb));
        const uint32_t pp = pack2(p0, p1);
        mma8v(o0, pp, pp, ym[0]);
        mma8v(o1, pp, pp, ym[1]);
        const float inv = rcp(qsum(l + (p0 + p1)));
        st_async4(ra, (o0[0] + u0[2]) * inv, (o0[1] + u0[3]) * inv, (o1[0] + u1[2]) * inv, (o1[1] + u1[3]) * inv, rb);
      }
      sts_u2(yb + 4096 - (tid & 127) * 8 + (s & 1) * 5120, ym[0], ym[1]);
      if (!rec) bar_arrive(N_ST, 256);
      if (rec) {
        bar_arrive(N_ZX, 256);
      }
      if (rec) {
        float d[16];
        mbar_wait(bar + 8 * (B_X + ((s + 1) & 3)), ((s + 1) >> 2) & 1, lim);
        gemm_x(w, sb + ((s + 1) & 3) * XB, d);
#pragma unroll
        for (int i = 0; i < 8; i++) yx[i] = pack2(d[2 * i], d[2 * i + 1]);
        bar_sync(N_YX, 256);
        sts_u4(yb + ((s + 1) & 1) * 5120, yx[0], yx[4], yx[1], yx[5]);
        sts_u4(yb + ((s + 1) & 1) * 5120 + 2048, yx[2], yx[6], yx[3], yx[7]);
      }
    }
    if (lim <= 0) g_err = 1;
    __syncwarp();
    cluster_arrive_relaxed();
    cluster_wait();
  } else {
    asm volatile("setmaxnreg.dec.sync.aligned.u32 72;");
    if (warp == 8) {
      const int u = (lane & 15) >> 1, nt = lane & 1;
      uint8_t* gm0 = &g_mslot[0][(8 * j + 2 * (h >> 2) + nt) * 128 + (2 * (h & 3) + (u >> 2)) * 16 + (u & 3) * 4];
#pragma unroll
      for (int k = 0; k < 3; k++) asm volatile("st.relaxed.gpu.global.u32 [%0], 0xffffffff;" :: "l"(gm0 + k * 8192) : "memory");
      cluster_wait();
      if (lane == 0) {
        int lim1 = SPIN_LIMIT;
        if (h < 7) tma2d_mc(sb + h * 4096, &tmX, h * 64, 0, bar + 8 * B_X);
#pragma unroll 1
        for (int c = 4; c < 16; c++) {
          const int st = c & 3;
          mbar_wait1(bar + 8 * (B_PE + st), ((c >> 2) - 1) & 1, lim1);
          if (c == FFN_AT) asm volatile("griddepcontrol.launch_dependents;");
          mbar_expect(bar + 8 * (B_PF + st), XB);
          tma2d(sb + (st + 1) * XB, (c & 1) ? &tmWv : &tmWk, h * DH + ((c >> 1) & 3) * 64, (c >> 3) * 224, bar + 8 * (B_PF + st));
        }
      }
      __syncwarp();
      cluster_arrive();
      cluster_wait();
      if (lane == 0) {
        for (int k = 1; k < 3; k++) {
          mbar_expect(bar + 8 * (B_X + k), XB);
          if (h < 7) tma2d_mc(sb + k * XB + h * 4096, &tmX, h * 64, k * 32, bar + 8 * (B_X + k));
        }
      }
      uint32_t chk = sb + O_MIMG + lane * 32 + (lane >> 2) * 4, rs0 = sb + O_RS + (lane >> 4) * 1024 + (lane & 15) * 8;
      const uint8_t* gnear = &g_mslot[0][0];
      const uint32_t pc_st = keep(sb + O_PC + (nt * 2 + (u >> 2)) * 16 + (u & 3) * 4, lane);
      const uint32_t mj_a = keep(mapa(sb + O_MJ + (2 * (h >> 2) + ((lane >> 1) & 1)) * 128 + (2 * (h & 3) + (lane & 1)) * 16, lane >> 2), lane);
      const uint32_t mj_b = keep(mapa(bar + 8 * B_MJ, lane >> 2), lane), mj_st = mapa(sb, 8) - mapa(sb, 0);
      chk = keep(chk, lane); rs0 = keep(rs0, lane); gm0 = keepp(gm0, lane);
      const uint32_t m2r = mapa(bar + 8 * (B_M2 + 1), lane & 15);
      auto cl_sync_arrive = [&](uint32_t a) { if (lane < 16) asm volatile("mbarrier.arrive.relaxed.cluster.shared::cluster.b64 _, [%0];" :: "r"(a) : "memory"); __syncwarp(); };
      const uint8_t* p_gsrc = reinterpret_cast<const uint8_t*>(&g_smm[h][0][0][0]);
      bar_sync(N_INIT, 160);
      uint32_t m2p = 0;
      int s3 = 0;
#pragma unroll 1
      for (int s = 0; s < NSEG; s++) {
        uint32_t ck = chk + (s & 1) * 7168;
        pin(ck);
        bool redo = false;
        if (s) {
          mbar_wait(bar + 8 * (B_M + (s & 1)), ((s - 1) >> 1) & 1, lim);
          while (true) {
            uint32_t v[7];
#pragma unroll
            for (int k = 0; k < 7; k++) v[k] = lds32v(ck + k * 1024);
            const uint32_t mx = __vimax3_u32(__vimax3_u32(v[0], v[1], v[2]), __vimax3_u32(v[3], v[4], v[5]), v[6]);
            if (__builtin_expect(!__any_sync(0xffffffffu, mx == 0xffffffffu) || lim <= 0, 1)) break;
            redo = true;
            cl_sync_arrive(m2r);
            if (elect()) mbar_expect(bar + 8 * B_M2, 7168);
            mbar_wait(bar + 8 * (B_M2 + 1), m2p, lim);
            if (elect()) bulk_mc(sb + O_MIMG + (s & 1) * 7168 + h * 448, gnear + s3 * 8192 + h * 448, 448, bar + 8 * B_M2);
            mbar_wait(bar + 8 * B_M2, m2p, lim);
            m2p ^= 1;
          }
        }
        sts32v(sb + O_REDO, redo);
        bar_sync(N_ZM, 160);
        if (redo) bar_sync(N_ZM, 160);
        if (s == NSEG - 1) break;
        {
          const uint32_t tz = clk();
          const uint8_t* gsrc = p_gsrc + (s & 1) * 1792;
          asm volatile("{\n.reg .pred e, p, q, x;\n.reg .u32 t, u, f0, f1, td, n;\n.reg .u64 c;\n"
                       "elect.sync _|e, 0xffffffff;\nmov.u32 td, %9;\n"
                       "@e mbarrier.expect_tx.relaxed.cta.shared::cta.b64 [%3], 2048;\n"
                       "@e cp.async.bulk.shared::cluster.global.mbarrier::complete_tx::bytes [%6], [%7], 2048, [%3];\n"
                       "setp.eq.u32 x, td, td;\n"
                       "REFRESH:\nmov.u64 c, %%clock64;\nmov.b64 {t, u}, c;\nsub.u32 t, t, %1;\nsetp.lt.u32 p, t, td;\n@p bra.uni REFRESH;\n"
                       "selp.u32 n, 3840, 1792, x;\nand.pred q, e, x;\n"
                       "@e mbarrier.expect_tx.relaxed.cta.shared::cta.b64 [%3], n;\n"
                       "@e cp.async.bulk.shared::cluster.global.mbarrier::complete_tx::bytes [%4], [%5], 1792, [%3];\n"
                       "@q cp.async.bulk.shared::cluster.global.mbarrier::complete_tx::bytes [%6], [%7], 2048, [%3];\n"
                       "ld.volatile.shared.v2.u32 {f0, f1}, [%8];\nadd.u32 td, td, %10;\nsub.s32 %0, %0, 1;\n"
                       "setp.le.s32 x, f1, %2;\nsetp.le.s32 p, f0, %2;\nsetp.gt.and.s32 p, %0, 0, p;\n@p bra.uni REFRESH;\n}"
                       : "+r"(lim)
                       : "r"(tz), "r"(s), "r"(bar + 8 * B_G), "r"(sb + O_GX + (s & 1) * 1792), "l"(gsrc), "r"(sb + O_GY), "l"(&g_xacc[s & 7][h][0]),
                         "r"(sb + O_DONE), "n"(D_S), "n"(D_SS)
                       : "memory");
        }
        while (__any_sync(0xffffffffu, (int)lds32v(sb + O_C3) < s - 2) && --lim > 0) {}
        const int s3n = s3 == 2 ? 0 : s3 + 1;
        uint32_t rb = rs0 + (s & 1) * 2048;
        uint8_t* gm = gm0 + s3n * 8192;
        const uint32_t mdst = sb + O_MIMG + ((s + 1) & 1) * 7168 + h * 448, mb = bar + 8 * (B_M + ((s + 1) & 1));
        const uint8_t* msrc = gnear + s3n * 8192 + h * 448;
        s3 = s3n;
        pin(rb); pinp(gm);
        mbar_wait(bar + 8 * (B_RS + (s & 1)), (s >> 1) & 1, lim);
        uint2 v[8];
#pragma unroll
        for (int k = 0; k < 8; k++) v[k] = lds_u2(rb + k * 128);
        float s0 = ((__uint_as_float(v[0].x) + __uint_as_float(v[1].x)) + (__uint_as_float(v[2].x) + __uint_as_float(v[3].x))) +
                   ((__uint_as_float(v[4].x) + __uint_as_float(v[5].x)) + (__uint_as_float(v[6].x) + __uint_as_float(v[7].x)));
        float s1 = ((__uint_as_float(v[0].y) + __uint_as_float(v[1].y)) + (__uint_as_float(v[2].y) + __uint_as_float(v[3].y))) +
                   ((__uint_as_float(v[4].y) + __uint_as_float(v[5].y)) + (__uint_as_float(v[6].y) + __uint_as_float(v[7].y)));
        s0 += __shfl_xor_sync(0xffffffffu, s0, 16);
        s1 += __shfl_xor_sync(0xffffffffu, s1, 16);
        const uint32_t mw = pack2(s0, s1);
        if (lane < 16) asm volatile("st.relaxed.gpu.global.u32 [%0], %1;" :: "l"(gm), "r"(mw) : "memory");
        const uint32_t tm = clk();
        sts32v(pc_st, mw);
        __syncwarp();
        const float4 pc = lds_f4(sb + O_PC + (lane & 3) * 16);
        if (s < NSEG - 2) {
          const uint32_t o = ((s + 1) & 1) * 1024, ob = ((s + 1) & 1) * 8;
          st_async4(mj_a + o, pc.x, pc.y, pc.z, pc.w, mj_b + ob);
          st_async4(mj_a + o + mj_st, pc.x, pc.y, pc.z, pc.w, mj_b + ob + mj_st);
        }
        const bool el = elect();
        if (el) mbar_expect(bar + 8 * (B_RS + (s & 1)), 2048);
        delay_until(tm, D_M);
        if (el) bulk_mc(mdst, msrc, 448, mb);
      }
      if (elect()) mbar_arrive(bar + 8 * B_G);
      mbar_wait(bar + 8 * B_G, 0, lim);
    } else if (warp < 11) {
      const int mt = warp - 9, q = lane & 3;
#pragma unroll
      for (int t = mt * 32 + lane; t < 448; t += 64) {
        const uint4 v = *reinterpret_cast<const uint4*>(mem0 + (t & 7) * DM + (t >> 3) * 8);
        sts_u4(sb + O_MIMG + t * 16, v.x, v.y, v.z, v.w);
      }
      asm volatile("fence.proxy.async.shared::cta;" ::: "memory");
      __syncwarp();
      cluster_wait();
      cluster_arrive();
      cluster_wait();
      uint8_t* gm0 = &g_mslot[0][(8 * j + 2 * (h >> 2) + (lane & 1)) * 128 + (2 * (h & 3) + ((lane >> 3) & 1)) * 16 + ((lane >> 1) & 3) * 4];
      int s3p = 2;
#pragma unroll 1
      for (int s = 0; s < NSEG; s++) {
        mbar_wait(bar + 8 * (B_T + (s & 1)), (s >> 1) & 1, lim);
        if (mt == 1 && s < NSEG - 1) {
          if (elect()) {
            mbar_expect(bar + 8 * (B_M + ((s + 1) & 1)), 7168);
            if (s < NSEG - 2) mbar_expect(bar + 8 * (B_MJ + ((s + 1) & 1)), 1024);
            if (s >= 1 && s + 2 < NSEG) {
              mbar_expect(bar + 8 * (B_X + ((s + 2) & 3)), XB);
              if (h < 7) tma2d_mc(sb + ((s + 2) & 3) * XB + h * 4096, &tmX, h * 64, (s + 2) * 32, bar + 8 * (B_X + ((s + 2) & 3)));
            }
          }
          asm volatile("st.relaxed.gpu.global.u32 [%0], 0xffffffff;" :: "l"(gm0 + s3p * 8192) : "memory");
          s3p = s3p == 2 ? 0 : s3p + 1;
        }
        const uint32_t t0 = clk();
        if (mt == 0 && elect()) {
          asm volatile("cp.reduce.async.bulk.global.shared::cta.bulk_group.add.f32 [%0], [%1], 5632;" :: "l"(&g_sacc[s & 7][h][0]), "r"(sb + O_ST + (s & 1) * 5632) : "memory");
          asm volatile("cp.async.bulk.commit_group;" ::: "memory");
          asm volatile("cp.async.bulk.wait_group.read 0;" ::: "memory");
        }
        __syncwarp();
        if (s < NSEG - 1) { mbar_wait(bar + 8 * (B_RS + (s & 1)), (s >> 1) & 1, lim);
          delay_until(t0, D_T); }
        else delay_until(t0, D_TL);
        const float4* sp = reinterpret_cast<const float4*>(&g_sacc[s & 7][h][mt * 512 + lane * 4]);
        float u[7][4];
        bool stale;
        do {
          stale = false;
#pragma unroll
          for (int c = 0; c < 7; c++) {
            u[c][0] = u[c][1] = u[c][2] = 0.f; u[c][3] = 7.f;
            if (c < 4 || mt)
              asm volatile("ld.relaxed.gpu.global.v4.f32 {%0,%1,%2,%3}, [%4];" : "=f"(u[c][0]), "=f"(u[c][1]), "=f"(u[c][2]), "=f"(u[c][3]) : "l"(sp + c * 32) : "memory");
          }
#pragma unroll
          for (int c = 0; c < 7; c++) stale |= u[c][3] != 7.f;
        } while (__any_sync(0xffffffffu, stale) && --lim > 0);
        uint32_t pk[2][5];
        float v[2][10];
#pragma unroll
        for (int e = 0; e < 10; e++) {
          const int i = 4 * (e >> 1) + (e & 1);
          v[0][e] = u[i / 3][i % 3];
          v[1][e] = u[(i + 2) / 3][(i + 2) % 3];
        }
#pragma unroll
        for (int rg = 0; rg < 2; rg++) {
          const int row = 16 * mt + 8 * rg + (lane >> 2);
#pragma unroll
          for (int e = 2; e < 10; e++)
            if (8 * ((e >> 1) - 1) + 2 * q + (e & 1) > row) v[rg][e] = MASKV;
          float mx = v[rg][0];
#pragma unroll
          for (int e = 1; e < 10; e++) mx = fmaxf(mx, v[rg][e]);
          mx = qmax(mx);
          const float nb = -mx * SC2;
          float l = 0.f;
#pragma unroll
          for (int e = 0; e < 10; e++) { v[rg][e] = ex2(fmaf(v[rg][e], SC2, nb)); l += v[rg][e]; }
          const float inv = rcp(qsum(l));
#pragma unroll
          for (int n = 0; n < 5; n++) pk[rg][n] = pack2(v[rg][2 * n] * inv, v[rg][2 * n + 1] * inv);
        }
        const uint32_t pb = sb + O_P + (s & 1) * 2560 + mt * 1280;
        sts_u4(pb + lane * 16, pk[0][1], pk[1][1], pk[0][3], pk[1][3]);
        sts_u4(pb + 512 + lane * 16, pk[0][2], pk[1][2], pk[0][4], pk[1][4]);
        sts_u2(pb + 1024 + lane * 8, pk[0][0], pk[1][0]);
        __syncwarp();
        if (lane == 0) mbar_arrive(bar + 8 * (B_P + (s & 1)));
        if (j + 7 * mt < 11) asm volatile("st.relaxed.gpu.global.v4.f32 [%0], {%1,%1,%1,%1};" :: "l"(&g_sacc[(s + 4) & 7][h][(j + 7 * mt) * 128 + lane * 4]), "f"(0.f) : "memory");
      }
    } else {
      const int t1 = lane >> 4, l16 = lane & 15;
      uint2 gw[7];
#pragma unroll
      for (int k = 0; k < 7; k++) gw[k] = *reinterpret_cast<const uint2*>(gate_w + (k * 16 + l16) * 4);
      const int col = j * 64 + ((lane >> 2) & 3) * 16 + (lane & 3) * 2;
      const uint32_t epoch = ldg1r(&g_ticket[0]) / 112 + 1;
      __syncwarp();
      cluster_wait();
      cluster_arrive();
      cluster_wait();
      const int trow = 16 * (h >> 3) + (h & 7) + 8 * t1;
      const uint32_t xg = sb + trow * 128 + (((l16 >> 1) ^ (trow & 7)) << 4) + (l16 & 1) * 8;
      auto gate = [&](int sg) {
        mbar_wait(bar + 8 * (B_X + (sg & 3)), (sg >> 2) & 1, lim);
        float z = 0.f, z2 = 0.f;
#pragma unroll
        for (int k = 0; k < 7; k++) {
          const uint2 xv = lds_u2(xg + (sg & 3) * XB + k * 4096);
          z = fmaf(bf_lo(xv.x), bf_lo(gw[k].x), z); z2 = fmaf(bf_hi(xv.x), bf_hi(gw[k].x), z2);
          z = fmaf(bf_lo(xv.y), bf_lo(gw[k].y), z); z2 = fmaf(bf_hi(xv.y), bf_hi(gw[k].y), z2);
        }
        z += z2;
#pragma unroll
        for (int o = 1; o < 16; o <<= 1) z += __shfl_xor_sync(0xffffffffu, z, o);
        return rcp(1.f + ex2(-1.4426950408889634f * z));
      };
      float4 pa4 = make_float4(0.f, 0.f, 0.f, 0.f);
      bool pend = false;
      auto finish = [&](int sg) {
        if (ldg1r(&g_bflag[sg >> 1][j >> 2][0]) == epoch) {
          const int o = (sg * 32 + trow) * DM + col;
          uint32_t b0, b1, b2, b3;
          ldg2r(b0, b1, g_b + o); ldg2r(b2, b3, g_b + o + 8);
          uint32_t* op = reinterpret_cast<uint32_t*>(out + o);
          op[0] = pack2(pa4.x + __uint_as_float(b0), pa4.y + __uint_as_float(b1));
          op[4] = pack2(pa4.z + __uint_as_float(b2), pa4.w + __uint_as_float(b3));
        }
      };
      const uint32_t* fl0 = keepp(&g_bflag[0][j >> 2][0], lane);
      uint32_t fnext = 0;
      float g1 = 0.f, g2 = 0.f;
#pragma unroll 1
      for (int s = -2; s < NSEG; s++) {
        if (s >= 0) {
        const int tok = s * 32 + trow;
        const bool have_b = fnext == epoch;
        fnext = ldg1r(fl0 + (min(s + 1, NSEG - 1) >> 1) * 16);
        const float* bp = &g_b[tok * DM + col];
        uint32_t b0 = 0, b1 = 0, b2 = 0, b3 = 0;
        if (have_b) { ldg2r(b0, b1, bp); ldg2r(b2, b3, bp + 8); }
        const bool last = s >= NSEG - 2;
        mbar_wait(bar + 8 * ((last ? B_OL : B_O) + (s & 1)), last ? 0 : (s >> 1) & 1, lim);
        if (lane < 19 && j * 19 + lane < 128)
          asm volatile("st.relaxed.gpu.global.v4.f32 [%0], {%1,%1,%1,%1};" :: "l"(&g_xacc[s & 7][h][(j * 19 + lane) * 4]), "f"(0.f) : "memory");
        const float g = g1;
        const uint32_t ob = sb + O_ORS + ((last ? 2 : 0) + (s & 1)) * 4096 + t1 * 2048 + l16 * 16;
        float e[8] = {0.f, 0.f, 0.f, 0.f, 0.f, 0.f, 0.f, 0.f};
#pragma unroll 2
        for (int k = 0; k < 8; k++) {
          const uint4 c = lds_u4(ob + k * 256);
          e[0] += bf_lo(c.x); e[1] += bf_hi(c.x); e[2] += bf_lo(c.y); e[3] += bf_hi(c.y);
          e[4] += bf_lo(c.z); e[5] += bf_hi(c.z); e[6] += bf_lo(c.w); e[7] += bf_hi(c.w);
        }
        float4 a;
        a.x = g * ((t1 ? e[4] : e[0]) + __shfl_xor_sync(0xffffffffu, t1 ? e[0] : e[4], 16));
        a.y = g * ((t1 ? e[5] : e[1]) + __shfl_xor_sync(0xffffffffu, t1 ? e[1] : e[5], 16));
        a.z = g * ((t1 ? e[6] : e[2]) + __shfl_xor_sync(0xffffffffu, t1 ? e[2] : e[6], 16));
        a.w = g * ((t1 ? e[7] : e[3]) + __shfl_xor_sync(0xffffffffu, t1 ? e[3] : e[7], 16));
        __syncwarp();
        if (lane == 0 && s < NSEG - 4) mbar_expect(bar + 8 * (B_O + (s & 1)), 4096);
        float* sp = &g_stash[tok * DM + col];
        stg2r(sp, tagf(a.x, epoch & 3), tagf(a.y, epoch & 3));
        stg2r(sp + 8, tagf(a.z, epoch & 3), tagf(a.w, epoch & 3));
        if (have_b) {
          uint32_t* op = reinterpret_cast<uint32_t*>(out + tok * DM + col);
          op[0] = pack2(a.x + __uint_as_float(b0), a.y + __uint_as_float(b1));
          op[4] = pack2(a.z + __uint_as_float(b2), a.w + __uint_as_float(b3));
        }
        if (pend) { if (s >= NSEG - 2) __threadfence(); finish(s - 1); }
        pend = !have_b;
        pa4 = a;
        }
        g1 = g2;
        if (s + 2 < NSEG) g2 = gate(s + 2);
        if (lane == 0 && s >= 0) sts32v(sb + O_C3, s + 1);
      }
      if (pend) { __threadfence(); finish(NSEG - 1); }
      if (lane == 0) atomicAdd(&g_ticket[0], 1);
    }
    if (lim <= 0) g_err = 1;
    __syncwarp();
    cluster_arrive_relaxed();
    cluster_wait();
  }
}

constexpr uint32_t F_STAGE = 49152, F_BAR = 4 * F_STAGE, F_G = F_BAR + 128, F_STG = F_G + 512, F_SMEM = F_STG + 8 * 2304 + 1024;

DEVI void release_stage(uint32_t sb, int st, int lane) {
  if (lane < 2) asm volatile("mbarrier.arrive.relaxed.cluster.shared::cluster.b64 _, [%0];" :: "r"(mapa(sb + F_BAR + 32 + 8 * st, lane)) : "memory");
}
template <int N>
DEVI void ffn_tile(float (&d)[N / 2], uint32_t sb, int wg, int nk, int& it, int& dead, int lane) {
#pragma unroll 1
  for (int k = 0; k < nk; k++, it++) {
    const int st = it & 3;
    mbar_wait(sb + F_BAR + 8 * st, (it >> 2) & 1, dead);
    const uint64_t da = desc128(sb + st * F_STAGE + wg * 8192, 1), db = desc128(sb + st * F_STAGE + 16384, 512);
    wg_fence();
#pragma unroll
    for (int kk = 0; kk < 4; kk++) {
      if constexpr (N == 256) wgmma_n256_kn(d, da + kk * 2, db + kk * 128, (k | kk) != 0);
      else                    wgmma_n192_kn(d, da + kk * 2, db + kk * 128, (k | kk) != 0);
    }
    wg_commit();
    if (k) { wg_wait<1>(); release_stage(sb, (it - 1) & 3, lane); }
  }
  wg_wait<0>();
  release_stage(sb, (it - 1) & 3, lane);
  reg_fence(d);
}

template <int NJ>
DEVI void ffn_finish(float (&d)[NJ * 32], float g0, float g1, uint32_t sb, int r0, int row, int j0, uint32_t epoch,
                     __nv_bfloat16* __restrict__ out, int tid) {
  const int wg = tid >> 7, t = tid & 127, off = (r0 + row) * DM + j0 * 64 + 2 * (tid & 3);
#pragma unroll
  for (int n = 0; n < NJ * 8; n++) {
    d[4 * n] *= g0; d[4 * n + 1] *= g0; d[4 * n + 2] *= g1; d[4 * n + 3] *= g1;
    *reinterpret_cast<float2*>(g_b + off + n * 8) = make_float2(d[4 * n], d[4 * n + 1]);
    *reinterpret_cast<float2*>(g_b + off + 8 * DM + n * 8) = make_float2(d[4 * n + 2], d[4 * n + 3]);
  }
  asm volatile("fence.release.gpu;" ::: "memory");
  bar_sync(2 + wg, 128);
  if (t == 0) {
    asm volatile("st.relaxed.gpu.global.u32 [%0], %1;" :: "l"(&g_bflag[(r0 >> 6) + wg][j0 >> 2][0]), "r"(epoch) : "memory");
    __threadfence();
  }
  bar_sync(2 + wg, 128);
#pragma unroll
  for (int n0 = 0; n0 < NJ * 8; n0 += 8) {
    uint32_t a[8][4];
#pragma unroll
    for (int n = 0; n < 8; n++) { ldg2r(a[n][0], a[n][1], g_stash + off + (n0 + n) * 8); ldg2r(a[n][2], a[n][3], g_stash + off + 8 * DM + (n0 + n) * 8); }
#pragma unroll
    for (int n = 0; n < 8; n++)
#pragma unroll
      for (int half = 0; half < 2; half++)
        if (((a[n][2 * half] ^ epoch) & 3) == 0)
          *reinterpret_cast<uint32_t*>(out + off + half * 8 * DM + (n0 + n) * 8) =
              pack2(__uint_as_float(a[n][2 * half]) + d[4 * (n0 + n) + 2 * half], __uint_as_float(a[n][2 * half + 1]) + d[4 * (n0 + n) + 2 * half + 1]);
  }
}

__global__ void __launch_bounds__(384, 1)
ffn_kernel(const __grid_constant__ CUtensorMap tmX, const __grid_constant__ CUtensorMap tmW1,
           const __grid_constant__ CUtensorMap tmH, const __grid_constant__ CUtensorMap tmW2,
           const __nv_bfloat16* __restrict__ x, const __nv_bfloat16* __restrict__ gate_w, __nv_bfloat16* __restrict__ out) {
  extern __shared__ uint8_t smem_raw[];
  const uint32_t sb = (smem_u32(smem_raw) + 1023) & ~1023u;
  const uint32_t hbar = sb + F_BAR + 64;
  int dead = SPIN_LIMIT;
  const int tid = threadIdx.x, lane = tid & 31, warp = __shfl_sync(0xffffffffu, tid >> 5, 0), r0 = blockIdx.x * 128;
  if (tid == 0) {
    for (int i = 0; i < 4; i++) { mbar_init(sb + F_BAR + 8 * i, 1); mbar_init(sb + F_BAR + 32 + 8 * i, 16); }
    mbar_init(hbar, 256);
    asm volatile("fence.mbarrier_init.release.cluster;" ::: "memory");
    asm volatile("fence.proxy.async.shared::cta;" ::: "memory");
  }
  __syncthreads();
  cluster_arrive_relaxed();
  cluster_wait();
  if (warp >= 8) {
    asm volatile("setmaxnreg.dec.sync.aligned.u32 56;");
    if (tid == 256) {
      int it = 0;
#pragma unroll 1
      for (int t = 0; t < 9; t++) {
        const int nk = t < 7 ? 7 : 28, nb = t < 8 ? 4 : 3;
        if (t == 7) mbar_wait1(hbar, 0, dead);
#pragma unroll 1
        for (int k = 0; k < nk; k++, it++) {
          const int st = it & 3;
          const uint32_t fb = sb + F_BAR + 8 * st, a = sb + st * F_STAGE;
          if (it >= 4) mbar_wait1(fb + 32, ((it >> 2) - 1) & 1, dead);
          mbar_expect(fb, 16384 + nb * 8192);
          tma2d(a, t < 7 ? &tmX : &tmH, k * 64, r0, fb);
          for (int b = blockIdx.x & 1; b < nb; b += 2)
            asm volatile("cp.async.bulk.tensor.2d.shared::cluster.global.mbarrier::complete_tx::bytes.multicast::cluster [%0], [%1, {%2, %3}], [%4], %5;"
                         :: "r"(a + 16384 + b * 8192), "l"(t < 7 ? &tmW1 : &tmW2), "r"((t < 7 ? t : t - 7) * 256 + b * 64), "r"(k * 64), "r"(fb), "h"((uint16_t)3) : "memory");
        }
      }
    } else if (warp > 8) {
      const int l16 = lane & 15;
      for (int r = (warp - 9) * 2 + (lane >> 4); r < 132; r += 6) {
        const int rr = r < 128 ? r : 127;
        float z = 0.f;
#pragma unroll
        for (int k = 0; k < 7; k++) {
          const uint2 xv = *reinterpret_cast<const uint2*>(x + (r0 + rr) * DM + (k * 16 + l16) * 4);
          const uint2 gv = *reinterpret_cast<const uint2*>(gate_w + (k * 16 + l16) * 4);
          z = fmaf(bf_lo(xv.x), bf_lo(gv.x), z); z = fmaf(bf_hi(xv.x), bf_hi(gv.x), z);
          z = fmaf(bf_lo(xv.y), bf_lo(gv.y), z); z = fmaf(bf_hi(xv.y), bf_hi(gv.y), z);
        }
#pragma unroll
        for (int o = 1; o < 16; o <<= 1) z += __shfl_xor_sync(0xffffffffu, z, o);
        if (l16 == 0) sts32v(sb + F_G + rr * 4, __float_as_uint(1.f - rcp(1.f + ex2(-1.4426950408889634f * z))));
      }
      __syncwarp();
      bar_arrive(1, 352);
    }
    __syncwarp();
    cluster_arrive_relaxed();
    cluster_wait();
  } else {
    asm volatile("setmaxnreg.inc.sync.aligned.u32 224;");
    const int wg = warp >> 2, row = wg * 64 + (warp & 3) * 16 + (lane >> 2);
    const uint32_t epoch = (ldg1r(&g_ticket[1]) >> 4) + 1;
    int it = 0;
#pragma unroll 1
    for (int t = 0; t < 7; t++) {
      float d[128];
      ffn_tile<256>(d, sb, wg, 7, it, dead, lane);
      const uint32_t stg = sb + F_STG + warp * 2304;
      __nv_bfloat16* hp = g_h + (size_t)(r0 + warp * 16 + (lane >> 3)) * DFF + t * 256 + (lane & 7) * 8;
#pragma unroll
      for (int hf = 0; hf < 4; hf++) {
#pragma unroll
        for (int n = 0; n < 8; n += 2) {
          const float* e = d + 32 * hf + 4 * n;
          asm volatile("stmatrix.sync.aligned.m8n8.x4.shared.b16 [%0], {%1,%2,%3,%4};"
                       :: "r"(stg + (lane & 15) * 144 + (n + (lane >> 4)) * 16), "r"(pack2(fmaxf(e[0], 0.f), fmaxf(e[1], 0.f))), "r"(pack2(fmaxf(e[2], 0.f), fmaxf(e[3], 0.f))),
                          "r"(pack2(fmaxf(e[4], 0.f), fmaxf(e[5], 0.f))), "r"(pack2(fmaxf(e[6], 0.f), fmaxf(e[7], 0.f))) : "memory");
        }
        __syncwarp();
#pragma unroll
        for (int r = 0; r < 4; r++) {
          const uint4 v = lds_u4(stg + (4 * r + (lane >> 3)) * 144 + (lane & 7) * 16);
          *reinterpret_cast<uint4*>(hp + (size_t)4 * r * DFF + hf * 64) = v;
        }
        __syncwarp();
      }
    }
    __threadfence();
    asm volatile("fence.proxy.async;" ::: "memory");
    mbar_arrive(hbar);
    bar_sync(1, 352);
    const float g0 = __uint_as_float(lds32v(sb + F_G + row * 4)), g1 = __uint_as_float(lds32v(sb + F_G + row * 4 + 32));
    {
      float d[128];
      ffn_tile<256>(d, sb, wg, 28, it, dead, lane);
      ffn_finish<4>(d, g0, g1, sb, r0, row, 0, epoch, out, tid);
    }
    {
      float d[96];
      ffn_tile<192>(d, sb, wg, 28, it, dead, lane);
      ffn_finish<3>(d, g0, g1, sb, r0, row, 4, epoch, out, tid);
    }
    bar_sync(1, 256);
    if (tid == 0) atomicAdd(&g_ticket[1], 1);
    if (dead <= 0) g_err = 1;
    cluster_arrive_relaxed();
    cluster_wait();
  }
}

__device__ float g_fmem[8 * DM];
__global__ void fb_qkv(const __nv_bfloat16* x, const __nv_bfloat16* mem0, const __nv_bfloat16* wq, const __nv_bfloat16* wk,
                       const __nv_bfloat16* wv, int s) {
  __shared__ __nv_bfloat16 hs[40 * DM];
  for (int i = threadIdx.x; i < 40 * DM; i += 128)
    hs[i] = i >= 8 * DM ? x[s * 32 * DM + i - 8 * DM] : s ? __float2bfloat16(g_fmem[i]) : mem0[i];
  __syncthreads();
  const int col = blockIdx.x * 128 + threadIdx.x;
  const __nv_bfloat16* w = (blockIdx.y == 0 ? wq : blockIdx.y == 1 ? wk : wv) + col;
  float acc[40];
#pragma unroll
  for (int r = 0; r < 40; r++) acc[r] = 0.f;
  for (int d = 0; d < DM; d++) {
    const float wv_ = __bfloat162float(w[d * 4096]);
#pragma unroll
    for (int r = 0; r < 40; r++) acc[r] = fmaf(__bfloat162float(hs[r * DM + d]), wv_, acc[r]);
  }
#pragma unroll
  for (int r = 0; r < 40; r++) g_b[(blockIdx.y * 40 + r) * 4096 + col] = acc[r];
}
__global__ void fb_attn() {
  __shared__ float p[40];
  const int h = blockIdx.x, r = blockIdx.y, t = threadIdx.x;
  if (t < 40) {
    float a = 0.f;
    for (int e = 0; e < DH; e++) a = fmaf(g_b[r * 4096 + h * DH + e], g_b[(40 + t) * 4096 + h * DH + e], a);
    p[t] = (r < 8 || r >= t) ? a * 0.0625f : -1e9f;
  }
  __syncthreads();
  float mx = p[0], l = 0.f, o = 0.f;
  for (int k = 1; k < 40; k++) mx = fmaxf(mx, p[k]);
  for (int k = 0; k < 40; k++) { const float e = expf(p[k] - mx); l += e; o = fmaf(e, g_b[(80 + k) * 4096 + h * DH + t], o); }
  g_b[(120 + r) * 4096 + h * DH + t] = o / l;
}
__global__ void fb_out(const __nv_bfloat16* wo, int s) {
  const int r = blockIdx.x, c = threadIdx.x;
  float a = 0.f;
  for (int k = 0; k < 4096; k++) a = fmaf(g_b[(120 + r) * 4096 + k], __bfloat162float(wo[k * DM + c]), a);
  if (r < 8) g_fmem[r * DM + c] = a; else g_stash[(s * 32 + r - 8) * DM + c] = a;
}
__global__ void fb_ffn(const __nv_bfloat16* x, const __nv_bfloat16* w1, const __nv_bfloat16* w2, const __nv_bfloat16* gw, __nv_bfloat16* out) {
  __shared__ float xs[DM], hs[DFF];
  const int r = blockIdx.x, c = threadIdx.x;
  xs[c] = __bfloat162float(x[r * DM + c]);
  __syncthreads();
  float z = 0.f, b = 0.f;
  for (int d = 0; d < DM; d++) z = fmaf(xs[d], __bfloat162float(gw[d]), z);
  for (int f = c; f < DFF; f += DM) {
    float a = 0.f;
    for (int d = 0; d < DM; d++) a = fmaf(xs[d], __bfloat162float(w1[d * DFF + f]), a);
    hs[f] = fmaxf(a, 0.f);
  }
  __syncthreads();
  for (int f = 0; f < DFF; f++) b = fmaf(hs[f], __bfloat162float(w2[f * DM + c]), b);
  const float g = 1.f / (1.f + expf(-z));
  out[r * DM + c] = __float2bfloat16(g * g_stash[r * DM + c] + (1.f - g) * b);
}

typedef CUresult (*EncodeFn)(CUtensorMap*, CUtensorMapDataType, cuuint32_t, void*, const cuuint64_t*, const cuuint64_t*,
                             const cuuint32_t*, const cuuint32_t*, CUtensorMapInterleave, CUtensorMapSwizzle,
                             CUtensorMapL2promotion, CUtensorMapFloatOOBfill);

void make_map(EncodeFn fn, CUtensorMap* m, const void* p, uint64_t rows, uint64_t cols, uint32_t box_rows) {
  const cuuint64_t dims[2] = {cols, rows}, strides[1] = {cols * 2};
  const cuuint32_t box[2] = {64, box_rows}, es[2] = {1, 1};
  fn(m, CU_TENSOR_MAP_DATA_TYPE_BFLOAT16, 2, const_cast<void*>(p), dims, strides, box, es, CU_TENSOR_MAP_INTERLEAVE_NONE,
     CU_TENSOR_MAP_SWIZZLE_128B, CU_TENSOR_MAP_L2_PROMOTION_L2_256B, CU_TENSOR_MAP_FLOAT_OOB_FILL_NONE);
}

}

extern "C" void kernel_launch(void* const* d_in, const int* in_sizes, int n_in, void* d_out, int out_size) {
  (void)in_sizes; (void)n_in; (void)out_size;
  const __nv_bfloat16* x = (const __nv_bfloat16*)d_in[0];
  const __nv_bfloat16* mem0 = (const __nv_bfloat16*)d_in[1];
  const __nv_bfloat16* gate_w = (const __nv_bfloat16*)d_in[10];
  static EncodeFn fn = nullptr;
  static void* hptr = nullptr;
  static int mode = 0;
  cudaLaunchConfig_t cfg = {};
  cudaLaunchAttribute at[2];
  cfg.gridDim = dim3(112); cfg.blockDim = dim3(384); cfg.dynamicSmemBytes = T_SMEM; cfg.stream = cudaStreamPerThread;
  at[0].id = cudaLaunchAttributeClusterDimension;
  at[0].val.clusterDim.x = 16; at[0].val.clusterDim.y = 1; at[0].val.clusterDim.z = 1;
  cfg.attrs = at; cfg.numAttrs = 1;
  if (!mode) {
    cudaDriverEntryPointQueryResult qr;
    cudaGetDriverEntryPoint("cuTensorMapEncodeTiled", (void**)&fn, cudaEnableDefault, &qr);
    cudaGetSymbolAddress(&hptr, g_h);
    cudaFuncSetAttribute(rmt_kernel, cudaFuncAttributeMaxDynamicSharedMemorySize, T_SMEM);
    cudaFuncSetAttribute(rmt_kernel, cudaFuncAttributeNonPortableClusterSizeAllowed, 1);
    cudaFuncSetAttribute(ffn_kernel, cudaFuncAttributeMaxDynamicSharedMemorySize, F_SMEM);
    int ncl = 0;
    mode = fn && cudaOccupancyMaxActiveClusters(&ncl, rmt_kernel, &cfg) == cudaSuccess && ncl >= 7 ? 1 : 2;
    (void)cudaGetLastError();
  }
  if (mode == 2) {
    const __nv_bfloat16* const* in = (const __nv_bfloat16* const*)d_in;
    for (int s = 0; s < NSEG; s++) {
      fb_qkv<<<dim3(32, 3), 128, 0, cudaStreamPerThread>>>(x, mem0, in[2], in[3], in[4], s);
      fb_attn<<<dim3(NH, 40), DH, 0, cudaStreamPerThread>>>();
      fb_out<<<40, DM, 0, cudaStreamPerThread>>>(in[5], s);
    }
    fb_ffn<<<SEQ, DM, 0, cudaStreamPerThread>>>(x, in[8], in[9], gate_w, (__nv_bfloat16*)d_out);
    return;
  }
  CUtensorMap mWq, mWk, mWv, mWo, mX, mXf, mW1, mH, mW2;
  make_map(fn, &mWq, d_in[2], DM, NH * DH, 64);
  make_map(fn, &mWk, d_in[3], DM, NH * DH, 224);
  make_map(fn, &mWv, d_in[4], DM, NH * DH, 224);
  make_map(fn, &mWo, d_in[5], NH * DH, DM, 256);
  make_map(fn, &mX, x, SEQ, DM, 32);
  make_map(fn, &mXf, x, SEQ, DM, 128);
  make_map(fn, &mW1, d_in[8], DM, DFF, 64);
  make_map(fn, &mH, hptr, SEQ, DFF, 128);
  make_map(fn, &mW2, d_in[9], DFF, DM, 64);

  cudaLaunchKernelEx(&cfg, rmt_kernel, mWq, mWk, mWv, mWo, mX, x, mem0, gate_w, (__nv_bfloat16*)d_out);

  cfg.gridDim = dim3(16); cfg.dynamicSmemBytes = F_SMEM;
  at[0].val.clusterDim.x = 2;
  at[1].id = cudaLaunchAttributeProgrammaticStreamSerialization;
  at[1].val.programmaticStreamSerializationAllowed = 1;
  cfg.numAttrs = 2;
  cudaLaunchKernelEx(&cfg, ffn_kernel, mXf, mW1, mH, mW2, x, gate_w, (__nv_bfloat16*)d_out);
}
```

```cpp
#include <cuda_runtime.h>
#include <cuda_bf16.h>
#include <cuda.h>
#include <stdint.h>

namespace {

#define DEVI __device__ __forceinline__

constexpr int SEQ = 2048, DM = 448, NH = 16, DH = 256, NSEG = 64, DFF = 1792;
constexpr float SC2 = 1.4426950408889634f / 16.0f;
constexpr float MASKV = -1.6e10f;
constexpr int SPIN_LIMIT = 1 << 20;

#define D_M 420
#define D_T 700
#define D_SS 230
#define D_TL 750
#define FFN_AT 12
#define MP 448
#define D_S 150

__device__ __align__(1024) uint8_t g_mslot[3][8192];
__device__ __align__(1024) float g_smm[NH][2][7][64];
__device__ __align__(1024) float g_xacc[8][NH][512];
__device__ __align__(1024) float g_sacc[8][NH][1408];
__device__ __align__(1024) float g_stash[SEQ * DM];
__device__ __align__(1024) float g_b[SEQ * DM];
__device__ __align__(1024) __nv_bfloat16 g_h[SEQ * DFF];
__device__ __align__(1024) uint32_t g_bflag[32][2][8];
__device__ uint32_t g_ticket[2];
__device__ int g_err;
#define TS(i)
#define PTS(i)

DEVI uint32_t smem_u32(const void* p) { return (uint32_t)__cvta_generic_to_shared(p); }
DEVI uint32_t clk() { uint32_t c; asm volatile("mov.u32 %0, %%clock;" : "=r"(c) :: "memory"); return c; }
DEVI void mbar_init(uint32_t bar, uint32_t cnt) { asm volatile("mbarrier.init.shared::cta.b64 [%0], %1;" :: "r"(bar), "r"(cnt) : "memory"); }
DEVI void mbar_expect(uint32_t bar, uint32_t bytes) { asm volatile("mbarrier.arrive.expect_tx.shared::cta.b64 _, [%0], %1;" :: "r"(bar), "r"(bytes) : "memory"); }
DEVI void mbar_arrive(uint32_t bar) { asm volatile("mbarrier.arrive.shared::cta.b64 _, [%0];" :: "r"(bar) : "memory"); }
DEVI uint32_t lds32v(uint32_t a) { uint32_t v; asm volatile("ld.volatile.shared::cta.u32 %0, [%1];" : "=r"(v) : "r"(a) : "memory"); return v; }
DEVI void sts32v(uint32_t a, uint32_t v) { asm volatile("st.volatile.shared::cta.u32 [%0], %1;" :: "r"(a), "r"(v) : "memory"); }
DEVI void mbar_wait(uint32_t bar, uint32_t par, int& lim) {
  asm volatile("{\n.reg .pred p, q;\nWAIT_LOOP:\n"
               "mbarrier.try_wait.parity.shared::cta.b64 p, [%1], %2;\n"
               "sub.s32 %0, %0, 1;\nsetp.gt.and.s32 q, %0, 0, !p;\n@q bra.uni WAIT_LOOP;\n}"
               : "+r"(lim) : "r"(bar), "r"(par) : "memory");
}
DEVI void mbar_wait1(uint32_t bar, uint32_t par, int& lim) {
  asm volatile("{\n.reg .pred p, q;\nWAIT_LOOP:\n"
               "mbarrier.try_wait.parity.shared::cta.b64 p, [%1], %2;\n"
               "sub.s32 %0, %0, 1;\nsetp.gt.and.s32 q, %0, 0, !p;\n@q bra WAIT_LOOP;\n}"
               : "+r"(lim) : "r"(bar), "r"(par) : "memory");
}
DEVI bool elect() { uint32_t p; asm volatile("{\n.reg .pred p;\nelect.sync _|p, 0xffffffff;\nselp.u32 %0, 1, 0, p;\n}" : "=r"(p)); return p; }
DEVI void delay_until(uint32_t t0, uint32_t d) {
  asm volatile("{\n.reg .pred p;\n.reg .u32 t, u;\n.reg .u64 c;\nDELAY_LOOP:\nmov.u64 c, %%clock64;\nmov.b64 {t, u}, c;\nsub.u32 t, t, %0;\nsetp.lt.u32 p, t, %1;\n@p bra.uni DELAY_LOOP;\n}"
               :: "r"(t0), "r"(d) : "memory");
}
DEVI float rcp(float x) { float y; asm("rcp.approx.ftz.f32 %0, %1;" : "=f"(y) : "f"(x)); return y; }
DEVI uint32_t keep(uint32_t v, int lane) { return __shfl_sync(0xffffffffu, v, lane); }
template <class T> DEVI T* keepp(T* p, int lane) { return reinterpret_cast<T*>(__shfl_sync(0xffffffffu, reinterpret_cast<unsigned long long>(p), lane)); }
template <class T> DEVI void pin(T& v) { asm volatile("" : "+r"(v)); }
template <class T> DEVI void pinp(T*& v) { asm volatile("" : "+l"(v)); }
DEVI void bar_sync(int id, int n) { asm volatile("bar.sync %0, %1;" :: "r"(id), "r"(n) : "memory"); }
DEVI void bar_arrive(int id, int n) { asm volatile("bar.arrive %0, %1;" :: "r"(id), "r"(n) : "memory"); }
DEVI void cluster_arrive_relaxed() { asm volatile("barrier.cluster.arrive.relaxed.aligned;" ::: "memory"); }
DEVI void cluster_arrive() { asm volatile("barrier.cluster.arrive.release.aligned;" ::: "memory"); }
DEVI void cluster_wait() { asm volatile("barrier.cluster.wait.acquire.aligned;" ::: "memory"); }
DEVI uint32_t mapa(uint32_t a, uint32_t r) { uint32_t o; asm("mapa.shared::cluster.u32 %0, %1, %2;" : "=r"(o) : "r"(a), "r"(r)); return o; }
DEVI uint32_t pack2(float lo, float hi) { uint32_t r; asm("cvt.rn.bf16x2.f32 %0, %1, %2;" : "=r"(r) : "f"(hi), "f"(lo)); return r; }
DEVI float ex2(float x) { float y; asm("ex2.approx.ftz.f32 %0, %1;" : "=f"(y) : "f"(x)); return y; }
DEVI float bf_lo(uint32_t v) { return __uint_as_float(v << 16); }
DEVI float bf_hi(uint32_t v) { return __uint_as_float(v & 0xffff0000u); }
DEVI void ldsm4(uint32_t (&r)[4], uint32_t a) {
  asm volatile("ldmatrix.sync.aligned.m8n8.x4.shared.b16 {%0,%1,%2,%3}, [%4];" : "=r"(r[0]), "=r"(r[1]), "=r"(r[2]), "=r"(r[3]) : "r"(a) : "memory");
}
DEVI void stsm4t(uint32_t a, uint32_t r0, uint32_t r1, uint32_t r2, uint32_t r3) {
  asm volatile("stmatrix.sync.aligned.m8n8.x4.trans.shared.b16 [%0], {%1,%2,%3,%4};" :: "r"(a), "r"(r0), "r"(r1), "r"(r2), "r"(r3) : "memory");
}
DEVI void stsm2t(uint32_t a, uint32_t r0, uint32_t r1) {
  asm volatile("stmatrix.sync.aligned.m8n8.x2.trans.shared.b16 [%0], {%1,%2};" :: "r"(a), "r"(r0), "r"(r1) : "memory");
}
DEVI void mma16(float (&c)[4], uint32_t a0, uint32_t a1, uint32_t a2, uint32_t a3, uint32_t b0, uint32_t b1) {
  asm("mma.sync.aligned.m16n8k16.row.col.f32.bf16.bf16.f32 {%0,%1,%2,%3},{%4,%5,%6,%7},{%8,%9},{%0,%1,%2,%3};"
      : "+f"(c[0]), "+f"(c[1]), "+f"(c[2]), "+f"(c[3]) : "r"(a0), "r"(a1), "r"(a2), "r"(a3), "r"(b0), "r"(b1));
}
DEVI void mma8(float (&c)[4], uint32_t a0, uint32_t a1, uint32_t b0) {
  asm("mma.sync.aligned.m16n8k8.row.col.f32.bf16.bf16.f32 {%0,%1,%2,%3},{%4,%5},{%6},{%0,%1,%2,%3};"
      : "+f"(c[0]), "+f"(c[1]), "+f"(c[2]), "+f"(c[3]) : "r"(a0), "r"(a1), "r"(b0));
}
DEVI void mma16v(float (&c)[4], uint32_t a0, uint32_t a1, uint32_t a2, uint32_t a3, uint32_t b0, uint32_t b1) {
  asm volatile("mma.sync.aligned.m16n8k16.row.col.f32.bf16.bf16.f32 {%0,%1,%2,%3},{%4,%5,%6,%7},{%8,%9},{%0,%1,%2,%3};"
      : "+f"(c[0]), "+f"(c[1]), "+f"(c[2]), "+f"(c[3]) : "r"(a0), "r"(a1), "r"(a2), "r"(a3), "r"(b0), "r"(b1));
}
DEVI void mma8v(float (&c)[4], uint32_t a0, uint32_t a1, uint32_t b0) {
  asm volatile("mma.sync.aligned.m16n8k8.row.col.f32.bf16.bf16.f32 {%0,%1,%2,%3},{%4,%5},{%6},{%0,%1,%2,%3};"
      : "+f"(c[0]), "+f"(c[1]), "+f"(c[2]), "+f"(c[3]) : "r"(a0), "r"(a1), "r"(b0));
}
DEVI float2 mma_rows8(const uint32_t (&a0)[4], const uint32_t (&a1)[4], const uint32_t (&b0)[4], const uint32_t (&b1)[4]) {
  float e0[4] = {0.f, 0.f, 0.f, 0.f}, e1[4] = {0.f, 0.f, 0.f, 0.f}, e2[4] = {0.f, 0.f, 0.f, 0.f}, e3[4] = {0.f, 0.f, 0.f, 0.f};
  mma16v(e0, a0[0], a0[1], a0[2], a0[3], b0[0], b0[1]);
  mma16v(e1, a0[0], a0[1], a0[2], a0[3], b0[2], b0[3]);
  mma16v(e2, a1[0], a1[1], a1[2], a1[3], b1[0], b1[1]);
  mma16v(e3, a1[0], a1[1], a1[2], a1[3], b1[2], b1[3]);
  return make_float2((e0[0] + e1[2]) + (e2[0] + e3[2]), (e0[1] + e1[3]) + (e2[1] + e3[3]));
}
DEVI void wg_fence() { asm volatile("wgmma.fence.sync.aligned;" ::: "memory"); }
DEVI void wg_commit() { asm volatile("wgmma.commit_group.sync.aligned;" ::: "memory"); }
template <int N> DEVI void wg_wait() { asm volatile("wgmma.wait_group.sync.aligned %0;" :: "n"(N) : "memory"); }
template <int N> DEVI void reg_fence(float (&d)[N]) {
#pragma unroll
  for (int i = 0; i < N; i++) asm volatile("" : "+f"(d[i]) :: "memory");
}
DEVI uint64_t desc128(uint32_t addr, uint32_t lbo16) {
  return (uint64_t)((addr >> 4) & 0x3fff) | ((uint64_t)lbo16 << 16) | (64ull << 32) | (1ull << 62);
}
DEVI void tma2d(uint32_t dst, const CUtensorMap* tm, int c0, int c1, uint32_t bar) {
  asm volatile("cp.async.bulk.tensor.2d.shared::cluster.global.mbarrier::complete_tx::bytes [%0], [%1, {%2, %3}], [%4];"
               :: "r"(dst), "l"(tm), "r"(c0), "r"(c1), "r"(bar) : "memory");
}
DEVI void tma2d_mc(uint32_t dst, const CUtensorMap* tm, int c0, int c1, uint32_t bar) {
  asm volatile("cp.async.bulk.tensor.2d.shared::cluster.global.mbarrier::complete_tx::bytes.multicast::cluster [%0], [%1, {%2, %3}], [%4], %5;"
               :: "r"(dst), "l"(tm), "r"(c0), "r"(c1), "r"(bar), "h"((uint16_t)0xffff) : "memory");
}
DEVI void bulk_mc(uint32_t dst, const void* src, uint32_t bytes, uint32_t bar) {
  asm volatile("cp.async.bulk.shared::cluster.global.mbarrier::complete_tx::bytes.multicast::cluster [%0], [%1], %2, [%3], %4;"
               :: "r"(dst), "l"(src), "r"(bytes), "r"(bar), "h"((uint16_t)0xffff) : "memory");
}
DEVI void st_async4(uint32_t a, float x, float y, float z, float w, uint32_t bar) {
  asm volatile("st.async.weak.shared::cluster.mbarrier::complete_tx::bytes.v4.f32 [%0], {%1,%2,%3,%4}, [%5];"
               :: "r"(a), "f"(x), "f"(y), "f"(z), "f"(w), "r"(bar) : "memory");
}
DEVI void st_async4u(uint32_t a, uint32_t x, uint32_t y, uint32_t z, uint32_t w, uint32_t bar) {
  asm volatile("st.async.weak.shared::cluster.mbarrier::complete_tx::bytes.v4.b32 [%0], {%1,%2,%3,%4}, [%5];"
               :: "r"(a), "r"(x), "r"(y), "r"(z), "r"(w), "r"(bar) : "memory");
}
DEVI uint32_t ldg1r(const void* p) { uint32_t v; asm volatile("ld.relaxed.gpu.global.u32 %0, [%1];" : "=r"(v) : "l"(p) : "memory"); return v; }
DEVI void ldg2r(uint32_t& x, uint32_t& y, const void* p) { asm volatile("ld.relaxed.gpu.global.v2.u32 {%0,%1}, [%2];" : "=r"(x), "=r"(y) : "l"(p) : "memory"); }
DEVI void stg2r(void* p, uint32_t x, uint32_t y) { asm volatile("st.relaxed.gpu.global.v2.u32 [%0], {%1,%2};" :: "l"(p), "r"(x), "r"(y) : "memory"); }
DEVI float4 lds_f4(uint32_t a) { float4 v; asm volatile("ld.shared.v4.f32 {%0,%1,%2,%3}, [%4];" : "=f"(v.x), "=f"(v.y), "=f"(v.z), "=f"(v.w) : "r"(a) : "memory"); return v; }
DEVI uint2 lds_u2(uint32_t a) { uint2 v; asm volatile("ld.shared.v2.u32 {%0,%1}, [%2];" : "=r"(v.x), "=r"(v.y) : "r"(a) : "memory"); return v; }
DEVI uint4 lds_u4(uint32_t a) { uint4 v; asm volatile("ld.shared.v4.u32 {%0,%1,%2,%3}, [%4];" : "=r"(v.x), "=r"(v.y), "=r"(v.z), "=r"(v.w) : "r"(a) : "memory"); return v; }
DEVI void sts_f4(uint32_t a, float x, float y, float z, float w) { asm volatile("st.shared.v4.f32 [%0], {%1,%2,%3,%4};" :: "r"(a), "f"(x), "f"(y), "f"(z), "f"(w) : "memory"); }
DEVI void sts_u2(uint32_t a, uint32_t x, uint32_t y) { asm volatile("st.shared.v2.u32 [%0], {%1,%2};" :: "r"(a), "r"(x), "r"(y) : "memory"); }
DEVI void sts_u4(uint32_t a, uint32_t x, uint32_t y, uint32_t z, uint32_t w) { asm volatile("st.shared.v4.u32 [%0], {%1,%2,%3,%4};" :: "r"(a), "r"(x), "r"(y), "r"(z), "r"(w) : "memory"); }
DEVI uint32_t tagf(float v, uint32_t tag) { return (__float_as_uint(v) & ~3u) | tag; }
DEVI float qmax(float v) { v = fmaxf(v, __shfl_xor_sync(0xffffffffu, v, 1)); return fmaxf(v, __shfl_xor_sync(0xffffffffu, v, 2)); }
DEVI float qsum(float v) { v += __shfl_xor_sync(0xffffffffu, v, 1); return v + __shfl_xor_sync(0xffffffffu, v, 2); }

__device__ __forceinline__ void wgmma_n224_kk(float (&d)[112], uint64_t da, uint64_t db, int sc) {
  asm volatile("{\n.reg .pred p;\nsetp.ne.b32 p, %114, 0;\n"
    "wgmma.mma_async.sync.aligned.m64n224k16.f32.bf16.bf16 {%0,%1,%2,%3,%4,%5,%6,%7,%8,%9,%10,%11,%12,%13,%14,%15,%16,%17,%18,%19,%20,%21,%22,%23,%24,%25,%26,%27,%28,%29,%30,%31,%32,%33,%34,%35,%36,%37,%38,%39,%40,%41,%42,%43,%44,%45,%46,%47,%48,%49,%50,%51,%52,%53,%54,%55,%56,%57,%58,%59,%60,%61,%62,%63,%64,%65,%66,%67,%68,%69,%70,%71,%72,%73,%74,%75,%76,%77,%78,%79,%80,%81,%82,%83,%84,%85,%86,%87,%88,%89,%90,%91,%92,%93,%94,%95,%96,%97,%98,%99,%100,%101,%102,%103,%104,%105,%106,%107,%108,%109,%110,%111}, %112, %113, p, 1, 1, 0, 0;\n}"
    : "+f"(d[0]),"+f"(d[1]),"+f"(d[2]),"+f"(d[3]),"+f"(d[4]),"+f"(d[5]),"+f"(d[6]),"+f"(d[7]),"+f"(d[8]),"+f"(d[9]),"+f"(d[10]),"+f"(d[11]),"+f"(d[12]),"+f"(d[13]),"+f"(d[14]),"+f"(d[15]),"+f"(d[16]),"+f"(d[17]),"+f"(d[18]),"+f"(d[19]),"+f"(d[20]),"+f"(d[21]),"+f"(d[22]),"+f"(d[23]),"+f"(d[24]),"+f"(d[25]),"+f"(d[26]),"+f"(d[27]),"+f"(d[28]),"+f"(d[29]),"+f"(d[30]),"+f"(d[31]),"+f"(d[32]),"+f"(d[33]),"+f"(d[34]),"+f"(d[35]),"+f"(d[36]),"+f"(d[37]),"+f"(d[38]),"+f"(d[39]),"+f"(d[40]),"+f"(d[41]),"+f"(d[42]),"+f"(d[43]),"+f"(d[44]),"+f"(d[45]),"+f"(d[46]),"+f"(d[47]),"+f"(d[48]),"+f"(d[49]),"+f"(d[50]),"+f"(d[51]),"+f"(d[52]),"+f"(d[53]),"+f"(d[54]),"+f"(d[55]),"+f"(d[56]),"+f"(d[57]),"+f"(d[58]),"+f"(d[59]),"+f"(d[60]),"+f"(d[61]),"+f"(d[62]),"+f"(d[63]),"+f"(d[64]),"+f"(d[65]),"+f"(d[66]),"+f"(d[67]),"+f"(d[68]),"+f"(d[69]),"+f"(d[70]),"+f"(d[71]),"+f"(d[72]),"+f"(d[73]),"+f"(d[74]),"+f"(d[75]),"+f"(d[76]),"+f"(d[77]),"+f"(d[78]),"+f"(d[79]),"+f"(d[80]),"+f"(d[81]),"+f"(d[82]),"+f"(d[83]),"+f"(d[84]),"+f"(d[85]),"+f"(d[86]),"+f"(d[87]),"+f"(d[88]),"+f"(d[89]),"+f"(d[90]),"+f"(d[91]),"+f"(d[92]),"+f"(d[93]),"+f"(d[94]),"+f"(d[95]),"+f"(d[96]),"+f"(d[97]),"+f"(d[98]),"+f"(d[99]),"+f"(d[100]),"+f"(d[101]),"+f"(d[102]),"+f"(d[103]),"+f"(d[104]),"+f"(d[105]),"+f"(d[106]),"+f"(d[107]),"+f"(d[108]),"+f"(d[109]),"+f"(d[110]),"+f"(d[111])
    : "l"(da),"l"(db),"r"(sc));
}
__device__ __forceinline__ void wgmma_n224_mk(float (&d)[112], uint64_t da, uint64_t db, int sc) {
  asm volatile("{\n.reg .pred p;\nsetp.ne.b32 p, %114, 0;\n"
    "wgmma.mma_async.sync.aligned.m64n224k16.f32.bf16.bf16 {%0,%1,%2,%3,%4,%5,%6,%7,%8,%9,%10,%11,%12,%13,%14,%15,%16,%17,%18,%19,%20,%21,%22,%23,%24,%25,%26,%27,%28,%29,%30,%31,%32,%33,%34,%35,%36,%37,%38,%39,%40,%41,%42,%43,%44,%45,%46,%47,%48,%49,%50,%51,%52,%53,%54,%55,%56,%57,%58,%59,%60,%61,%62,%63,%64,%65,%66,%67,%68,%69,%70,%71,%72,%73,%74,%75,%76,%77,%78,%79,%80,%81,%82,%83,%84,%85,%86,%87,%88,%89,%90,%91,%92,%93,%94,%95,%96,%97,%98,%99,%100,%101,%102,%103,%104,%105,%106,%107,%108,%109,%110,%111}, %112, %113, p, 1, 1, 1, 0;\n}"
    : "+f"(d[0]),"+f"(d[1]),"+f"(d[2]),"+f"(d[3]),"+f"(d[4]),"+f"(d[5]),"+f"(d[6]),"+f"(d[7]),"+f"(d[8]),"+f"(d[9]),"+f"(d[10]),"+f"(d[11]),"+f"(d[12]),"+f"(d[13]),"+f"(d[14]),"+f"(d[15]),"+f"(d[16]),"+f"(d[17]),"+f"(d[18]),"+f"(d[19]),"+f"(d[20]),"+f"(d[21]),"+f"(d[22]),"+f"(d[23]),"+f"(d[24]),"+f"(d[25]),"+f"(d[26]),"+f"(d[27]),"+f"(d[28]),"+f"(d[29]),"+f"(d[30]),"+f"(d[31]),"+f"(d[32]),"+f"(d[33]),"+f"(d[34]),"+f"(d[35]),"+f"(d[36]),"+f"(d[37]),"+f"(d[38]),"+f"(d[39]),"+f"(d[40]),"+f"(d[41]),"+f"(d[42]),"+f"(d[43]),"+f"(d[44]),"+f"(d[45]),"+f"(d[46]),"+f"(d[47]),"+f"(d[48]),"+f"(d[49]),"+f"(d[50]),"+f"(d[51]),"+f"(d[52]),"+f"(d[53]),"+f"(d[54]),"+f"(d[55]),"+f"(d[56]),"+f"(d[57]),"+f"(d[58]),"+f"(d[59]),"+f"(d[60]),"+f"(d[61]),"+f"(d[62]),"+f"(d[63]),"+f"(d[64]),"+f"(d[65]),"+f"(d[66]),"+f"(d[67]),"+f"(d[68]),"+f"(d[69]),"+f"(d[70]),"+f"(d[71]),"+f"(d[72]),"+f"(d[73]),"+f"(d[74]),"+f"(d[75]),"+f"(d[76]),"+f"(d[77]),"+f"(d[78]),"+f"(d[79]),"+f"(d[80]),"+f"(d[81]),"+f"(d[82]),"+f"(d[83]),"+f"(d[84]),"+f"(d[85]),"+f"(d[86]),"+f"(d[87]),"+f"(d[88]),"+f"(d[89]),"+f"(d[90]),"+f"(d[91]),"+f"(d[92]),"+f"(d[93]),"+f"(d[94]),"+f"(d[95]),"+f"(d[96]),"+f"(d[97]),"+f"(d[98]),"+f"(d[99]),"+f"(d[100]),"+f"(d[101]),"+f"(d[102]),"+f"(d[103]),"+f"(d[104]),"+f"(d[105]),"+f"(d[106]),"+f"(d[107]),"+f"(d[108]),"+f"(d[109]),"+f"(d[110]),"+f"(d[111])
    : "l"(da),"l"(db),"r"(sc));
}
__device__ __forceinline__ void wgmma_n32_rs(float (&d)[16], const uint32_t (&a)[4], uint64_t db, int sc) {
  asm volatile("{\n.reg .pred p;\nsetp.ne.b32 p, %21, 0;\n"
    "wgmma.mma_async.sync.aligned.m64n32k16.f32.bf16.bf16 {%0,%1,%2,%3,%4,%5,%6,%7,%8,%9,%10,%11,%12,%13,%14,%15}, {%16,%17,%18,%19}, %20, p, 1, 1, 0;\n}"
    : "+f"(d[0]),"+f"(d[1]),"+f"(d[2]),"+f"(d[3]),"+f"(d[4]),"+f"(d[5]),"+f"(d[6]),"+f"(d[7]),"+f"(d[8]),"+f"(d[9]),"+f"(d[10]),"+f"(d[11]),"+f"(d[12]),"+f"(d[13]),"+f"(d[14]),"+f"(d[15])
    : "r"(a[0]),"r"(a[1]),"r"(a[2]),"r"(a[3]),"l"(db),"r"(sc));
}
__device__ __forceinline__ void wgmma_n8_rs(float (&d)[4], const uint32_t (&a)[4], uint64_t db, int sc) {
  asm volatile("{\n.reg .pred p;\nsetp.ne.b32 p, %9, 0;\n"
    "wgmma.mma_async.sync.aligned.m64n8k16.f32.bf16.bf16 {%0,%1,%2,%3}, {%4,%5,%6,%7}, %8, p, 1, 1, 0;\n}"
    : "+f"(d[0]),"+f"(d[1]),"+f"(d[2]),"+f"(d[3])
    : "r"(a[0]),"r"(a[1]),"r"(a[2]),"r"(a[3]),"l"(db),"r"(sc));
}
__device__ __forceinline__ void wgmma_n256_kn(float (&d)[128], uint64_t da, uint64_t db, int sc) {
  asm volatile("{\n.reg .pred p;\nsetp.ne.b32 p, %130, 0;\n"
    "wgmma.mma_async.sync.aligned.m64n256k16.f32.bf16.bf16 {%0,%1,%2,%3,%4,%5,%6,%7,%8,%9,%10,%11,%12,%13,%14,%15,%16,%17,%18,%19,%20,%21,%22,%23,%24,%25,%26,%27,%28,%29,%30,%31,%32,%33,%34,%35,%36,%37,%38,%39,%40,%41,%42,%43,%44,%45,%46,%47,%48,%49,%50,%51,%52,%53,%54,%55,%56,%57,%58,%59,%60,%61,%62,%63,%64,%65,%66,%67,%68,%69,%70,%71,%72,%73,%74,%75,%76,%77,%78,%79,%80,%81,%82,%83,%84,%85,%86,%87,%88,%89,%90,%91,%92,%93,%94,%95,%96,%97,%98,%99,%100,%101,%102,%103,%104,%105,%106,%107,%108,%109,%110,%111,%112,%113,%114,%115,%116,%117,%118,%119,%120,%121,%122,%123,%124,%125,%126,%127}, %128, %129, p, 1, 1, 0, 1;\n}"
    : "+f"(d[0]),"+f"(d[1]),"+f"(d[2]),"+f"(d[3]),"+f"(d[4]),"+f"(d[5]),"+f"(d[6]),"+f"(d[7]),"+f"(d[8]),"+f"(d[9]),"+f"(d[10]),"+f"(d[11]),"+f"(d[12]),"+f"(d[13]),"+f"(d[14]),"+f"(d[15]),"+f"(d[16]),"+f"(d[17]),"+f"(d[18]),"+f"(d[19]),"+f"(d[20]),"+f"(d[21]),"+f"(d[22]),"+f"(d[23]),"+f"(d[24]),"+f"(d[25]),"+f"(d[26]),"+f"(d[27]),"+f"(d[28]),"+f"(d[29]),"+f"(d[30]),"+f"(d[31]),"+f"(d[32]),"+f"(d[33]),"+f"(d[34]),"+f"(d[35]),"+f"(d[36]),"+f"(d[37]),"+f"(d[38]),"+f"(d[39]),"+f"(d[40]),"+f"(d[41]),"+f"(d[42]),"+f"(d[43]),"+f"(d[44]),"+f"(d[45]),"+f"(d[46]),"+f"(d[47]),"+f"(d[48]),"+f"(d[49]),"+f"(d[50]),"+f"(d[51]),"+f"(d[52]),"+f"(d[53]),"+f"(d[54]),"+f"(d[55]),"+f"(d[56]),"+f"(d[57]),"+f"(d[58]),"+f"(d[59]),"+f"(d[60]),"+f"(d[61]),"+f"(d[62]),"+f"(d[63]),"+f"(d[64]),"+f"(d[65]),"+f"(d[66]),"+f"(d[67]),"+f"(d[68]),"+f"(d[69]),"+f"(d[70]),"+f"(d[71]),"+f"(d[72]),"+f"(d[73]),"+f"(d[74]),"+f"(d[75]),"+f"(d[76]),"+f"(d[77]),"+f"(d[78]),"+f"(d[79]),"+f"(d[80]),"+f"(d[81]),"+f"(d[82]),"+f"(d[83]),"+f"(d[84]),"+f"(d[85]),"+f"(d[86]),"+f"(d[87]),"+f"(d[88]),"+f"(d[89]),"+f"(d[90]),"+f"(d[91]),"+f"(d[92]),"+f"(d[93]),"+f"(d[94]),"+f"(d[95]),"+f"(d[96]),"+f"(d[97]),"+f"(d[98]),"+f"(d[99]),"+f"(d[100]),"+f"(d[101]),"+f"(d[102]),"+f"(d[103]),"+f"(d[104]),"+f"(d[105]),"+f"(d[106]),"+f"(d[107]),"+f"(d[108]),"+f"(d[109]),"+f"(d[110]),"+f"(d[111]),"+f"(d[112]),"+f"(d[113]),"+f"(d[114]),"+f"(d[115]),"+f"(d[116]),"+f"(d[117]),"+f"(d[118]),"+f"(d[119]),"+f"(d[120]),"+f"(d[121]),"+f"(d[122]),"+f"(d[123]),"+f"(d[124]),"+f"(d[125]),"+f"(d[126]),"+f"(d[127])
    : "l"(da),"l"(db),"r"(sc));
}
__device__ __forceinline__ void wgmma_n192_kn(float (&d)[96], uint64_t da, uint64_t db, int sc) {
  asm volatile("{\n.reg .pred p;\nsetp.ne.b32 p, %98, 0;\n"
    "wgmma.mma_async.sync.aligned.m64n192k16.f32.bf16.bf16 {%0,%1,%2,%3,%4,%5,%6,%7,%8,%9,%10,%11,%12,%13,%14,%15,%16,%17,%18,%19,%20,%21,%22,%23,%24,%25,%26,%27,%28,%29,%30,%31,%32,%33,%34,%35,%36,%37,%38,%39,%40,%41,%42,%43,%44,%45,%46,%47,%48,%49,%50,%51,%52,%53,%54,%55,%56,%57,%58,%59,%60,%61,%62,%63,%64,%65,%66,%67,%68,%69,%70,%71,%72,%73,%74,%75,%76,%77,%78,%79,%80,%81,%82,%83,%84,%85,%86,%87,%88,%89,%90,%91,%92,%93,%94,%95}, %96, %97, p, 1, 1, 0, 1;\n}"
    : "+f"(d[0]),"+f"(d[1]),"+f"(d[2]),"+f"(d[3]),"+f"(d[4]),"+f"(d[5]),"+f"(d[6]),"+f"(d[7]),"+f"(d[8]),"+f"(d[9]),"+f"(d[10]),"+f"(d[11]),"+f"(d[12]),"+f"(d[13]),"+f"(d[14]),"+f"(d[15]),"+f"(d[16]),"+f"(d[17]),"+f"(d[18]),"+f"(d[19]),"+f"(d[20]),"+f"(d[21]),"+f"(d[22]),"+f"(d[23]),"+f"(d[24]),"+f"(d[25]),"+f"(d[26]),"+f"(d[27]),"+f"(d[28]),"+f"(d[29]),"+f"(d[30]),"+f"(d[31]),"+f"(d[32]),"+f"(d[33]),"+f"(d[34]),"+f"(d[35]),"+f"(d[36]),"+f"(d[37]),"+f"(d[38]),"+f"(d[39]),"+f"(d[40]),"+f"(d[41]),"+f"(d[42]),"+f"(d[43]),"+f"(d[44]),"+f"(d[45]),"+f"(d[46]),"+f"(d[47]),"+f"(d[48]),"+f"(d[49]),"+f"(d[50]),"+f"(d[51]),"+f"(d[52]),"+f"(d[53]),"+f"(d[54]),"+f"(d[55]),"+f"(d[56]),"+f"(d[57]),"+f"(d[58]),"+f"(d[59]),"+f"(d[60]),"+f"(d[61]),"+f"(d[62]),"+f"(d[63]),"+f"(d[64]),"+f"(d[65]),"+f"(d[66]),"+f"(d[67]),"+f"(d[68]),"+f"(d[69]),"+f"(d[70]),"+f"(d[71]),"+f"(d[72]),"+f"(d[73]),"+f"(d[74]),"+f"(d[75]),"+f"(d[76]),"+f"(d[77]),"+f"(d[78]),"+f"(d[79]),"+f"(d[80]),"+f"(d[81]),"+f"(d[82]),"+f"(d[83]),"+f"(d[84]),"+f"(d[85]),"+f"(d[86]),"+f"(d[87]),"+f"(d[88]),"+f"(d[89]),"+f"(d[90]),"+f"(d[91]),"+f"(d[92]),"+f"(d[93]),"+f"(d[94]),"+f"(d[95])
    : "l"(da),"l"(db),"r"(sc));
}

constexpr uint32_t XB = 28672;
constexpr uint32_t O_WQ = 5 * XB;
constexpr uint32_t O_WO = O_WQ + 32768;
constexpr uint32_t O_MIMG = O_WO + 32768;
constexpr uint32_t O_BAR = O_MIMG + 2 * 7168;
constexpr uint32_t O_TS = O_BAR + 384;
constexpr uint32_t T_SMEM = O_TS + 4096 + 128 + 1024;
constexpr uint32_t O_Z = 4 * XB;
constexpr uint32_t O_RS = O_Z + 2 * 5120;
constexpr uint32_t O_ORS = O_RS + 2 * 2048;
constexpr uint32_t O_P = O_ORS + 4 * 4096;
constexpr uint32_t O_MJ = O_P + 2 * 2560;
constexpr uint32_t O_ST = O_MJ + 2048;
constexpr uint32_t O_PC = O_ST + 2 * 5632;
constexpr uint32_t O_YB = O_PC + 128;
constexpr uint32_t O_GX = O_YB + 2 * 5120;
constexpr uint32_t O_GY = O_GX + 2 * 1792;
enum { B_X = 0, B_M = 4, B_RS = 6, B_O = 8, B_ZX = 10, B_P = 12, B_PF = 14, B_PE = 18, B_WQ = 22, B_WO = 23, B_T = 24, B_MJ = 26, B_OL = 28, B_G = 30, B_M2 = 31, B_YM = 33, B_N = 34 };
constexpr uint32_t O_DONE = O_BAR + 8 * B_N, O_C3 = O_DONE + 8, O_REDO = O_C3 + 4;
enum { N_ZM = 1, N_MOK = 2, N_W1 = 3, N_INIT = 4, N_ZX = 5, N_YX = 6, N_SS = 7, N_ST = 8 };

DEVI void gemm_m(const uint32_t (&w)[28][4], uint32_t img_lane, float (&c)[4]) {
  float acc[4][4];
#pragma unroll
  for (int i = 0; i < 4; i++) { acc[i][0] = acc[i][1] = acc[i][2] = acc[i][3] = 0.f; }
  uint32_t r[14][4];
#pragma unroll
  for (int u = 0; u < 14; u++) ldsm4(r[u], img_lane + u * 512);
#pragma unroll
  for (int u = 0; u < 14; u++) {
    mma16v(acc[(2 * u) & 3], w[2 * u][0], w[2 * u][1], w[2 * u][2], w[2 * u][3], r[u][0], r[u][1]);
    mma16v(acc[(2 * u + 1) & 3], w[2 * u + 1][0], w[2 * u + 1][1], w[2 * u + 1][2], w[2 * u + 1][3], r[u][2], r[u][3]);
  }
#pragma unroll
  for (int i = 0; i < 4; i++) c[i] = (acc[0][i] + acc[1][i]) + (acc[2][i] + acc[3][i]);
}

DEVI void gemm_x_issue(const uint32_t (&w)[28][4], uint32_t xbuf, float (&d)[16]) {
  const uint64_t b0 = desc128(xbuf, 1);
  wg_fence();
#pragma unroll
  for (int k = 0; k < 28; k++) wgmma_n32_rs(d, w[k], b0 + (uint64_t)((k >> 2) * 256 + (k & 3) * 2), k != 0);
  wg_commit();
}
DEVI void gemm_x(const uint32_t (&w)[28][4], uint32_t xbuf, float (&d)[16]) {
  gemm_x_issue(w, xbuf, d);
  wg_wait<0>();
  reg_fence(d);
}

template <int WHICH>
DEVI void build_weights(uint32_t (&w)[28][4], uint32_t sb, int& dead, int lane) {
  const uint32_t bar = sb + O_BAR;
  mbar_wait(bar + 8 * (WHICH ? B_WO : B_WQ), 0, dead);
  if ((threadIdx.x & 127) == 0) PTS(4 + WHICH);
#pragma unroll
  for (int half = 0; half < 2; half++) {
    float d[112];
#pragma unroll 1
    for (int fk = 0; fk < 4; fk++) {
      const int c = 2 * (4 * half + fk) + WHICH, st = c & 3;
      mbar_wait(bar + 8 * (B_PF + st), (c >> 2) & 1, dead);
      const uint64_t db = desc128(sb + (st + 1) * XB, 1);
      wg_fence();
#pragma unroll
      for (int kk = 0; kk < 4; kk++) {
        if (WHICH == 0) wgmma_n224_kk(d, desc128(sb + O_WQ + fk * 8192 + kk * 32, 1), db + kk * 2, (fk | kk) != 0);
        else            wgmma_n224_mk(d, desc128(sb + O_WO + (fk * 4 + kk) * 2048, 1), db + kk * 2, (fk | kk) != 0);
      }
      wg_commit();
      wg_wait<0>();
      if (lane == 0) mbar_arrive(bar + 8 * (B_PE + st));
    }
    reg_fence(d);
#pragma unroll
    for (int kk = 0; kk < 14; kk++) {
      w[14 * half + kk][0] = pack2(d[8 * kk + 0], d[8 * kk + 1]);
      w[14 * half + kk][1] = pack2(d[8 * kk + 2], d[8 * kk + 3]);
      w[14 * half + kk][2] = pack2(d[8 * kk + 4], d[8 * kk + 5]);
      w[14 * half + kk][3] = pack2(d[8 * kk + 6], d[8 * kk + 7]);
    }
  }
}

DEVI bool stale7(const uint32_t (&v)[14], uint32_t tag) {
  const uint32_t o = ((v[0] | v[1] | v[2]) | (v[3] | v[4] | v[5]) | (v[6] | v[7] | v[8])) | ((v[9] | v[10] | v[11]) | (v[12] | v[13]));
  const uint32_t a = ((v[0] & v[1] & v[2]) & (v[3] & v[4] & v[5]) & (v[6] & v[7] & v[8])) & ((v[9] & v[10] & v[11]) & (v[12] & v[13]));
  return (((o ^ tag) | (a ^ tag)) & 3u) != 0;
}
DEVI float2 add7(const uint32_t (&v)[14]) {
  float2 r;
  r.x = ((__uint_as_float(v[0]) + __uint_as_float(v[2])) + (__uint_as_float(v[4]) + __uint_as_float(v[6]))) +
        ((__uint_as_float(v[8]) + __uint_as_float(v[10])) + __uint_as_float(v[12]));
  r.y = ((__uint_as_float(v[1]) + __uint_as_float(v[3])) + (__uint_as_float(v[5]) + __uint_as_float(v[7]))) +
        ((__uint_as_float(v[9]) + __uint_as_float(v[11])) + __uint_as_float(v[13]));
  return r;
}

__global__ void __launch_bounds__(384, 1)
rmt_kernel(const __grid_constant__ CUtensorMap tmWq, const __grid_constant__ CUtensorMap tmWk,
           const __grid_constant__ CUtensorMap tmWv, const __grid_constant__ CUtensorMap tmWo,
           const __grid_constant__ CUtensorMap tmX, const __nv_bfloat16* __restrict__ x,
           const __nv_bfloat16* __restrict__ mem0, const __nv_bfloat16* __restrict__ gate_w, __nv_bfloat16* __restrict__ out) {
  extern __shared__ uint8_t smem_raw[];
  const uint32_t sb = (smem_u32(smem_raw) + 1023) & ~1023u;
  const uint32_t bar = sb + O_BAR;
  int lim = SPIN_LIMIT;
  int tid;
  uint32_t h, j;
  asm volatile("mov.u32 %0, %%tid.x;" : "=r"(tid));
  asm volatile("mov.u32 %0, %%cluster_ctarank;" : "=r"(h));
  asm volatile("mov.u32 %0, %%clusterid.x;" : "=r"(j));
  tid = __shfl_sync(0xffffffffu, tid, tid & 31);
  const int lane = tid & 31, warp = __shfl_sync(0xffffffffu, tid >> 5, 0);
  if (warp == 0) PTS(0);

  if (warp == 8) {
    if (elect()) {
#pragma unroll
      for (int i = 0; i < 4; i++) mbar_init(bar + 8 * (B_PF + i), 1);
      mbar_init(bar + 8 * B_WQ, 1);
      mbar_init(bar + 8 * B_WO, 1);
      asm volatile("fence.mbarrier_init.release.cluster;" ::: "memory");
      PTS(1);
      mbar_expect(bar + 8 * B_PF, XB);
      tma2d(sb + XB, &tmWk, h * DH, 0, bar + 8 * B_PF);
      mbar_expect(bar + 8 * B_WQ, 32768);
#pragma unroll
      for (int k = 0; k < 4; k++) tma2d(sb + O_WQ + k * 8192, &tmWq, h * DH + k * 64, j * 64, bar + 8 * B_WQ);
      mbar_expect(bar + 8 * B_WO, 32768);
      tma2d(sb + O_WO, &tmWo, j * 64, h * DH, bar + 8 * B_WO);
#pragma unroll
      for (int c = 1; c < 4; c++) {
        mbar_expect(bar + 8 * (B_PF + c), XB);
        tma2d(sb + (c + 1) * XB, (c & 1) ? &tmWv : &tmWk, h * DH + (c >> 1) * 64, 0, bar + 8 * (B_PF + c));
      }
    }
  } else if (warp == 9) {
    if (elect()) {
#pragma unroll
      for (int i = 0; i < B_N; i++)
        if (i < B_PF || (i >= B_PE && i < B_WQ) || i >= B_T) mbar_init(bar + 8 * i, i == B_M2 + 1 ? 16 : i >= B_MJ ? 1 : i >= B_T ? 3 : i >= B_PE ? 4 : i >= B_P ? 2 : i >= B_ZX ? 4 : 1);
      sts32v(sb + O_DONE, 0);
      sts32v(sb + O_C3, 0);
      sts32v(sb + O_REDO + 4, 0);
      sts32v(sb + O_DONE + 4, 0);
      mbar_expect(bar + 8 * B_X, XB);
      mbar_expect(bar + 8 * B_OL, 4096);
      mbar_expect(bar + 8 * (B_OL + 1), 4096);
#pragma unroll
      for (int i = 0; i < 2; i++) { mbar_expect(bar + 8 * (B_RS + i), 2048); mbar_expect(bar + 8 * (B_O + i), 4096); }
      asm volatile("fence.mbarrier_init.release.cluster;" ::: "memory");
    }
  }
  if (FFN_AT == 0) asm volatile("griddepcontrol.launch_dependents;");
  if (warp == 8) PTS(2);
  __syncthreads();
  cluster_arrive_relaxed();
  if (warp == 0) PTS(3);

  if (warp < 4) {
    asm volatile("setmaxnreg.inc.sync.aligned.u32 216;");
    uint32_t w[28][4];
    build_weights<0>(w, sb, lim, lane);
    if (warp == 0) PTS(6);
    cluster_wait();
    cluster_arrive_relaxed();
    uint32_t zst = sb + O_Z + ((2 * warp + ((lane >> 3) & 1)) * 40 + 8 * (lane >> 4) + (lane & 7)) * 16;
    const int mt = warp & 1, n0 = (warp >> 1) * 3;
    const int ch = lane >> 3, chp = (ch >> 1) | ((ch & 1) << 1);
    uint32_t zld = sb + O_Z + ((warp == 2 ? chp : ch) * 40 + (lane & 7)) * 16 + (warp == 2 ? 0 : n0 * 128);
    const int xrow = 16 * mt + (lane & 15);
    uint32_t xq = sb + j * 4096 + xrow * 128 + (((lane >> 4) ^ (xrow & 7)) << 4);
    uint32_t mimg = sb + O_MIMG + lane * 16, sta = sb + O_ST + (warp == 3 ? 4096 : mt * 2048) + lane * 16;
    float* p_smm = &g_smm[h][0][j][lane * 2];
    zst = keep(zst, lane); zld = keep(zld, lane); xq = keep(xq, lane); mimg = keep(mimg, lane); sta = keep(sta, lane);
    p_smm = keepp(p_smm, lane);
    {
      float d[16];
      mbar_wait(bar + 8 * B_X, 0, lim);
      gemm_x(w, sb, d);
      if (warp == 0) PTS(7);
      cluster_wait();
      if (warp == 0) PTS(24);
      stsm4t(zst + 8 * 16, pack2(d[0], d[1]), pack2(d[2], d[3]), pack2(d[4], d[5]), pack2(d[6], d[7]));
      stsm4t(zst + 24 * 16, pack2(d[8], d[9]), pack2(d[10], d[11]), pack2(d[12], d[13]), pack2(d[14], d[15]));
    }
    const uint32_t rda0 = keep(sb + O_REDO, lane);
    const uint32_t o_a = keep(mapa(sb + O_ORS + h * 256 + warp * 64 + (lane & 3) * 16, lane >> 2), lane);
    const uint32_t o_b = keep(mapa(bar + 8 * B_O, lane >> 2), lane);
    const uint32_t o_st = mapa(sb, 8) - mapa(sb, 0);
    uint32_t oh[8];
    auto token_pv = [&](int sp) {
      const uint32_t p16 = mimg + (O_P - O_MIMG) + (sp & 1) * 2560, p8 = p16 + 1024 - lane * 8, yb = sb + O_YB + (sp & 1) * 5120 + tid * 16;
      const uint4 y0 = lds_u4(yb), y1 = lds_u4(yb + 2048);
      const uint2 ymp = lds_u2(yb + 4096 - tid * 8);
      mbar_wait(bar + 8 * (B_P + (sp & 1)), (sp >> 1) & 1, lim);
      const uint2 m0 = lds_u2(p8), m1 = lds_u2(p8 + 1280);
      const uint4 p0 = lds_u4(p16), p1 = lds_u4(p16 + 512), p2 = lds_u4(p16 + 1280), p3 = lds_u4(p16 + 1280 + 512);
      float o0[4] = {0.f, 0.f, 0.f, 0.f}, o1[4] = {0.f, 0.f, 0.f, 0.f}, o2[4] = {0.f, 0.f, 0.f, 0.f}, o3[4] = {0.f, 0.f, 0.f, 0.f};
      mma8(o0, m0.x, m0.y, ymp.x);
      mma8(o1, m0.x, m0.y, ymp.y);
      mma8(o2, m1.x, m1.y, ymp.x);
      mma8(o3, m1.x, m1.y, ymp.y);
      mma16(o0, p0.x, p0.y, p0.z, p0.w, y0.x, y0.y);
      mma16(o1, p0.x, p0.y, p0.z, p0.w, y0.z, y0.w);
      mma16(o2, p2.x, p2.y, p2.z, p2.w, y0.x, y0.y);
      mma16(o3, p2.x, p2.y, p2.z, p2.w, y0.z, y0.w);
      mma16(o0, p1.x, p1.y, p1.z, p1.w, y1.x, y1.y);
      mma16(o1, p1.x, p1.y, p1.z, p1.w, y1.z, y1.w);
      mma16(o2, p3.x, p3.y, p3.z, p3.w, y1.x, y1.y);
      mma16(o3, p3.x, p3.y, p3.z, p3.w, y1.z, y1.w);
      oh[0] = pack2(o0[0], o0[1]); oh[1] = pack2(o1[0], o1[1]); oh[2] = pack2(o0[2], o0[3]); oh[3] = pack2(o1[2], o1[3]);
      oh[4] = pack2(o2[0], o2[1]); oh[5] = pack2(o3[0], o3[1]); oh[6] = pack2(o2[2], o2[3]); oh[7] = pack2(o3[2], o3[3]);
    };
    auto token_send = [&](int sp) {
      const bool last = sp >= NSEG - 2;
      const uint32_t oa = o_a + ((last ? 2 : 0) + (sp & 1)) * 4096, ob = o_b + ((last ? B_OL - B_O : 0) + (sp & 1)) * 8;
      st_async4u(oa, oh[0], oh[1], oh[2], oh[3], ob);
      st_async4u(oa + o_st, oh[4], oh[5], oh[6], oh[7], ob + o_st);
    };
#pragma unroll 1
    for (int s = 0; s < NSEG; s++) {
      const bool rec = s < NSEG - 1;
      uint32_t img = mimg + (s & 1) * 7168, zs = zst + (s & 1) * 5120, zl = zld + (s & 1) * 5120;
      uint32_t tag = ((s >> 1) + 1) & 3;
      float* smm = p_smm + (s & 1) * 448;
      pin(img); pin(zs); pin(zl); pin(tag); pinp(smm);
      uint32_t a[4][4];
      if (rec) {
        bar_arrive(N_W1, 256);
        if (warp == 2) {
          const uint32_t mj = s ? mimg + (O_MJ - O_MIMG) + (s & 1) * 1024 : img + j * 1024;
          if (s) mbar_wait(bar + 8 * (B_MJ + (s & 1)), ((s - 1) >> 1) & 1, lim);
          ldsm4(a[0], mj);
          ldsm4(a[1], mj + 512);
        }
      }
      if (s) mbar_wait(bar + 8 * (B_M + (s & 1)), ((s - 1) >> 1) & 1, lim);
      if (warp == 2) TS(0);
      if (warp == 2 && s == 63) PTS(27);
      if (warp == 2 && s == 0) PTS(28);
      if (warp == 2 && s == 1) PTS(29);
      float c[4];
      uint32_t b0[4], b1[4], rda = rda0;
      while (true) {
        gemm_m(w, img, c);
        stsm2t(zs, pack2(c[0], c[1]), pack2(c[2], c[3]));
        if (warp == 1) TS(24);
        bar_sync(N_ZM, 160);
        if (warp == 2) { ldsm4(b0, zl); ldsm4(b1, zl + 4 * 640); }
        const uint32_t redo = lds32v(rda);
        rda += 4;
        if (warp == 2) {
          const float2 e = mma_rows8(a[0], a[1], b0, b1);
          if (rec && !redo) stg2r(smm, tagf(e.x, tag), tagf(e.y, tag));
          if (lane == 0 && !redo && rec) mbar_arrive(bar + 8 * B_YM);
          TS(2);
        }
        if (__builtin_expect(!__any_sync(0xffffffffu, redo), 1)) break;
        bar_sync(N_MOK, 128);
      }
      bar_sync(N_SS, 128);
      if (s >= 2 && rec) token_send(s - 2);
      if (warp != 2) {
        const uint32_t st = sta + (s & 1) * 5632, aq = xq + (s & 3) * XB;
        uint32_t b2[4], b3[4], b4[4], b5[4];
        ldsm4(a[0], aq); ldsm4(b0, zl); ldsm4(b2, zl + 128); ldsm4(b4, zl + 256); ldsm4(a[1], aq ^ 32);
        ldsm4(a[2], aq ^ 64); ldsm4(b1, zl + 2560); ldsm4(b3, zl + 2560 + 128); ldsm4(b5, zl + 2560 + 256); ldsm4(a[3], aq ^ 96);
        float e0[4] = {0.f, 0.f, 0.f, 0.f}, e1[4] = {0.f, 0.f, 0.f, 0.f}, e2[4] = {0.f, 0.f, 0.f, 0.f};
        mma16(e0, a[0][0], a[0][1], a[0][2], a[0][3], b0[0], b0[1]);
        mma16(e1, a[0][0], a[0][1], a[0][2], a[0][3], b2[0], b2[1]);
        mma16(e2, a[0][0], a[0][1], a[0][2], a[0][3], b4[0], b4[1]);
        mma16(e0, a[1][0], a[1][1], a[1][2], a[1][3], b0[2], b0[3]);
        mma16(e1, a[1][0], a[1][1], a[1][2], a[1][3], b2[2], b2[3]);
        mma16(e2, a[1][0], a[1][1], a[1][2], a[1][3], b4[2], b4[3]);
        mma16(e0, a[2][0], a[2][1], a[2][2], a[2][3], b1[0], b1[1]);
        mma16(e1, a[2][0], a[2][1], a[2][2], a[2][3], b3[0], b3[1]);
        mma16(e2, a[2][0], a[2][1], a[2][2], a[2][3], b5[0], b5[1]);
        mma16(e0, a[3][0], a[3][1], a[3][2], a[3][3], b1[2], b1[3]);
        mma16(e1, a[3][0], a[3][1], a[3][2], a[3][3], b3[2], b3[3]);
        mma16(e2, a[3][0], a[3][1], a[3][2], a[3][3], b5[2], b5[3]);
        sts_f4(st, e0[0], e0[1], e0[2], 1.f);
        sts_f4(st + 512, e0[3], e1[0], e1[1], 1.f);
        sts_f4(st + 1024, e1[2], e1[3], n0 ? 0.f : e2[0], 1.f);
        if (n0 == 0) sts_f4(st + 1536, e2[1], e2[2], e2[3], 1.f);
        if (warp == 1) TS(19);
        asm volatile("fence.proxy.async.shared::cta;" ::: "memory");
        __syncwarp();
        if (lane == 0) mbar_arrive(bar + 8 * (B_T + (s & 1)));
      }
      if (!rec) {
        if (tid == 32) mbar_arrive(bar + 8 * B_YM);
        token_send(s - 2);
      }
      if (s) token_pv(s - 1);
      if (rec) bar_arrive(N_YX, 256);
      if (warp == 1) TS(5);
      if (rec) {
        float d[16];
        if (warp == 1) TS(16);
        mbar_wait(bar + 8 * (B_X + ((s + 1) & 3)), ((s + 1) >> 2) & 1, lim);
        bar_sync(N_ZX, 256);
        if (warp == 1) TS(17);
        gemm_x_issue(w, sb + ((s + 1) & 3) * XB, d);
        wg_wait<0>();
        reg_fence(d);
        if (warp == 1) TS(18);
        const uint32_t zn = zst + ((s + 1) & 1) * 5120;
        stsm4t(zn + 8 * 16, pack2(d[0], d[1]), pack2(d[2], d[3]), pack2(d[4], d[5]), pack2(d[6], d[7]));
        stsm4t(zn + 24 * 16, pack2(d[8], d[9]), pack2(d[10], d[11]), pack2(d[12], d[13]), pack2(d[14], d[15]));
        if (warp == 2) TS(3);
      }
    }
    token_send(NSEG - 2);
    bar_sync(N_ST, 256);
    token_pv(NSEG - 1);
    token_send(NSEG - 1);
    if (warp == 0) PTS(13);
    if (lim <= 0) g_err = 1;
    __syncwarp();
    if (warp == 0) PTS(25);
    cluster_arrive_relaxed();
    cluster_wait();
  } else if (warp < 8) {
    asm volatile("setmaxnreg.inc.sync.aligned.u32 216;");
    const int wq = warp - 4;
    uint32_t w[28][4];
    build_weights<1>(w, sb, lim, lane);
    cluster_wait();
    cluster_arrive_relaxed();
    uint32_t yx[8], ym[2];
    {
      float d[16];
      mbar_wait(bar + 8 * B_X, 0, lim);
      gemm_x(w, sb, d);
#pragma unroll
      for (int i = 0; i < 8; i++) yx[i] = pack2(d[2 * i], d[2 * i + 1]);
      cluster_wait();
    }
    const int ri = lane >> 2, q = lane & 3;
    uint32_t rs_a = mapa(sb + O_RS + h * 128 + ((ri & 1) * 4 + q) * 16, 4 * wq + (ri >> 1));
    uint32_t rs_b = mapa(bar + 8 * B_RS, 4 * wq + (ri >> 1));
    uint32_t mimg = sb + O_MIMG + lane * 16, l8 = sb + lane * 8;
    for (int k = wq; k < 22; k += 4) sts_u2(sb + O_GX + k * 256 + lane * 8, 0, 0);
    asm volatile("fence.proxy.async.shared::cta;" ::: "memory");
    bar_sync(N_INIT, 160);
    const uint32_t zx = keep(sb + O_Z + (((lane >> 4) | ((lane >> 2) & 2)) * 40 + 8 + 8 * wq + (lane & 7)) * 16, lane);
    float* p_smx = keepp(&g_xacc[0][h][wq * 128 + lane * 4], lane);
    const uint32_t yb = sb + O_YB + (tid & 127) * 16;
    sts_u4(yb, yx[0], yx[4], yx[1], yx[5]);
    sts_u4(yb + 2048, yx[2], yx[6], yx[3], yx[7]);
    rs_a = keep(rs_a, lane); rs_b = keep(rs_b, lane); mimg = keep(mimg, lane); l8 = keep(l8, lane);

#pragma unroll 1
    for (int s = 0; s < NSEG; s++) {
      const bool rec = s < NSEG - 1;
      uint32_t img = mimg + (s & 1) * 7168, tag = ((s >> 1) + 1) & 3;
      uint32_t ra = rs_a + (s & 1) * 2048, rb = rs_b + (s & 1) * 8;
      pin(img); pin(tag); pin(ra); pin(rb);
      if (rec) {
        uint32_t zb0[4], zb1[4], a[2][4];
        bar_sync(N_W1, 256);
        ldsm4(zb0, zx + (s & 1) * 5120);
        ldsm4(zb1, zx + (s & 1) * 5120 + 4 * 640);
        const uint32_t mj = s ? mimg + (O_MJ - O_MIMG) + (s & 1) * 1024 : img + j * 1024;
        if (s) mbar_wait(bar + 8 * (B_MJ + (s & 1)), ((s - 1) >> 1) & 1, lim);
        ldsm4(a[0], mj);
        ldsm4(a[1], mj + 512);
        const float2 e = mma_rows8(a[0], a[1], zb0, zb1);
        asm volatile("red.relaxed.gpu.global.add.v4.f32 [%0], {%1,%2,%3,%4};" :: "l"(p_smx + (s & 7) * (NH * 512)), "f"(e.x), "f"(e.y), "f"((float)(s + 1)), "f"(0.f) : "memory");
        if (wq == 0) TS(15);
      }
      if (wq == 0) TS(20);
      mbar_wait(bar + 8 * B_YM, s & 1, lim);
      float c[4];
      {
        const uint64_t dm = (uint64_t)(((sb + O_MIMG + (s & 1) * 7168) >> 4) & 0x3fff) | (8ull << 16) | (8ull << 32);
        wg_fence();
#pragma unroll
        for (int k = 0; k < 28; k++) wgmma_n8_rs(c, w[k], dm + k * 16, k != 0);
        wg_commit();
        if (wq == 0) TS(21);
      }
      float v[4][4], mxl = 0.f;
      if (rec) {
        const float full = 7.f * (s + 1);
        do {
#pragma unroll
          for (int n = 0; n < 4; n++)
            asm volatile("ld.volatile.shared.v4.f32 {%0,%1,%2,%3}, [%4];" : "=f"(v[n][0]), "=f"(v[n][1]), "=f"(v[n][2]), "=f"(v[n][3]) : "r"(mimg + (O_GY - O_MIMG) + n * 512) : "memory");
        } while (__any_sync(0xffffffffu, (v[0][2] + v[0][3] != full) | (v[1][2] + v[1][3] != full) | (v[2][2] + v[2][3] != full) | (v[3][2] + v[3][3] != full)) && --lim > 0);
        sts32v(sb + O_DONE + 4, s + 1);
        mxl = fmaxf(fmaxf(fmaxf(v[0][0], v[0][1]), fmaxf(v[1][0], v[1][1])), fmaxf(fmaxf(v[2][0], v[2][1]), fmaxf(v[3][0], v[3][1])));
        if (wq == 0) TS(22);
      }
      wg_wait<0>();
      reg_fence(c);
      ym[0] = pack2(c[0], c[1]);
      ym[1] = pack2(c[2], c[3]);
      if (rec) {
        uint32_t vm[14];
        const uint32_t gx = l8 + O_GX + (s & 1) * 1792;
        do {
#pragma unroll
          for (int k = 0; k < 7; k++) asm volatile("ld.volatile.shared.v2.u32 {%0,%1}, [%2];" : "=r"(vm[2 * k]), "=r"(vm[2 * k + 1]) : "r"(gx + k * 256) : "memory");
        } while (__any_sync(0xffffffffu, stale7(vm, tag)) && --lim > 0);
        sts32v(sb + O_DONE, s + 1);
        const float2 sm = add7(vm);
        if (wq == 0) TS(8);
        const float mx = qmax(fmaxf(mxl, fmaxf(sm.x, sm.y)));
        const float nb = -mx * SC2;
        uint32_t pa[4];
        float l = 0.f;
#pragma unroll
        for (int n = 0; n < 4; n++) {
          const float p0 = ex2(fmaf(v[n][0], SC2, nb)), p1 = ex2(fmaf(v[n][1], SC2, nb));
          l += p0 + p1;
          pa[n] = pack2(p0, p1);
        }
        float o0[4] = {0.f, 0.f, 0.f, 0.f}, o1[4] = {0.f, 0.f, 0.f, 0.f}, u0[4] = {0.f, 0.f, 0.f, 0.f}, u1[4] = {0.f, 0.f, 0.f, 0.f};
        mma16v(o0, pa[0], pa[1], pa[2], pa[3], yx[0], yx[4]);
        mma16v(o1, pa[0], pa[1], pa[2], pa[3], yx[1], yx[5]);
        mma16v(u0, pa[0], pa[1], pa[2], pa[3], yx[2], yx[6]);
        mma16v(u1, pa[0], pa[1], pa[2], pa[3], yx[3], yx[7]);
        const float p0 = ex2(fmaf(sm.x, SC2, nb)), p1 = ex2(fmaf(sm.y, SC2, nb));
        const uint32_t pp = pack2(p0, p1);
        mma8v(o0, pp, pp, ym[0]);
        mma8v(o1, pp, pp, ym[1]);
        const float inv = rcp(qsum(l + (p0 + p1)));
        st_async4(ra, (o0[0] + u0[2]) * inv, (o0[1] + u0[3]) * inv, (o1[0] + u1[2]) * inv, (o1[1] + u1[3]) * inv, rb);
      }
      sts_u2(yb + 4096 - (tid & 127) * 8 + (s & 1) * 5120, ym[0], ym[1]);
      if (!rec) bar_arrive(N_ST, 256);
      if (rec) {
        bar_arrive(N_ZX, 256);
        if (wq == 0) TS(9);
      }
      if (rec) {
        float d[16];
        mbar_wait(bar + 8 * (B_X + ((s + 1) & 3)), ((s + 1) >> 2) & 1, lim);
        gemm_x(w, sb + ((s + 1) & 3) * XB, d);
#pragma unroll
        for (int i = 0; i < 8; i++) yx[i] = pack2(d[2 * i], d[2 * i + 1]);
        bar_sync(N_YX, 256);
        sts_u4(yb + ((s + 1) & 1) * 5120, yx[0], yx[4], yx[1], yx[5]);
        sts_u4(yb + ((s + 1) & 1) * 5120 + 2048, yx[2], yx[6], yx[3], yx[7]);
        if (wq == 0) TS(10);
      }
    }
    if (lim <= 0) g_err = 1;
    __syncwarp();
    cluster_arrive_relaxed();
    cluster_wait();
  } else {
    asm volatile("setmaxnreg.dec.sync.aligned.u32 72;");
    if (warp == 8) {
      const int u = (lane & 15) >> 1, nt = lane & 1;
      uint8_t* gm0 = &g_mslot[0][(8 * j + 2 * (h >> 2) + nt) * 128 + (2 * (h & 3) + (u >> 2)) * 16 + (u & 3) * 4];
#pragma unroll
      for (int k = 0; k < 3; k++) asm volatile("st.relaxed.gpu.global.u32 [%0], 0xffffffff;" :: "l"(gm0 + k * 8192) : "memory");
      cluster_wait();
      if (lane == 0) {
        int lim1 = SPIN_LIMIT;
        if (h < 7) tma2d_mc(sb + h * 4096, &tmX, h * 64, 0, bar + 8 * B_X);
#pragma unroll 1
        for (int c = 4; c < 16; c++) {
          const int st = c & 3;
          mbar_wait1(bar + 8 * (B_PE + st), ((c >> 2) - 1) & 1, lim1);
          if (c == FFN_AT) asm volatile("griddepcontrol.launch_dependents;");
          mbar_expect(bar + 8 * (B_PF + st), XB);
          tma2d(sb + (st + 1) * XB, (c & 1) ? &tmWv : &tmWk, h * DH + ((c >> 1) & 3) * 64, (c >> 3) * 224, bar + 8 * (B_PF + st));
        }
      }
      __syncwarp();
      cluster_arrive();
      cluster_wait();
      if (lane == 0) {
        for (int k = 1; k < 3; k++) {
          mbar_expect(bar + 8 * (B_X + k), XB);
          if (h < 7) tma2d_mc(sb + k * XB + h * 4096, &tmX, h * 64, k * 32, bar + 8 * (B_X + k));
        }
      }
      uint32_t chk = sb + O_MIMG + lane * 32 + (lane >> 2) * 4, rs0 = sb + O_RS + (lane >> 4) * 1024 + (lane & 15) * 8;
      const uint8_t* gnear = &g_mslot[0][0];
      const uint32_t pc_st = keep(sb + O_PC + (nt * 2 + (u >> 2)) * 16 + (u & 3) * 4, lane);
      const uint32_t mj_a = keep(mapa(sb + O_MJ + (2 * (h >> 2) + ((lane >> 1) & 1)) * 128 + (2 * (h & 3) + (lane & 1)) * 16, lane >> 2), lane);
      const uint32_t mj_b = keep(mapa(bar + 8 * B_MJ, lane >> 2), lane), mj_st = mapa(sb, 8) - mapa(sb, 0);
      chk = keep(chk, lane); rs0 = keep(rs0, lane); gm0 = keepp(gm0, lane);
      const uint32_t m2r = mapa(bar + 8 * (B_M2 + 1), lane & 15);
      auto cl_sync_arrive = [&](uint32_t a) { if (lane < 16) asm volatile("mbarrier.arrive.relaxed.cluster.shared::cluster.b64 _, [%0];" :: "r"(a) : "memory"); __syncwarp(); };
      const uint8_t* p_gsrc = reinterpret_cast<const uint8_t*>(&g_smm[h][0][0][0]);
      bar_sync(N_INIT, 160);
      uint32_t m2p = 0;
      int s3 = 0;
#pragma unroll 1
      for (int s = 0; s < NSEG; s++) {
        uint32_t ck = chk + (s & 1) * 7168;
        pin(ck);
        bool redo = false;
        if (s) {
          mbar_wait(bar + 8 * (B_M + (s & 1)), ((s - 1) >> 1) & 1, lim);
          while (true) {
            uint32_t v[7];
#pragma unroll
            for (int k = 0; k < 7; k++) v[k] = lds32v(ck + k * 1024);
            const uint32_t mx = __vimax3_u32(__vimax3_u32(v[0], v[1], v[2]), __vimax3_u32(v[3], v[4], v[5]), v[6]);
            if (__builtin_expect(!__any_sync(0xffffffffu, mx == 0xffffffffu) || lim <= 0, 1)) break;
            redo = true;
            cl_sync_arrive(m2r);
            if (elect()) mbar_expect(bar + 8 * B_M2, 7168);
            mbar_wait(bar + 8 * (B_M2 + 1), m2p, lim);
            if (h < 7168 / MP && elect()) bulk_mc(sb + O_MIMG + (s & 1) * 7168 + h * MP, gnear + s3 * 8192 + h * MP, MP, bar + 8 * B_M2);
            mbar_wait(bar + 8 * B_M2, m2p, lim);
            m2p ^= 1;
          }
        }
        TS(23);
        sts32v(sb + O_REDO, redo);
        bar_sync(N_ZM, 160);
        if (redo) bar_sync(N_ZM, 160);
        if (s == NSEG - 1) break;
        {
          const uint32_t tz = clk();
          const uint8_t* gsrc = p_gsrc + (s & 1) * 1792;
          asm volatile("{\n.reg .pred e, p, q, x;\n.reg .u32 t, u, f0, f1, td, n;\n.reg .u64 c;\n"
                       "elect.sync _|e, 0xffffffff;\nmov.u32 td, %9;\n"
                       "@e mbarrier.expect_tx.relaxed.cta.shared::cta.b64 [%3], 2048;\n"
                       "@e cp.async.bulk.shared::cluster.global.mbarrier::complete_tx::bytes [%6], [%7], 2048, [%3];\n"
                       "setp.eq.u32 x, td, td;\n"
                       "REFRESH:\nmov.u64 c, %%clock64;\nmov.b64 {t, u}, c;\nsub.u32 t, t, %1;\nsetp.lt.u32 p, t, td;\n@p bra.uni REFRESH;\n"
                       "selp.u32 n, 3840, 1792, x;\nand.pred q, e, x;\n"
                       "@e mbarrier.expect_tx.relaxed.cta.shared::cta.b64 [%3], n;\n"
                       "@e cp.async.bulk.shared::cluster.global.mbarrier::complete_tx::bytes [%4], [%5], 1792, [%3];\n"
                       "@q cp.async.bulk.shared::cluster.global.mbarrier::complete_tx::bytes [%6], [%7], 2048, [%3];\n"
                       "ld.volatile.shared.v2.u32 {f0, f1}, [%8];\nadd.u32 td, td, %10;\nsub.s32 %0, %0, 1;\n"
                       "setp.le.s32 x, f1, %2;\nsetp.le.s32 p, f0, %2;\nsetp.gt.and.s32 p, %0, 0, p;\n@p bra.uni REFRESH;\n}"
                       : "+r"(lim)
                       : "r"(tz), "r"(s), "r"(bar + 8 * B_G), "r"(sb + O_GX + (s & 1) * 1792), "l"(gsrc), "r"(sb + O_GY), "l"(&g_xacc[s & 7][h][0]),
                         "r"(sb + O_DONE), "n"(D_S), "n"(D_SS)
                       : "memory");
        }
        while (__any_sync(0xffffffffu, (int)lds32v(sb + O_C3) < s - 2) && --lim > 0) {}
        const int s3n = s3 == 2 ? 0 : s3 + 1;
        uint32_t rb = rs0 + (s & 1) * 2048;
        uint8_t* gm = gm0 + s3n * 8192;
        const uint32_t mdst = sb + O_MIMG + ((s + 1) & 1) * 7168 + h * MP, mb = bar + 8 * (B_M + ((s + 1) & 1));
        const uint8_t* msrc = gnear + s3n * 8192 + h * MP;
        s3 = s3n;
        pin(rb); pinp(gm);
        mbar_wait(bar + 8 * (B_RS + (s & 1)), (s >> 1) & 1, lim);
        TS(11);
        uint2 v[8];
#pragma unroll
        for (int k = 0; k < 8; k++) v[k] = lds_u2(rb + k * 128);
        float s0 = ((__uint_as_float(v[0].x) + __uint_as_float(v[1].x)) + (__uint_as_float(v[2].x) + __uint_as_float(v[3].x))) +
                   ((__uint_as_float(v[4].x) + __uint_as_float(v[5].x)) + (__uint_as_float(v[6].x) + __uint_as_float(v[7].x)));
        float s1 = ((__uint_as_float(v[0].y) + __uint_as_float(v[1].y)) + (__uint_as_float(v[2].y) + __uint_as_float(v[3].y))) +
                   ((__uint_as_float(v[4].y) + __uint_as_float(v[5].y)) + (__uint_as_float(v[6].y) + __uint_as_float(v[7].y)));
        s0 += __shfl_xor_sync(0xffffffffu, s0, 16);
        s1 += __shfl_xor_sync(0xffffffffu, s1, 16);
        const uint32_t mw = pack2(s0, s1);
        if (lane < 16) asm volatile("st.relaxed.gpu.global.u32 [%0], %1;" :: "l"(gm), "r"(mw) : "memory");
        const uint32_t tm = clk();
        TS(12);
        sts32v(pc_st, mw);
        __syncwarp();
        const float4 pc = lds_f4(sb + O_PC + (lane & 3) * 16);
        if (s < NSEG - 2) {
          const uint32_t o = ((s + 1) & 1) * 1024, ob = ((s + 1) & 1) * 8;
          st_async4(mj_a + o, pc.x, pc.y, pc.z, pc.w, mj_b + ob);
          st_async4(mj_a + o + mj_st, pc.x, pc.y, pc.z, pc.w, mj_b + ob + mj_st);
        }
        const bool el = elect();
        if (el) mbar_expect(bar + 8 * (B_RS + (s & 1)), 2048);
        delay_until(tm, D_M);
        TS(25);
        if (el && h < 7168 / MP) bulk_mc(mdst, msrc, MP, mb);
      }
      if (elect()) mbar_arrive(bar + 8 * B_G);
      mbar_wait(bar + 8 * B_G, 0, lim);
    } else if (warp < 11) {
      const int mt = warp - 9, q = lane & 3;
#pragma unroll
      for (int t = mt * 32 + lane; t < 448; t += 64) {
        const uint4 v = *reinterpret_cast<const uint4*>(mem0 + (t & 7) * DM + (t >> 3) * 8);
        sts_u4(sb + O_MIMG + t * 16, v.x, v.y, v.z, v.w);
      }
      asm volatile("fence.proxy.async.shared::cta;" ::: "memory");
      __syncwarp();
      cluster_wait();
      cluster_arrive();
      cluster_wait();
      uint8_t* gm0 = &g_mslot[0][(8 * j + 2 * (h >> 2) + (lane & 1)) * 128 + (2 * (h & 3) + ((lane >> 3) & 1)) * 16 + ((lane >> 1) & 3) * 4];
      int s3p = 2;
#pragma unroll 1
      for (int s = 0; s < NSEG; s++) {
        mbar_wait(bar + 8 * (B_T + (s & 1)), (s >> 1) & 1, lim);
        if (mt == 1 && s < NSEG - 1) {
          if (elect()) {
            mbar_expect(bar + 8 * (B_M + ((s + 1) & 1)), 7168);
            if (s < NSEG - 2) mbar_expect(bar + 8 * (B_MJ + ((s + 1) & 1)), 1024);
            if (s >= 1 && s + 2 < NSEG) {
              mbar_expect(bar + 8 * (B_X + ((s + 2) & 3)), XB);
              if (h < 7) tma2d_mc(sb + ((s + 2) & 3) * XB + h * 4096, &tmX, h * 64, (s + 2) * 32, bar + 8 * (B_X + ((s + 2) & 3)));
            }
          }
          asm volatile("st.relaxed.gpu.global.u32 [%0], 0xffffffff;" :: "l"(gm0 + s3p * 8192) : "memory");
          s3p = s3p == 2 ? 0 : s3p + 1;
        }
        if (s == 63 && mt == 0) PTS(8);
        const uint32_t t0 = clk();
        if (mt == 0 && elect()) {
          asm volatile("cp.reduce.async.bulk.global.shared::cta.bulk_group.add.f32 [%0], [%1], 5632;" :: "l"(&g_sacc[s & 7][h][0]), "r"(sb + O_ST + (s & 1) * 5632) : "memory");
          asm volatile("cp.async.bulk.commit_group;" ::: "memory");
          asm volatile("cp.async.bulk.wait_group.read 0;" ::: "memory");
        }
        __syncwarp();
        if (s < NSEG - 1) { mbar_wait(bar + 8 * (B_RS + (s & 1)), (s >> 1) & 1, lim);
          delay_until(t0, D_T); }
        else delay_until(t0, D_TL);
        if (mt) TS(28);
        const float4* sp = reinterpret_cast<const float4*>(&g_sacc[s & 7][h][mt * 512 + lane * 4]);
        float u[7][4];
        bool stale;
        do {
          stale = false;
#pragma unroll
          for (int c = 0; c < 7; c++) {
            u[c][0] = u[c][1] = u[c][2] = 0.f; u[c][3] = 7.f;
            if (c < 4 || mt)
              asm volatile("ld.relaxed.gpu.global.v4.f32 {%0,%1,%2,%3}, [%4];" : "=f"(u[c][0]), "=f"(u[c][1]), "=f"(u[c][2]), "=f"(u[c][3]) : "l"(sp + c * 32) : "memory");
          }
#pragma unroll
          for (int c = 0; c < 7; c++) stale |= u[c][3] != 7.f;
        } while (__any_sync(0xffffffffu, stale) && --lim > 0);
        if (mt) TS(29);
        if (s == 63) PTS(9 + mt);
        uint32_t pk[2][5];
        float v[2][10];
#pragma unroll
        for (int e = 0; e < 10; e++) {
          const int i = 4 * (e >> 1) + (e & 1);
          v[0][e] = u[i / 3][i % 3];
          v[1][e] = u[(i + 2) / 3][(i + 2) % 3];
        }
#pragma unroll
        for (int rg = 0; rg < 2; rg++) {
          const int row = 16 * mt + 8 * rg + (lane >> 2);
#pragma unroll
          for (int e = 2; e < 10; e++)
            if (8 * ((e >> 1) - 1) + 2 * q + (e & 1) > row) v[rg][e] = MASKV;
          float mx = v[rg][0];
#pragma unroll
          for (int e = 1; e < 10; e++) mx = fmaxf(mx, v[rg][e]);
          mx = qmax(mx);
          const float nb = -mx * SC2;
          float l = 0.f;
#pragma unroll
          for (int e = 0; e < 10; e++) { v[rg][e] = ex2(fmaf(v[rg][e], SC2, nb)); l += v[rg][e]; }
          const float inv = rcp(qsum(l));
#pragma unroll
          for (int n = 0; n < 5; n++) pk[rg][n] = pack2(v[rg][2 * n] * inv, v[rg][2 * n + 1] * inv);
        }
        const uint32_t pb = sb + O_P + (s & 1) * 2560 + mt * 1280;
        sts_u4(pb + lane * 16, pk[0][1], pk[1][1], pk[0][3], pk[1][3]);
        sts_u4(pb + 512 + lane * 16, pk[0][2], pk[1][2], pk[0][4], pk[1][4]);
        sts_u2(pb + 1024 + lane * 8, pk[0][0], pk[1][0]);
        __syncwarp();
        if (lane == 0) mbar_arrive(bar + 8 * (B_P + (s & 1)));
        if (s == 63) PTS(11 + mt);
        if (mt == 1) TS(13);
        if (j + 7 * mt < 11) asm volatile("st.relaxed.gpu.global.v4.f32 [%0], {%1,%1,%1,%1};" :: "l"(&g_sacc[(s + 4) & 7][h][(j + 7 * mt) * 128 + lane * 4]), "f"(0.f) : "memory");
      }
    } else {
      const int t1 = lane >> 4, l16 = lane & 15;
      uint2 gw[7];
#pragma unroll
      for (int k = 0; k < 7; k++) gw[k] = *reinterpret_cast<const uint2*>(gate_w + (k * 16 + l16) * 4);
      const int col = j * 64 + ((lane >> 2) & 3) * 16 + (lane & 3) * 2;
      const uint32_t epoch = ldg1r(&g_ticket[0]) / 112 + 1;
      __syncwarp();
      cluster_wait();
      cluster_arrive();
      cluster_wait();
      const int trow = 16 * (h >> 3) + (h & 7) + 8 * t1;
      const uint32_t xg = sb + trow * 128 + (((l16 >> 1) ^ (trow & 7)) << 4) + (l16 & 1) * 8;
      auto gate = [&](int sg) {
        mbar_wait(bar + 8 * (B_X + (sg & 3)), (sg >> 2) & 1, lim);
        float z = 0.f, z2 = 0.f;
#pragma unroll
        for (int k = 0; k < 7; k++) {
          const uint2 xv = lds_u2(xg + (sg & 3) * XB + k * 4096);
          z = fmaf(bf_lo(xv.x), bf_lo(gw[k].x), z); z2 = fmaf(bf_hi(xv.x), bf_hi(gw[k].x), z2);
          z = fmaf(bf_lo(xv.y), bf_lo(gw[k].y), z); z2 = fmaf(bf_hi(xv.y), bf_hi(gw[k].y), z2);
        }
        z += z2;
#pragma unroll
        for (int o = 1; o < 16; o <<= 1) z += __shfl_xor_sync(0xffffffffu, z, o);
        return rcp(1.f + ex2(-1.4426950408889634f * z));
      };
      float4 pa4 = make_float4(0.f, 0.f, 0.f, 0.f);
      bool pend = false;
      auto finish = [&](int sg) {
        if (ldg1r(&g_bflag[sg >> 1][j >> 2][0]) == epoch) {
          const int o = (sg * 32 + trow) * DM + col;
          uint32_t b0, b1, b2, b3;
          ldg2r(b0, b1, g_b + o); ldg2r(b2, b3, g_b + o + 8);
          uint32_t* op = reinterpret_cast<uint32_t*>(out + o);
          op[0] = pack2(pa4.x + __uint_as_float(b0), pa4.y + __uint_as_float(b1));
          op[4] = pack2(pa4.z + __uint_as_float(b2), pa4.w + __uint_as_float(b3));
        }
      };
      const uint32_t* fl0 = keepp(&g_bflag[0][j >> 2][0], lane);
      uint32_t fnext = 0;
      float g1 = 0.f, g2 = 0.f;
#pragma unroll 1
      for (int s = -2; s < NSEG; s++) {
        if (s >= 0) {
        const int tok = s * 32 + trow;
        const bool have_b = fnext == epoch;
        fnext = ldg1r(fl0 + (min(s + 1, NSEG - 1) >> 1) * 16);
        const float* bp = &g_b[tok * DM + col];
        uint32_t b0 = 0, b1 = 0, b2 = 0, b3 = 0;
        if (have_b) { ldg2r(b0, b1, bp); ldg2r(b2, b3, bp + 8); }
        const bool last = s >= NSEG - 2;
        mbar_wait(bar + 8 * ((last ? B_OL : B_O) + (s & 1)), last ? 0 : (s >> 1) & 1, lim);
        if (lane < 19 && j * 19 + lane < 128)
          asm volatile("st.relaxed.gpu.global.v4.f32 [%0], {%1,%1,%1,%1};" :: "l"(&g_xacc[s & 7][h][(j * 19 + lane) * 4]), "f"(0.f) : "memory");
        if (s == 63) PTS(14);
        const float g = g1;
        const uint32_t ob = sb + O_ORS + ((last ? 2 : 0) + (s & 1)) * 4096 + t1 * 2048 + l16 * 16;
        float e[8] = {0.f, 0.f, 0.f, 0.f, 0.f, 0.f, 0.f, 0.f};
#pragma unroll 2
        for (int k = 0; k < 8; k++) {
          const uint4 c = lds_u4(ob + k * 256);
          e[0] += bf_lo(c.x); e[1] += bf_hi(c.x); e[2] += bf_lo(c.y); e[3] += bf_hi(c.y);
          e[4] += bf_lo(c.z); e[5] += bf_hi(c.z); e[6] += bf_lo(c.w); e[7] += bf_hi(c.w);
        }
        float4 a;
        a.x = g * ((t1 ? e[4] : e[0]) + __shfl_xor_sync(0xffffffffu, t1 ? e[0] : e[4], 16));
        a.y = g * ((t1 ? e[5] : e[1]) + __shfl_xor_sync(0xffffffffu, t1 ? e[1] : e[5], 16));
        a.z = g * ((t1 ? e[6] : e[2]) + __shfl_xor_sync(0xffffffffu, t1 ? e[2] : e[6], 16));
        a.w = g * ((t1 ? e[7] : e[3]) + __shfl_xor_sync(0xffffffffu, t1 ? e[3] : e[7], 16));
        __syncwarp();
        if (lane == 0 && s < NSEG - 4) mbar_expect(bar + 8 * (B_O + (s & 1)), 4096);
        if (s == 63) PTS(30);
        float* sp = &g_stash[tok * DM + col];
        stg2r(sp, tagf(a.x, epoch & 3), tagf(a.y, epoch & 3));
        stg2r(sp + 8, tagf(a.z, epoch & 3), tagf(a.w, epoch & 3));
        if (have_b) {
          uint32_t* op = reinterpret_cast<uint32_t*>(out + tok * DM + col);
          op[0] = pack2(a.x + __uint_as_float(b0), a.y + __uint_as_float(b1));
          op[4] = pack2(a.z + __uint_as_float(b2), a.w + __uint_as_float(b3));
        }
        if (pend) { if (s >= NSEG - 2) __threadfence(); finish(s - 1); }
        pend = !have_b;
        pa4 = a;
        }
        g1 = g2;
        if (s + 2 < NSEG) g2 = gate(s + 2);
        if (lane == 0 && s >= 0) sts32v(sb + O_C3, s + 1);
        TS(14);
      }
      if (pend) { __threadfence(); finish(NSEG - 1); }
      if (lane == 0) atomicAdd(&g_ticket[0], 1);
    }
    if (lim <= 0) g_err = 1;
    __syncwarp();
    cluster_arrive_relaxed();
    cluster_wait();
  }
}

constexpr uint32_t F_STAGE = 49152, F_BAR = 4 * F_STAGE, F_G = F_BAR + 128, F_STG = F_G + 512, F_SMEM = F_STG + 8 * 2304 + 1024;

DEVI void release_stage(uint32_t sb, int st, int lane) {
  if (lane < 2) asm volatile("mbarrier.arrive.relaxed.cluster.shared::cluster.b64 _, [%0];" :: "r"(mapa(sb + F_BAR + 32 + 8 * st, lane)) : "memory");
}
template <int N>
DEVI void ffn_tile(float (&d)[N / 2], uint32_t sb, int wg, int nk, int& it, int& dead, int lane) {
#pragma unroll 1
  for (int k = 0; k < nk; k++, it++) {
    const int st = it & 3;
    mbar_wait(sb + F_BAR + 8 * st, (it >> 2) & 1, dead);
    const uint64_t da = desc128(sb + st * F_STAGE + wg * 8192, 1), db = desc128(sb + st * F_STAGE + 16384, 512);
    wg_fence();
#pragma unroll
    for (int kk = 0; kk < 4; kk++) {
      if constexpr (N == 256) wgmma_n256_kn(d, da + kk * 2, db + kk * 128, (k | kk) != 0);
      else                    wgmma_n192_kn(d, da + kk * 2, db + kk * 128, (k | kk) != 0);
    }
    wg_commit();
    if (k) { wg_wait<1>(); release_stage(sb, (it - 1) & 3, lane); }
  }
  wg_wait<0>();
  release_stage(sb, (it - 1) & 3, lane);
  reg_fence(d);
}

template <int NJ>
DEVI void ffn_finish(float (&d)[NJ * 32], float g0, float g1, uint32_t sb, int r0, int row, int j0, uint32_t epoch,
                     __nv_bfloat16* __restrict__ out, int tid) {
  const int wg = tid >> 7, t = tid & 127, off = (r0 + row) * DM + j0 * 64 + 2 * (tid & 3);
#pragma unroll
  for (int n = 0; n < NJ * 8; n++) {
    d[4 * n] *= g0; d[4 * n + 1] *= g0; d[4 * n + 2] *= g1; d[4 * n + 3] *= g1;
    *reinterpret_cast<float2*>(g_b + off + n * 8) = make_float2(d[4 * n], d[4 * n + 1]);
    *reinterpret_cast<float2*>(g_b + off + 8 * DM + n * 8) = make_float2(d[4 * n + 2], d[4 * n + 3]);
  }
  asm volatile("fence.release.gpu;" ::: "memory");
  bar_sync(2 + wg, 128);
  if (t == 0) {
    asm volatile("st.relaxed.gpu.global.u32 [%0], %1;" :: "l"(&g_bflag[(r0 >> 6) + wg][j0 >> 2][0]), "r"(epoch) : "memory");
    __threadfence();
  }
  bar_sync(2 + wg, 128);
#pragma unroll
  for (int n0 = 0; n0 < NJ * 8; n0 += 8) {
    uint32_t a[8][4];
#pragma unroll
    for (int n = 0; n < 8; n++) { ldg2r(a[n][0], a[n][1], g_stash + off + (n0 + n) * 8); ldg2r(a[n][2], a[n][3], g_stash + off + 8 * DM + (n0 + n) * 8); }
#pragma unroll
    for (int n = 0; n < 8; n++)
#pragma unroll
      for (int half = 0; half < 2; half++)
        if (((a[n][2 * half] ^ epoch) & 3) == 0)
          *reinterpret_cast<uint32_t*>(out + off + half * 8 * DM + (n0 + n) * 8) =
              pack2(__uint_as_float(a[n][2 * half]) + d[4 * (n0 + n) + 2 * half], __uint_as_float(a[n][2 * half + 1]) + d[4 * (n0 + n) + 2 * half + 1]);
  }
}

__global__ void __launch_bounds__(384, 1)
ffn_kernel(const __grid_constant__ CUtensorMap tmX, const __grid_constant__ CUtensorMap tmW1,
           const __grid_constant__ CUtensorMap tmH, const __grid_constant__ CUtensorMap tmW2,
           const __nv_bfloat16* __restrict__ x, const __nv_bfloat16* __restrict__ gate_w, __nv_bfloat16* __restrict__ out) {
  extern __shared__ uint8_t smem_raw[];
  const uint32_t sb = (smem_u32(smem_raw) + 1023) & ~1023u;
  const uint32_t hbar = sb + F_BAR + 64;
  int dead = SPIN_LIMIT;
  const int tid = threadIdx.x, lane = tid & 31, warp = __shfl_sync(0xffffffffu, tid >> 5, 0), r0 = blockIdx.x * 128;
  if (tid == 0) {
    for (int i = 0; i < 4; i++) { mbar_init(sb + F_BAR + 8 * i, 1); mbar_init(sb + F_BAR + 32 + 8 * i, 16); }
    mbar_init(hbar, 256);
    asm volatile("fence.mbarrier_init.release.cluster;" ::: "memory");
    asm volatile("fence.proxy.async.shared::cta;" ::: "memory");
  }
  __syncthreads();
  cluster_arrive_relaxed();
  cluster_wait();
  if (warp >= 8) {
    asm volatile("setmaxnreg.dec.sync.aligned.u32 56;");
    if (tid == 256) {
      int it = 0;
#pragma unroll 1
      for (int t = 0; t < 9; t++) {
        const int nk = t < 7 ? 7 : 28, nb = t < 8 ? 4 : 3;
        if (t == 7) mbar_wait1(hbar, 0, dead);
#pragma unroll 1
        for (int k = 0; k < nk; k++, it++) {
          const int st = it & 3;
          const uint32_t fb = sb + F_BAR + 8 * st, a = sb + st * F_STAGE;
          if (it >= 4) mbar_wait1(fb + 32, ((it >> 2) - 1) & 1, dead);
          mbar_expect(fb, 16384 + nb * 8192);
          tma2d(a, t < 7 ? &tmX : &tmH, k * 64, r0, fb);
          for (int b = blockIdx.x & 1; b < nb; b += 2)
            asm volatile("cp.async.bulk.tensor.2d.shared::cluster.global.mbarrier::complete_tx::bytes.multicast::cluster [%0], [%1, {%2, %3}], [%4], %5;"
                         :: "r"(a + 16384 + b * 8192), "l"(t < 7 ? &tmW1 : &tmW2), "r"((t < 7 ? t : t - 7) * 256 + b * 64), "r"(k * 64), "r"(fb), "h"((uint16_t)3) : "memory");
        }
      }
    } else if (warp > 8) {
      const int l16 = lane & 15;
      for (int r = (warp - 9) * 2 + (lane >> 4); r < 132; r += 6) {
        const int rr = r < 128 ? r : 127;
        float z = 0.f;
#pragma unroll
        for (int k = 0; k < 7; k++) {
          const uint2 xv = *reinterpret_cast<const uint2*>(x + (r0 + rr) * DM + (k * 16 + l16) * 4);
          const uint2 gv = *reinterpret_cast<const uint2*>(gate_w + (k * 16 + l16) * 4);
          z = fmaf(bf_lo(xv.x), bf_lo(gv.x), z); z = fmaf(bf_hi(xv.x), bf_hi(gv.x), z);
          z = fmaf(bf_lo(xv.y), bf_lo(gv.y), z); z = fmaf(bf_hi(xv.y), bf_hi(gv.y), z);
        }
#pragma unroll
        for (int o = 1; o < 16; o <<= 1) z += __shfl_xor_sync(0xffffffffu, z, o);
        if (l16 == 0) sts32v(sb + F_G + rr * 4, __float_as_uint(1.f - rcp(1.f + ex2(-1.4426950408889634f * z))));
      }
      __syncwarp();
      bar_arrive(1, 352);
    }
    __syncwarp();
    cluster_arrive_relaxed();
    cluster_wait();
  } else {
    asm volatile("setmaxnreg.inc.sync.aligned.u32 224;");
    const int wg = warp >> 2, row = wg * 64 + (warp & 3) * 16 + (lane >> 2);
    const uint32_t epoch = (ldg1r(&g_ticket[1]) >> 4) + 1;
    int it = 0;
#pragma unroll 1
    for (int t = 0; t < 7; t++) {
      float d[128];
      ffn_tile<256>(d, sb, wg, 7, it, dead, lane);
      const uint32_t stg = sb + F_STG + warp * 2304;
      __nv_bfloat16* hp = g_h + (size_t)(r0 + warp * 16 + (lane >> 3)) * DFF + t * 256 + (lane & 7) * 8;
#pragma unroll
      for (int hf = 0; hf < 4; hf++) {
#pragma unroll
        for (int n = 0; n < 8; n += 2) {
          const float* e = d + 32 * hf + 4 * n;
          asm volatile("stmatrix.sync.aligned.m8n8.x4.shared.b16 [%0], {%1,%2,%3,%4};"
                       :: "r"(stg + (lane & 15) * 144 + (n + (lane >> 4)) * 16), "r"(pack2(fmaxf(e[0], 0.f), fmaxf(e[1], 0.f))), "r"(pack2(fmaxf(e[2], 0.f), fmaxf(e[3], 0.f))),
                          "r"(pack2(fmaxf(e[4], 0.f), fmaxf(e[5], 0.f))), "r"(pack2(fmaxf(e[6], 0.f), fmaxf(e[7], 0.f))) : "memory");
        }
        __syncwarp();
#pragma unroll
        for (int r = 0; r < 4; r++) {
          const uint4 v = lds_u4(stg + (4 * r + (lane >> 3)) * 144 + (lane & 7) * 16);
          *reinterpret_cast<uint4*>(hp + (size_t)4 * r * DFF + hf * 64) = v;
        }
        __syncwarp();
      }
    }
    __threadfence();
    asm volatile("fence.proxy.async;" ::: "memory");
    mbar_arrive(hbar);
    bar_sync(1, 352);
    const float g0 = __uint_as_float(lds32v(sb + F_G + row * 4)), g1 = __uint_as_float(lds32v(sb + F_G + row * 4 + 32));
    {
      float d[128];
      ffn_tile<256>(d, sb, wg, 28, it, dead, lane);
      ffn_finish<4>(d, g0, g1, sb, r0, row, 0, epoch, out, tid);
    }
    {
      float d[96];
      ffn_tile<192>(d, sb, wg, 28, it, dead, lane);
      ffn_finish<3>(d, g0, g1, sb, r0, row, 4, epoch, out, tid);
    }
    bar_sync(1, 256);
    if (tid == 0) atomicAdd(&g_ticket[1], 1);
    if (dead <= 0) g_err = 1;
    cluster_arrive_relaxed();
    cluster_wait();
  }
}

__device__ float g_fmem[8 * DM];
__global__ void fb_qkv(const __nv_bfloat16* x, const __nv_bfloat16* mem0, const __nv_bfloat16* wq, const __nv_bfloat16* wk,
                       const __nv_bfloat16* wv, int s) {
  __shared__ __nv_bfloat16 hs[40 * DM];
  for (int i = threadIdx.x; i < 40 * DM; i += 128)
    hs[i] = i >= 8 * DM ? x[s * 32 * DM + i - 8 * DM] : s ? __float2bfloat16(g_fmem[i]) : mem0[i];
  __syncthreads();
  const int col = blockIdx.x * 128 + threadIdx.x;
  const __nv_bfloat16* w = (blockIdx.y == 0 ? wq : blockIdx.y == 1 ? wk : wv) + col;
  float acc[40];
#pragma unroll
  for (int r = 0; r < 40; r++) acc[r] = 0.f;
  for (int d = 0; d < DM; d++) {
    const float wv_ = __bfloat162float(w[d * 4096]);
#pragma unroll
    for (int r = 0; r < 40; r++) acc[r] = fmaf(__bfloat162float(hs[r * DM + d]), wv_, acc[r]);
  }
#pragma unroll
  for (int r = 0; r < 40; r++) g_b[(blockIdx.y * 40 + r) * 4096 + col] = acc[r];
}
__global__ void fb_attn() {
  __shared__ float p[40];
  const int h = blockIdx.x, r = blockIdx.y, t = threadIdx.x;
  if (t < 40) {
    float a = 0.f;
    for (int e = 0; e < DH; e++) a = fmaf(g_b[r * 4096 + h * DH + e], g_b[(40 + t) * 4096 + h * DH + e], a);
    p[t] = (r < 8 || r >= t) ? a * 0.0625f : -1e9f;
  }
  __syncthreads();
  float mx = p[0], l = 0.f, o = 0.f;
  for (int k = 1; k < 40; k++) mx = fmaxf(mx, p[k]);
  for (int k = 0; k < 40; k++) { const float e = expf(p[k] - mx); l += e; o = fmaf(e, g_b[(80 + k) * 4096 + h * DH + t], o); }
  g_b[(120 + r) * 4096 + h * DH + t] = o / l;
}
__global__ void fb_out(const __nv_bfloat16* wo, int s) {
  const int r = blockIdx.x, c = threadIdx.x;
  float a = 0.f;
  for (int k = 0; k < 4096; k++) a = fmaf(g_b[(120 + r) * 4096 + k], __bfloat162float(wo[k * DM + c]), a);
  if (r < 8) g_fmem[r * DM + c] = a; else g_stash[(s * 32 + r - 8) * DM + c] = a;
}
__global__ void fb_ffn(const __nv_bfloat16* x, const __nv_bfloat16* w1, const __nv_bfloat16* w2, const __nv_bfloat16* gw, __nv_bfloat16* out) {
  __shared__ float xs[DM], hs[DFF];
  const int r = blockIdx.x, c = threadIdx.x;
  xs[c] = __bfloat162float(x[r * DM + c]);
  __syncthreads();
  float z = 0.f, b = 0.f;
  for (int d = 0; d < DM; d++) z = fmaf(xs[d], __bfloat162float(gw[d]), z);
  for (int f = c; f < DFF; f += DM) {
    float a = 0.f;
    for (int d = 0; d < DM; d++) a = fmaf(xs[d], __bfloat162float(w1[d * DFF + f]), a);
    hs[f] = fmaxf(a, 0.f);
  }
  __syncthreads();
  for (int f = 0; f < DFF; f++) b = fmaf(hs[f], __bfloat162float(w2[f * DM + c]), b);
  const float g = 1.f / (1.f + expf(-z));
  out[r * DM + c] = __float2bfloat16(g * g_stash[r * DM + c] + (1.f - g) * b);
}

typedef CUresult (*EncodeFn)(CUtensorMap*, CUtensorMapDataType, cuuint32_t, void*, const cuuint64_t*, const cuuint64_t*,
                             const cuuint32_t*, const cuuint32_t*, CUtensorMapInterleave, CUtensorMapSwizzle,
                             CUtensorMapL2promotion, CUtensorMapFloatOOBfill);

void make_map(EncodeFn fn, CUtensorMap* m, const void* p, uint64_t rows, uint64_t cols, uint32_t box_rows) {
  const cuuint64_t dims[2] = {cols, rows}, strides[1] = {cols * 2};
  const cuuint32_t box[2] = {64, box_rows}, es[2] = {1, 1};
  fn(m, CU_TENSOR_MAP_DATA_TYPE_BFLOAT16, 2, const_cast<void*>(p), dims, strides, box, es, CU_TENSOR_MAP_INTERLEAVE_NONE,
     CU_TENSOR_MAP_SWIZZLE_128B, CU_TENSOR_MAP_L2_PROMOTION_L2_256B, CU_TENSOR_MAP_FLOAT_OOB_FILL_NONE);
}

}

extern "C" void kernel_launch(void* const* d_in, const int* in_sizes, int n_in, void* d_out, int out_size) {
  (void)in_sizes; (void)n_in; (void)out_size;
  const __nv_bfloat16* x = (const __nv_bfloat16*)d_in[0];
  const __nv_bfloat16* mem0 = (const __nv_bfloat16*)d_in[1];
  const __nv_bfloat16* gate_w = (const __nv_bfloat16*)d_in[10];
  static EncodeFn fn = nullptr;
  static void* hptr = nullptr;
  static int mode = 0;
  cudaLaunchConfig_t cfg = {};
  cudaLaunchAttribute at[2];
  cfg.gridDim = dim3(112); cfg.blockDim = dim3(384); cfg.dynamicSmemBytes = T_SMEM; cfg.stream = cudaStreamPerThread;
  at[0].id = cudaLaunchAttributeClusterDimension;
  at[0].val.clusterDim.x = 16; at[0].val.clusterDim.y = 1; at[0].val.clusterDim.z = 1;
  cfg.attrs = at; cfg.numAttrs = 1;
  if (!mode) {
    cudaDriverEntryPointQueryResult qr;
    cudaGetDriverEntryPoint("cuTensorMapEncodeTiled", (void**)&fn, cudaEnableDefault, &qr);
    cudaGetSymbolAddress(&hptr, g_h);
    cudaFuncSetAttribute(rmt_kernel, cudaFuncAttributeMaxDynamicSharedMemorySize, T_SMEM);
    cudaFuncSetAttribute(rmt_kernel, cudaFuncAttributeNonPortableClusterSizeAllowed, 1);
    cudaFuncSetAttribute(ffn_kernel, cudaFuncAttributeMaxDynamicSharedMemorySize, F_SMEM);
    int ncl = 0;
    mode = fn && cudaOccupancyMaxActiveClusters(&ncl, rmt_kernel, &cfg) == cudaSuccess && ncl >= 7 ? 1 : 2;
    (void)cudaGetLastError();
  }
  if (mode == 2) {
    const __nv_bfloat16* const* in = (const __nv_bfloat16* const*)d_in;
    for (int s = 0; s < NSEG; s++) {
      fb_qkv<<<dim3(32, 3), 128, 0, cudaStreamPerThread>>>(x, mem0, in[2], in[3], in[4], s);
      fb_attn<<<dim3(NH, 40), DH, 0, cudaStreamPerThread>>>();
      fb_out<<<40, DM, 0, cudaStreamPerThread>>>(in[5], s);
    }
    fb_ffn<<<SEQ, DM, 0, cudaStreamPerThread>>>(x, in[8], in[9], gate_w, (__nv_bfloat16*)d_out);
    return;
  }
  CUtensorMap mWq, mWk, mWv, mWo, mX, mXf, mW1, mH, mW2;
  make_map(fn, &mWq, d_in[2], DM, NH * DH, 64);
  make_map(fn, &mWk, d_in[3], DM, NH * DH, 224);
  make_map(fn, &mWv, d_in[4], DM, NH * DH, 224);
  make_map(fn, &mWo, d_in[5], NH * DH, DM, 256);
  make_map(fn, &mX, x, SEQ, DM, 32);
  make_map(fn, &mXf, x, SEQ, DM, 128);
  make_map(fn, &mW1, d_in[8], DM, DFF, 64);
  make_map(fn, &mH, hptr, SEQ, DFF, 128);
  make_map(fn, &mW2, d_in[9], DFF, DM, 64);

  cudaLaunchKernelEx(&cfg, rmt_kernel, mWq, mWk, mWv, mWo, mX, x, mem0, gate_w, (__nv_bfloat16*)d_out);

  cfg.gridDim = dim3(16); cfg.dynamicSmemBytes = F_SMEM;
  at[0].val.clusterDim.x = 2;
  at[1].id = cudaLaunchAttributeProgrammaticStreamSerialization;
  at[1].val.programmaticStreamSerializationAllowed = 1;
  cfg.numAttrs = 2;
  cudaLaunchKernelEx(&cfg, ffn_kernel, mXf, mW1, mH, mW2, x, gate_w, (__nv_bfloat16*)d_out);
}
```
